```python
import torch

def _softmax(x, axis=-1):
    return torch.softmax(x, dim=axis)
def _gelu(x):
    return torch.nn.functional.gelu(x, approximate="tanh")
def _silu(x):
    return torch.nn.functional.silu(x)
def _sigmoid(x):
    return torch.sigmoid(x)
def _layernorm(x, axis=-1, eps=1e-5):
    m = x.mean(dim=axis, keepdim=True)
    v = x.var(dim=axis, keepdim=True, unbiased=False)
    return (x - m) / torch.sqrt(v + eps)
def _scatter_add(tgt, idx, src, axis=0):
    return tgt.clone().index_add_(axis, idx, src)
def _segment_sum(src, seg, n):
    out = torch.zeros((n,) + src.shape[1:], dtype=src.dtype)
    return out.index_add_(0, seg, src)
def _pad(x, pw):
    flat = tuple(v for pair in reversed(pw) for v in pair)
    return torch.nn.functional.pad(x, flat)

kernel_name = 'recurrent_scan__sliding_block_cached__moe_arch_mod__prompt'

def setup_inputs():

    _w = (lambda a: (lambda t: t.to(torch.bfloat16) if t.is_floating_point() else t)(torch.as_tensor(a)))
    def _A_setup():
        B, Sq, D = 1, 2048, 640
        Hq, Hkv, Sk, Dh = 32, 32, 2048, 192
        assert Hq % Hkv == 0, (Hq, Hkv)
        return {
            "x": _w((lambda *s: torch.randn(*s, dtype=torch.bfloat16) * 0.05)(B, Sq, D)),
            "k_cache": _w((lambda *s: torch.randn(*s, dtype=torch.bfloat16) * 0.8)(B, Hkv, Sk, Dh)),
            "v_cache": _w((lambda *s: torch.randn(*s, dtype=torch.bfloat16) * 0.2)(B, Hkv, Sk, Dh)),
            "wq": _w((lambda *s: torch.randn(*s, dtype=torch.bfloat16) * 0.8)(D, Hq * Dh) * (D ** -0.5)),
            "wo": _w((lambda *s: torch.randn(*s, dtype=torch.bfloat16) * 0.2)(Hq * Dh, D) * ((Hq * Dh) ** -0.5)),
        }
    _A_in = _A_setup()

    def _B_setup():
        B, S, D, F, C = 1, 2048, 640, 1536, 2
        return {
            "x": _w((lambda *s: torch.randn(*s, dtype=torch.bfloat16) * 0.05)(B, S, D)),
            "w_r": _w((lambda *s: torch.randn(*s, dtype=torch.bfloat16) * 0.2)(D)),
            "w_gate": _w((lambda *s: torch.randn(*s, dtype=torch.bfloat16) * 0.1)(D, F)),
            "w_up": _w((lambda *s: torch.randn(*s, dtype=torch.bfloat16) * 0.1)(D, F)),
            "w_down": _w((lambda *s: torch.randn(*s, dtype=torch.bfloat16) * 0.1)(F, D)),
        }
    _B_in = _B_setup()

    return {
        "A_x": _A_in["x"],
        "A_k_cache": _A_in["k_cache"],
        "A_v_cache": _A_in["v_cache"],
        "A_wq": _A_in["wq"],
        "A_wo": _A_in["wo"],
        "B_x": _B_in["x"],
        "B_w_r": _B_in["w_r"],
        "B_w_gate": _B_in["w_gate"],
        "B_w_up": _B_in["w_up"],
        "B_w_down": _B_in["w_down"],
    }

def reference(A_x, A_k_cache, A_v_cache, A_wq, A_wo, B_x, B_w_r, B_w_gate, B_w_up, B_w_down):
    def _A_ref(x, k_cache, v_cache, wq, wo):
        B, Sq, D = x.shape
        Hq, Dh = 32, 192
        Hkv, Sk = k_cache.shape[1], k_cache.shape[2]
        W = min(4096, max(256, Sk // 4))
        rep = Hq // Hkv
        q = (lambda x, *d: x.permute(*d))((x @ wq).reshape(B, Sq, Hq, Dh), 0, 2, 1, 3)
        k = (lambda x, n, axis: torch.repeat_interleave(x, n, dim=axis))(k_cache[:, :, Sk - W:, :], rep, axis=1)
        v = (lambda x, n, axis: torch.repeat_interleave(x, n, dim=axis))(v_cache[:, :, Sk - W:, :], rep, axis=1)
        scores = torch.einsum("bhqd,bhkd->bhqk", q, k) * (Dh ** -0.5)
        p = _softmax(scores, axis=-1)
        o = torch.einsum("bhqk,bhkd->bhqd", p, v)
        return (lambda x, *d: x.permute(*d))(o, 0, 2, 1, 3).reshape(B, Sq, Hq * Dh) @ wo

    def _B_ref(x, w_r, w_gate, w_up, w_down):
        B, S, D = x.shape
        C = 2
        r = x @ w_r
        idx = torch.argsort(-r, axis=-1)[:, :C]
        idx_e = (lambda x, n, axis: torch.repeat_interleave(x, n, dim=axis))(idx.reshape(B, C, 1), D, axis=2)
        x_sel = (lambda x, i, axis: torch.take_along_dim(x, i, dim=axis))(x, idx_e, axis=1)
        g = _silu(x_sel @ w_gate)
        u = x_sel @ w_up
        y = (g * u) @ w_down
        r_sel = _sigmoid((lambda x, i, axis: torch.take_along_dim(x, i, dim=axis))(r, idx, axis=1))
        y = y * r_sel.reshape(B, C, 1)
        b_off = (torch.arange(B) * S).reshape(B, 1)
        flat_idx = (idx + b_off).reshape(B * C)
        zero = (x * 0.0).reshape(B * S, D)
        upd = _scatter_add(zero, flat_idx, y.reshape(B * C, D), axis=0)
        return x + upd.reshape(B, S, D)

    x = A_x
    xn = _layernorm(x, axis=-1)
    s = _A_ref(xn, A_k_cache, A_v_cache, A_wq, A_wo)
    g = _silu(_B_ref(xn, B_w_r, B_w_gate, B_w_up, B_w_down))
    return x + s * g
```

```cpp
#include <cuda_runtime.h>
#include <cuda_bf16.h>
#include <cuda.h>
#include <stdint.h>

namespace {

constexpr int SQ = 2048, DM = 640, NH = 32, DH = 192, SKC = 2048, WIN = 512, FF = 1536;
constexpr int QD = NH * DH;
constexpr int NSLOT = 9;
constexpr uint32_t SLOT = 24576;
constexpr uint32_t SMEM_BYTES = NSLOT * SLOT + 1024 + 2048 + 5120;
constexpr uint32_t TA = 16384, TB = 20480, OFF_B = 5 * TA, OFF_X = OFF_B + 6 * TB, OFF_PK = 4 * TA;
constexpr int WAIT_BUDGET = 1 << 20;

constexpr int FL_XN = 0;
constexpr int FL_O = 512;
constexpr int FL_RD = FL_O + 1024;
constexpr int FL_FFN = FL_RD + 1024;
constexpr int FL_SIDE = FL_FFN + 32;
struct __align__(1024) Scratch {
  unsigned long long done, pad0[15];
  unsigned flag[FL_SIDE + 32];
  int sel[32];
  __nv_bfloat16 upd[2 * DM];
  float ffn[4 * 2 * DM];
  uint4 cs[8 * 8 * DH / 2];
  uint4 stat[SQ];
  __align__(1024) __nv_bfloat16 xn[SQ * DM];
  __align__(1024) uint4 o[SQ * QD / 8];
};
__device__ Scratch g_scratch;

__device__ __forceinline__ uint32_t smem_u32(const void* p) { return (uint32_t)__cvta_generic_to_shared(p); }
__device__ __forceinline__ void mbar_init(uint32_t bar, int cnt) { asm volatile("mbarrier.init.shared::cta.b64 [%0], %1;" ::"r"(bar), "r"(cnt)); }
__device__ __forceinline__ void mbar_expect_tx(uint32_t bar, uint32_t bytes) {
  asm volatile("mbarrier.arrive.expect_tx.shared::cta.b64 _, [%0], %1;" ::"r"(bar), "r"(bytes) : "memory");
}
__device__ __forceinline__ void mbar_arrive(uint32_t bar) { asm volatile("mbarrier.arrive.shared::cta.b64 _, [%0];" ::"r"(bar) : "memory"); }
__device__ __forceinline__ void mbar_arrive_cluster(uint32_t addr) { asm volatile("mbarrier.arrive.shared::cluster.b64 _, [%0];" ::"r"(addr) : "memory"); }
__device__ __forceinline__ bool mbar_try(uint32_t bar, uint32_t parity) {
  uint32_t ok;
  asm volatile("{\n.reg .pred p;\nmbarrier.try_wait.parity.shared::cta.b64 p, [%1], %2;\nselp.u32 %0, 1, 0, p;\n}\n" : "=r"(ok) : "r"(bar), "r"(parity) : "memory");
  return ok;
}
__device__ __forceinline__ void mbar_wait(uint32_t bar, uint32_t parity, int& budget) {
#pragma unroll 1
  while (!mbar_try(bar, parity)) { if (--budget < 0) break; }
}
__device__ __forceinline__ unsigned ld_acquire(const unsigned* p) { unsigned v; asm volatile("ld.acquire.gpu.global.u32 %0, [%1];" : "=r"(v) : "l"(p) : "memory"); return v; }
__device__ __forceinline__ void wait_flag(const unsigned* p, unsigned target, int& budget) {
#pragma unroll 1
  while (__any_sync(~0u, (int)(ld_acquire(p) - target) < 0)) { if (--budget < 0) break; }
}
__device__ __forceinline__ void red_release(unsigned* p) { asm volatile("red.release.gpu.global.add.u32 [%0], 1;" ::"l"(p) : "memory"); }
__device__ __forceinline__ void fence_proxy_async() { asm volatile("fence.proxy.async.global;" ::: "memory"); }
__device__ __forceinline__ bool elect() {
  uint32_t p;
  asm volatile("{\n.reg .pred P;\nelect.sync _|P, 0xffffffff;\nselp.u32 %0, 1, 0, P;\n}\n" : "=r"(p));
  return p;
}
__device__ __forceinline__ void cluster_arrive() { asm volatile("barrier.cluster.arrive.relaxed.aligned;" ::: "memory"); }
__device__ __forceinline__ void cluster_wait() { asm volatile("barrier.cluster.wait.aligned;" ::: "memory"); }
__device__ __forceinline__ void cluster_sync() { cluster_arrive(); cluster_wait(); }
__device__ __forceinline__ void tma2d(uint32_t dst, const CUtensorMap* tm, int c0, int c1, uint32_t bar) {
  asm volatile("cp.async.bulk.tensor.2d.shared::cluster.global.mbarrier::complete_tx::bytes [%0], [%1, {%3, %4}], [%2];"
               ::"r"(dst), "l"(tm), "r"(bar), "r"(c0), "r"(c1) : "memory");
}
constexpr uint64_t POL_FIRST = 0x12F0000000000000ull;
__device__ __forceinline__ void tma4d_mc(uint32_t dst, const CUtensorMap* tm, int c2, int c3, uint32_t bar) {
  asm volatile("cp.async.bulk.tensor.4d.shared::cluster.global.mbarrier::complete_tx::bytes.multicast::cluster.L2::cache_hint [%0], [%1, {%3, %3, %4, %5}], [%2], %6, %7;"
               ::"r"(dst), "l"(tm), "r"(bar), "r"(0), "r"(c2), "r"(c3), "h"((uint16_t)3), "l"(POL_FIRST) : "memory");
}
__device__ __forceinline__ void tma5d_mc(uint32_t dst, const CUtensorMap* tm, int c2, int c4, uint32_t bar) {
  asm volatile("cp.async.bulk.tensor.5d.shared::cluster.global.mbarrier::complete_tx::bytes.multicast::cluster.L2::cache_hint [%0], [%1, {%3, %3, %4, %3, %5}], [%2], %6, %7;"
               ::"r"(dst), "l"(tm), "r"(bar), "r"(0), "r"(c2), "r"(c4), "h"((uint16_t)3), "l"(POL_FIRST) : "memory");
}
__device__ __forceinline__ void bulk_load(uint32_t dst, const void* src, uint32_t bytes, uint32_t bar) {
  asm volatile("cp.async.bulk.shared::cluster.global.mbarrier::complete_tx::bytes.L2::cache_hint [%0], [%1], %2, [%3], %4;" ::"r"(dst), "l"(src), "r"(bytes), "r"(bar), "l"(POL_FIRST) : "memory");
}
__device__ __forceinline__ void tma2d_store(const CUtensorMap* tm, uint32_t src, int c0, int c1) {
  asm volatile("cp.async.bulk.tensor.2d.global.shared::cta.bulk_group [%0, {%2, %3}], [%1];" ::"l"(tm), "r"(src), "r"(c0), "r"(c1) : "memory");
}
__device__ __forceinline__ uint32_t lds32(uint32_t a) { uint32_t v; asm volatile("ld.shared.u32 %0, [%1];" : "=r"(v) : "r"(a) : "memory"); return v; }
__device__ __forceinline__ uint2 lds64(uint32_t a) { uint2 v; asm volatile("ld.shared.v2.u32 {%0,%1}, [%2];" : "=r"(v.x), "=r"(v.y) : "r"(a) : "memory"); return v; }
__device__ __forceinline__ uint4 lds128(uint32_t a) { uint4 v; asm volatile("ld.shared.v4.u32 {%0,%1,%2,%3}, [%4];" : "=r"(v.x), "=r"(v.y), "=r"(v.z), "=r"(v.w) : "r"(a) : "memory"); return v; }
__device__ __forceinline__ void sts32(uint32_t a, uint32_t v) { asm volatile("st.shared.u32 [%0], %1;" ::"r"(a), "r"(v) : "memory"); }
__device__ __forceinline__ void st_pkt(uint4* p, uint32_t a, uint32_t b, uint32_t c, uint32_t d) {
  asm volatile("{\n.reg .b128 v;\nmov.b128 v, {%1, %2, %3, %4};\nst.relaxed.gpu.global.b128 [%0], v;\n}\n" ::"l"(p), "r"(a), "r"(b), "r"(c), "r"(d) : "memory");
}
__device__ __forceinline__ uint4 ld_pkt(const uint4* p) {
  uint4 v;
  asm volatile("{\n.reg .b128 v;\nld.relaxed.gpu.global.b128 v, [%4];\nmov.b128 {%0, %1, %2, %3}, v;\n}\n" : "=r"(v.x), "=r"(v.y), "=r"(v.z), "=r"(v.w) : "l"(p) : "memory");
  return v;
}
__device__ __forceinline__ uint4 ldg_nc(const void* p) {
  uint4 v;
  asm volatile("ld.global.nc.v4.u32 {%0,%1,%2,%3}, [%4];" : "=r"(v.x), "=r"(v.y), "=r"(v.z), "=r"(v.w) : "l"(p));
  return v;
}
__device__ __forceinline__ uint4 ldg_stream(const void* p) {
  uint4 v;
  asm volatile("ld.global.nc.L1::no_allocate.L2::cache_hint.v4.u32 {%0,%1,%2,%3}, [%4], %5;" : "=r"(v.x), "=r"(v.y), "=r"(v.z), "=r"(v.w) : "l"(p), "l"(POL_FIRST));
  return v;
}
#define WG_FENCE() asm volatile("wgmma.fence.sync.aligned;" ::: "memory")
#define WG_COMMIT() asm volatile("wgmma.commit_group.sync.aligned;" ::: "memory")
#define WG_WAIT(n) asm volatile("wgmma.wait_group.sync.aligned " #n ";" ::: "memory")
template <int N> __device__ __forceinline__ void reg_fence(float (&d)[N]) {
#pragma unroll
  for (int i = 0; i < N; i++) asm volatile("" : "+f"(d[i])::"memory");
}
template <int N> __device__ __forceinline__ void reg_fence(uint32_t (&d)[N]) {
#pragma unroll
  for (int i = 0; i < N; i++) asm volatile("" : "+r"(d[i])::"memory");
}
__device__ __forceinline__ constexpr uint64_t desc_hi(uint32_t lbo, uint32_t sbo, uint64_t sw) {
  return ((uint64_t)(lbo >> 4) << 16) | ((uint64_t)(sbo >> 4) << 32) | (sw << 62);
}
__device__ __forceinline__ uint64_t mkdesc(uint32_t addr, uint64_t hi) { return hi | (uint64_t)((addr & 0x3FFFF) >> 4); }
__device__ __forceinline__ uint32_t pack_bf16(float lo, float hi) { uint32_t r; asm("cvt.rn.bf16x2.f32 %0, %1, %2;" : "=r"(r) : "f"(hi), "f"(lo)); return r; }
__device__ __forceinline__ float bf_lo(uint32_t v) { return __uint_as_float(v << 16); }
__device__ __forceinline__ float bf_hi(uint32_t v) { return __uint_as_float(v & 0xffff0000u); }
__device__ __forceinline__ uint32_t hadd2(uint32_t a, uint32_t b) { uint32_t r; asm("add.rn.bf16x2 %0, %1, %2;" : "=r"(r) : "r"(a), "r"(b)); return r; }
__device__ __forceinline__ uint32_t hsub2(uint32_t a, uint32_t b) { uint32_t r; asm("sub.rn.bf16x2 %0, %1, %2;" : "=r"(r) : "r"(a), "r"(b)); return r; }
__device__ __forceinline__ uint32_t hmul2(uint32_t a, uint32_t b) { uint32_t r; asm("mul.rn.bf16x2 %0, %1, %2;" : "=r"(r) : "r"(a), "r"(b)); return r; }
__device__ __forceinline__ float rbf(float x) { return __bfloat162float(__float2bfloat16_rn(x)); }
__device__ __forceinline__ float ex2(float x) { float y; asm("ex2.approx.ftz.f32 %0, %1;" : "=f"(y) : "f"(x)); return y; }
__device__ __forceinline__ float rcp(float x) { float y; asm("rcp.approx.ftz.f32 %0, %1;" : "=f"(y) : "f"(x)); return y; }
__device__ __forceinline__ float sigmoid_f(float x) { return rcp(1.f + ex2(x * -1.4426950408889634f)); }
__device__ __forceinline__ float silu_f(float x) { return x * sigmoid_f(x); }

__device__ __forceinline__ void wg_ss192t(float (&d)[96], uint64_t da, uint64_t db, int sd) {
  asm volatile("{\n.reg .pred p;\nsetp.ne.b32 p, %98, 0;\n"
    "wgmma.mma_async.sync.aligned.m64n192k16.f32.bf16.bf16 {%0,%1,%2,%3,%4,%5,%6,%7,%8,%9,%10,%11,%12,%13,%14,%15,%16,%17,%18,%19,%20,%21,%22,%23,%24,%25,%26,%27,%28,%29,%30,%31,%32,%33,%34,%35,%36,%37,%38,%39,%40,%41,%42,%43,%44,%45,%46,%47,%48,%49,%50,%51,%52,%53,%54,%55,%56,%57,%58,%59,%60,%61,%62,%63,%64,%65,%66,%67,%68,%69,%70,%71,%72,%73,%74,%75,%76,%77,%78,%79,%80,%81,%82,%83,%84,%85,%86,%87,%88,%89,%90,%91,%92,%93,%94,%95}, %96, %97, p, 1, 1, 0, 1;\n}\n"
    : "+f"(d[0]),"+f"(d[1]),"+f"(d[2]),"+f"(d[3]),"+f"(d[4]),"+f"(d[5]),"+f"(d[6]),"+f"(d[7]),"+f"(d[8]),"+f"(d[9]),"+f"(d[10]),"+f"(d[11]),"+f"(d[12]),"+f"(d[13]),"+f"(d[14]),"+f"(d[15]),"+f"(d[16]),"+f"(d[17]),"+f"(d[18]),"+f"(d[19]),"+f"(d[20]),"+f"(d[21]),"+f"(d[22]),"+f"(d[23]),"+f"(d[24]),"+f"(d[25]),"+f"(d[26]),"+f"(d[27]),"+f"(d[28]),"+f"(d[29]),"+f"(d[30]),"+f"(d[31]),"+f"(d[32]),"+f"(d[33]),"+f"(d[34]),"+f"(d[35]),"+f"(d[36]),"+f"(d[37]),"+f"(d[38]),"+f"(d[39]),"+f"(d[40]),"+f"(d[41]),"+f"(d[42]),"+f"(d[43]),"+f"(d[44]),"+f"(d[45]),"+f"(d[46]),"+f"(d[47]),"+f"(d[48]),"+f"(d[49]),"+f"(d[50]),"+f"(d[51]),"+f"(d[52]),"+f"(d[53]),"+f"(d[54]),"+f"(d[55]),"+f"(d[56]),"+f"(d[57]),"+f"(d[58]),"+f"(d[59]),"+f"(d[60]),"+f"(d[61]),"+f"(d[62]),"+f"(d[63]),"+f"(d[64]),"+f"(d[65]),"+f"(d[66]),"+f"(d[67]),"+f"(d[68]),"+f"(d[69]),"+f"(d[70]),"+f"(d[71]),"+f"(d[72]),"+f"(d[73]),"+f"(d[74]),"+f"(d[75]),"+f"(d[76]),"+f"(d[77]),"+f"(d[78]),"+f"(d[79]),"+f"(d[80]),"+f"(d[81]),"+f"(d[82]),"+f"(d[83]),"+f"(d[84]),"+f"(d[85]),"+f"(d[86]),"+f"(d[87]),"+f"(d[88]),"+f"(d[89]),"+f"(d[90]),"+f"(d[91]),"+f"(d[92]),"+f"(d[93]),"+f"(d[94]),"+f"(d[95])
    : "l"(da), "l"(db), "r"(sd));
}
__device__ __forceinline__ void wg_rs64(float (&d)[32], uint32_t a0, uint32_t a1, uint32_t a2, uint32_t a3, uint64_t db, int sd) {
  asm volatile("{\n.reg .pred p;\nsetp.ne.b32 p, %37, 0;\n"
    "wgmma.mma_async.sync.aligned.m64n64k16.f32.bf16.bf16 {%0,%1,%2,%3,%4,%5,%6,%7,%8,%9,%10,%11,%12,%13,%14,%15,%16,%17,%18,%19,%20,%21,%22,%23,%24,%25,%26,%27,%28,%29,%30,%31}, {%32,%33,%34,%35}, %36, p, 1, 1, 0;\n}\n"
    : "+f"(d[0]),"+f"(d[1]),"+f"(d[2]),"+f"(d[3]),"+f"(d[4]),"+f"(d[5]),"+f"(d[6]),"+f"(d[7]),"+f"(d[8]),"+f"(d[9]),"+f"(d[10]),"+f"(d[11]),"+f"(d[12]),"+f"(d[13]),"+f"(d[14]),"+f"(d[15]),"+f"(d[16]),"+f"(d[17]),"+f"(d[18]),"+f"(d[19]),"+f"(d[20]),"+f"(d[21]),"+f"(d[22]),"+f"(d[23]),"+f"(d[24]),"+f"(d[25]),"+f"(d[26]),"+f"(d[27]),"+f"(d[28]),"+f"(d[29]),"+f"(d[30]),"+f"(d[31])
    : "r"(a0), "r"(a1), "r"(a2), "r"(a3), "l"(db), "r"(sd));
}
__device__ __forceinline__ void wg_rs192t(float (&d)[96], uint32_t a0, uint32_t a1, uint32_t a2, uint32_t a3, uint64_t db, int sd) {
  asm volatile("{\n.reg .pred p;\nsetp.ne.b32 p, %101, 0;\n"
    "wgmma.mma_async.sync.aligned.m64n192k16.f32.bf16.bf16 {%0,%1,%2,%3,%4,%5,%6,%7,%8,%9,%10,%11,%12,%13,%14,%15,%16,%17,%18,%19,%20,%21,%22,%23,%24,%25,%26,%27,%28,%29,%30,%31,%32,%33,%34,%35,%36,%37,%38,%39,%40,%41,%42,%43,%44,%45,%46,%47,%48,%49,%50,%51,%52,%53,%54,%55,%56,%57,%58,%59,%60,%61,%62,%63,%64,%65,%66,%67,%68,%69,%70,%71,%72,%73,%74,%75,%76,%77,%78,%79,%80,%81,%82,%83,%84,%85,%86,%87,%88,%89,%90,%91,%92,%93,%94,%95}, {%96,%97,%98,%99}, %100, p, 1, 1, 1;\n}\n"
    : "+f"(d[0]),"+f"(d[1]),"+f"(d[2]),"+f"(d[3]),"+f"(d[4]),"+f"(d[5]),"+f"(d[6]),"+f"(d[7]),"+f"(d[8]),"+f"(d[9]),"+f"(d[10]),"+f"(d[11]),"+f"(d[12]),"+f"(d[13]),"+f"(d[14]),"+f"(d[15]),"+f"(d[16]),"+f"(d[17]),"+f"(d[18]),"+f"(d[19]),"+f"(d[20]),"+f"(d[21]),"+f"(d[22]),"+f"(d[23]),"+f"(d[24]),"+f"(d[25]),"+f"(d[26]),"+f"(d[27]),"+f"(d[28]),"+f"(d[29]),"+f"(d[30]),"+f"(d[31]),"+f"(d[32]),"+f"(d[33]),"+f"(d[34]),"+f"(d[35]),"+f"(d[36]),"+f"(d[37]),"+f"(d[38]),"+f"(d[39]),"+f"(d[40]),"+f"(d[41]),"+f"(d[42]),"+f"(d[43]),"+f"(d[44]),"+f"(d[45]),"+f"(d[46]),"+f"(d[47]),"+f"(d[48]),"+f"(d[49]),"+f"(d[50]),"+f"(d[51]),"+f"(d[52]),"+f"(d[53]),"+f"(d[54]),"+f"(d[55]),"+f"(d[56]),"+f"(d[57]),"+f"(d[58]),"+f"(d[59]),"+f"(d[60]),"+f"(d[61]),"+f"(d[62]),"+f"(d[63]),"+f"(d[64]),"+f"(d[65]),"+f"(d[66]),"+f"(d[67]),"+f"(d[68]),"+f"(d[69]),"+f"(d[70]),"+f"(d[71]),"+f"(d[72]),"+f"(d[73]),"+f"(d[74]),"+f"(d[75]),"+f"(d[76]),"+f"(d[77]),"+f"(d[78]),"+f"(d[79]),"+f"(d[80]),"+f"(d[81]),"+f"(d[82]),"+f"(d[83]),"+f"(d[84]),"+f"(d[85]),"+f"(d[86]),"+f"(d[87]),"+f"(d[88]),"+f"(d[89]),"+f"(d[90]),"+f"(d[91]),"+f"(d[92]),"+f"(d[93]),"+f"(d[94]),"+f"(d[95])
    : "r"(a0), "r"(a1), "r"(a2), "r"(a3), "l"(db), "r"(sd));
}
__device__ __forceinline__ void wg_ss160t(float (&d)[80], uint64_t da, uint64_t db, int sd) {
  asm volatile("{\n.reg .pred p;\nsetp.ne.b32 p, %82, 0;\n"
    "wgmma.mma_async.sync.aligned.m64n160k16.f32.bf16.bf16 {%0,%1,%2,%3,%4,%5,%6,%7,%8,%9,%10,%11,%12,%13,%14,%15,%16,%17,%18,%19,%20,%21,%22,%23,%24,%25,%26,%27,%28,%29,%30,%31,%32,%33,%34,%35,%36,%37,%38,%39,%40,%41,%42,%43,%44,%45,%46,%47,%48,%49,%50,%51,%52,%53,%54,%55,%56,%57,%58,%59,%60,%61,%62,%63,%64,%65,%66,%67,%68,%69,%70,%71,%72,%73,%74,%75,%76,%77,%78,%79}, %80, %81, p, 1, 1, 0, 1;\n}\n"
    : "+f"(d[0]),"+f"(d[1]),"+f"(d[2]),"+f"(d[3]),"+f"(d[4]),"+f"(d[5]),"+f"(d[6]),"+f"(d[7]),"+f"(d[8]),"+f"(d[9]),"+f"(d[10]),"+f"(d[11]),"+f"(d[12]),"+f"(d[13]),"+f"(d[14]),"+f"(d[15]),"+f"(d[16]),"+f"(d[17]),"+f"(d[18]),"+f"(d[19]),"+f"(d[20]),"+f"(d[21]),"+f"(d[22]),"+f"(d[23]),"+f"(d[24]),"+f"(d[25]),"+f"(d[26]),"+f"(d[27]),"+f"(d[28]),"+f"(d[29]),"+f"(d[30]),"+f"(d[31]),"+f"(d[32]),"+f"(d[33]),"+f"(d[34]),"+f"(d[35]),"+f"(d[36]),"+f"(d[37]),"+f"(d[38]),"+f"(d[39]),"+f"(d[40]),"+f"(d[41]),"+f"(d[42]),"+f"(d[43]),"+f"(d[44]),"+f"(d[45]),"+f"(d[46]),"+f"(d[47]),"+f"(d[48]),"+f"(d[49]),"+f"(d[50]),"+f"(d[51]),"+f"(d[52]),"+f"(d[53]),"+f"(d[54]),"+f"(d[55]),"+f"(d[56]),"+f"(d[57]),"+f"(d[58]),"+f"(d[59]),"+f"(d[60]),"+f"(d[61]),"+f"(d[62]),"+f"(d[63]),"+f"(d[64]),"+f"(d[65]),"+f"(d[66]),"+f"(d[67]),"+f"(d[68]),"+f"(d[69]),"+f"(d[70]),"+f"(d[71]),"+f"(d[72]),"+f"(d[73]),"+f"(d[74]),"+f"(d[75]),"+f"(d[76]),"+f"(d[77]),"+f"(d[78]),"+f"(d[79])
    : "l"(da), "l"(db), "r"(sd));
}

struct Ring {
  uint32_t slot, phase;
  __device__ __forceinline__ void next() { if (++slot == NSLOT) { slot = 0; phase ^= 1; } }
};

struct Params {
  const __nv_bfloat16 *x, *wr, *wg, *wu, *wd, *k, *v;
  Scratch* s;
};

__device__ __forceinline__ void side_cta(const Params& p, int sc, unsigned epoch, float* sm) {
  const int tid = threadIdx.x;
  int budget = WAIT_BUDGET;
  float* s_x = sm;
  float* s_red = sm + 1280;
  float* s_h = s_red + 6144;
  float* s_v = s_h + 768;
  int* s_i = (int*)(s_v + 32);
  float v0 = -INFINITY, v1 = -INFINITY; int i0 = 0x7fffffff, i1 = 0x7fffffff;
  auto better = [](float a, int ia, float b, int ib) { return a > b || (a == b && ia < ib); };
  auto push = [&](float v, int i) {
    if (better(v, i, v0, i0)) { v1 = v0; i1 = i0; v0 = v; i0 = i; }
    else if (better(v, i, v1, i1)) { v1 = v; i1 = i; }
  };
#pragma unroll 1
  for (int i = tid; i < SQ; i += 384) {
    uint4 v;
    do v = ld_pkt(p.s->stat + i); while (v.w != epoch + 1 && --budget >= 0);
    push(__uint_as_float(v.z), i);
  }
  __syncwarp();
#pragma unroll
  for (int o = 16; o > 0; o >>= 1) {
    float a0 = __shfl_xor_sync(~0u, v0, o), a1 = __shfl_xor_sync(~0u, v1, o);
    int b0 = __shfl_xor_sync(~0u, i0, o), b1 = __shfl_xor_sync(~0u, i1, o);
    push(a0, b0); push(a1, b1);
  }
  if ((tid & 31) == 0) { int w = tid >> 5; s_v[2 * w] = v0; s_v[2 * w + 1] = v1; s_i[2 * w] = i0; s_i[2 * w + 1] = i1; }
  __syncthreads();
  v0 = v1 = -INFINITY; i0 = i1 = 0x7fffffff;
  for (int w = 0; w < 24; w++) push(s_v[w], s_i[w]);
  if (i0 >= SQ) i0 = 0;
  if (i1 >= SQ) i1 = (i0 == 0) ? 1 : 0;
  for (int i = tid; i < 2 * DM; i += 384) {
    const int row = i < DM ? i0 : i1;
    const uint4 st = ld_pkt(p.s->stat + row);
    const uint32_t u = __ldg((const unsigned short*)p.x + (size_t)row * DM + i % DM);
    s_x[i] = rbf(bf_lo(hsub2(u, st.x)) * __uint_as_float(st.y));
  }
  __syncthreads();
  {
    const int cg = tid % 96, ks = tid / 96;
    const __nv_bfloat16* w = (cg < 48 ? p.wg : p.wu) + (size_t)(ks * 160) * FF + sc * 384 + (cg % 48) * 8;
    float a[2][8];
#pragma unroll
    for (int i = 0; i < 8; i++) a[0][i] = a[1][i] = 0.f;
#pragma unroll 16
    for (int k = 0; k < 160; k++) {
      uint4 v = ldg_stream(w + (size_t)k * FF);
      float x0 = s_x[ks * 160 + k], x1 = s_x[DM + ks * 160 + k];
      uint32_t u[4] = {v.x, v.y, v.z, v.w};
#pragma unroll
      for (int i = 0; i < 4; i++) {
        a[0][2 * i] += x0 * bf_lo(u[i]); a[0][2 * i + 1] += x0 * bf_hi(u[i]);
        a[1][2 * i] += x1 * bf_lo(u[i]); a[1][2 * i + 1] += x1 * bf_hi(u[i]);
      }
    }
#pragma unroll
    for (int t = 0; t < 2; t++)
#pragma unroll
      for (int i = 0; i < 8; i++) s_red[(ks * 2 + t) * 768 + cg * 8 + i] = a[t][i];
  }
  __syncthreads();
  for (int i = tid; i < 768; i += 384) {
    int t = i / 384, c = i % 384;
    float g = 0.f, u = 0.f;
#pragma unroll
    for (int ks = 0; ks < 4; ks++) { g += s_red[(ks * 2 + t) * 768 + c]; u += s_red[(ks * 2 + t) * 768 + 384 + c]; }
    s_h[i] = rbf(rbf(silu_f(rbf(g))) * rbf(u));
  }
  __syncthreads();
  if (tid < 320) {
    const int cg = tid % 80, ks = tid / 80;
    const __nv_bfloat16* w = p.wd + (size_t)(sc * 384 + ks * 96) * DM + cg * 8;
    float a[2][8];
#pragma unroll
    for (int i = 0; i < 8; i++) a[0][i] = a[1][i] = 0.f;
#pragma unroll 16
    for (int k = 0; k < 96; k++) {
      uint4 v = ldg_stream(w + (size_t)k * DM);
      float x0 = s_h[ks * 96 + k], x1 = s_h[384 + ks * 96 + k];
      uint32_t u[4] = {v.x, v.y, v.z, v.w};
#pragma unroll
      for (int i = 0; i < 4; i++) {
        a[0][2 * i] += x0 * bf_lo(u[i]); a[0][2 * i + 1] += x0 * bf_hi(u[i]);
        a[1][2 * i] += x1 * bf_lo(u[i]); a[1][2 * i + 1] += x1 * bf_hi(u[i]);
      }
    }
#pragma unroll
    for (int t = 0; t < 2; t++)
#pragma unroll
      for (int i = 0; i < 8; i++) s_red[(ks * 2 + t) * 768 + cg * 8 + i] = a[t][i];
  }
  __syncthreads();
  for (int i = tid; i < 2 * DM; i += 384) {
    int t = i / DM, c = i % DM;
    p.s->ffn[sc * 2 * DM + i] = s_red[t * 768 + c] + s_red[(2 + t) * 768 + c] + s_red[(4 + t) * 768 + c] + s_red[(6 + t) * 768 + c];
  }
  __syncthreads();
  if (tid == 0) { __threadfence(); s_i[0] = (atomicAdd(&p.s->flag[FL_SIDE], 1u) & 3u) == 3u; __threadfence(); }
  __syncthreads();
  if (s_i[0]) {
    const float rs0 = rbf(sigmoid_f(v0)), rs1 = rbf(sigmoid_f(v1));
    for (int i = tid; i < 2 * DM; i += 384) {
      const float y = __ldcg(&p.s->ffn[i]) + __ldcg(&p.s->ffn[2 * DM + i]) + __ldcg(&p.s->ffn[4 * DM + i]) + __ldcg(&p.s->ffn[6 * DM + i]);
      p.s->upd[i] = __float2bfloat16_rn(rbf(y) * (i < DM ? rs0 : rs1));
    }
    if (tid == 0) { p.s->sel[0] = i0; p.s->sel[1] = i1; }
    __syncthreads();
    if (tid == 0) red_release(&p.s->flag[FL_FFN]);
  }
}

constexpr float SM_C = 0.07216878364870322f * 1.4426950408889634f;

__device__ __forceinline__ float half_sum(float v) {
#pragma unroll
  for (int o = 8; o > 0; o >>= 1) v += __shfl_xor_sync(~0u, v, o);
  return v;
}
__device__ __forceinline__ void ln_row(const Params& p, uint32_t (&uu)[40], int row, int l16, uint32_t tag) {
  const uint32_t* ww = uu + 20;
  const float x0 = bf_lo(__shfl_sync(~0u, uu[0], 0, 16));
  float s0 = 0.f, s1 = 0.f, q0 = 0.f, q1 = 0.f;
#pragma unroll
  for (int i = 0; i < 20; i++) {
    const float a = bf_lo(uu[i]) - x0, b = bf_hi(uu[i]) - x0;
    s0 += a; s1 += b; q0 = fmaf(a, a, q0); q1 = fmaf(b, b, q1);
  }
  s0 += s1; q0 += q1;
#pragma unroll
  for (int o = 8; o > 0; o >>= 1) { s0 += __shfl_xor_sync(~0u, s0, o); q0 += __shfl_xor_sync(~0u, q0, o); }
  s0 *= 1.f / DM;
  const float mean = x0 + s0, var = rbf(fmaxf(fmaf(q0, 1.f / DM, -s0 * s0), 0.f));
  float sd; asm("sqrt.approx.ftz.f32 %0, %1;" : "=f"(sd) : "f"(rbf(var + 1e-5f)));
  const float inv = rcp(rbf(sd)), invc = inv * SM_C;
  const __nv_bfloat162 mb = __float2bfloat162_rn(mean);
  float r = 0.f, r1 = 0.f;
#pragma unroll
  for (int i = 0; i < 20; i++) {
    __nv_bfloat162 d = __hsub2(*reinterpret_cast<__nv_bfloat162*>(&uu[i]), mb);
    const uint32_t du = *reinterpret_cast<uint32_t*>(&d);
    const uint32_t xn = pack_bf16(bf_lo(du) * inv, bf_hi(du) * inv);
    r = fmaf(bf_lo(xn), bf_lo(ww[i]), r); r1 = fmaf(bf_hi(xn), bf_hi(ww[i]), r1);
    uu[i] = pack_bf16(bf_lo(du) * invc, bf_hi(du) * invc);
  }
#pragma unroll
  for (int i = 0; i < 5; i++) *((uint4*)(p.s->xn + (size_t)row * DM) + i * 16 + l16) = make_uint4(uu[4 * i], uu[4 * i + 1], uu[4 * i + 2], uu[4 * i + 3]);
  r = half_sum(r + r1);
  if (l16 == 0) st_pkt(&p.s->stat[row], *reinterpret_cast<const uint32_t*>(&mb), __float_as_uint(inv), __float_as_uint(rbf(r)), tag);
}

constexpr float SM_HI = 0x1p64f, SM_LO = 0x1p-64f;
__device__ __forceinline__ void exp_block(float (&s)[32], float& l0, float& l1) {
#pragma unroll
  for (int i = 0; i < 32; i++) { s[i] = ex2(s[i]); if (i & 2) l1 += s[i]; else l0 += s[i]; }
}
__device__ __forceinline__ float quad_sum(float v) { v += __shfl_xor_sync(~0u, v, 1); return v + __shfl_xor_sync(~0u, v, 2); }
__device__ __forceinline__ float quad_max(float v) { v = fmaxf(v, __shfl_xor_sync(~0u, v, 1)); return fmaxf(v, __shfl_xor_sync(~0u, v, 2)); }
__device__ __forceinline__ void safe_head(const uint32_t* kp, const uint32_t* vp, const uint32_t (&fq)[48], float (&o)[96], float& l0, float& l1) {
  float m0 = -INFINITY, m1 = -INFINITY;
  l0 = l1 = 0.f;
#pragma unroll
  for (int c = 0; c < 24; c++)
    asm volatile("mma.sync.aligned.m16n8k8.row.col.f32.bf16.bf16.f32 {%0,%1,%2,%3}, {%4,%4}, {%4}, {%5,%5,%5,%5};"
                 : "=f"(o[4 * c]), "=f"(o[4 * c + 1]), "=f"(o[4 * c + 2]), "=f"(o[4 * c + 3]) : "r"(0), "f"(0.f));
#pragma unroll 1
  for (int n = 0; n < 128; n++) {
    const uint32_t *kr = kp + (n & 63) * (8 * DH / 2), *vr = vp + (n & 63) * (8 * DH / 2);
    float d[4] = {};
#pragma unroll
    for (int t = 0; t < 12; t++)
      asm volatile("mma.sync.aligned.m16n8k16.row.col.f32.bf16.bf16.f32 {%0,%1,%2,%3}, {%4,%5,%6,%7}, {%8,%9}, {%0,%1,%2,%3};"
                   : "+f"(d[0]), "+f"(d[1]), "+f"(d[2]), "+f"(d[3])
                   : "r"(fq[4 * t]), "r"(fq[4 * t + 1]), "r"(fq[4 * t + 2]), "r"(fq[4 * t + 3]), "r"(__ldg(kr + 8 * t)), "r"(__ldg(kr + 8 * t + 4)));
    if (n < 64) { m0 = quad_max(fmaxf(m0, fmaxf(d[0], d[1]))); m1 = quad_max(fmaxf(m1, fmaxf(d[2], d[3]))); continue; }
    d[0] = ex2(d[0] - m0); d[1] = ex2(d[1] - m0); d[2] = ex2(d[2] - m1); d[3] = ex2(d[3] - m1);
    l0 += quad_sum(d[0] + d[1]); l1 += quad_sum(d[2] + d[3]);
    const uint32_t p0 = pack_bf16(d[0], d[1]), p1 = pack_bf16(d[2], d[3]);
#pragma unroll
    for (int c = 0; c < 24; c++)
      asm volatile("{\n.reg .b32 t;\nmovmatrix.sync.aligned.m8n8.trans.b16 t, %6;\n"
                   "mma.sync.aligned.m16n8k8.row.col.f32.bf16.bf16.f32 {%0,%1,%2,%3}, {%4,%5}, {t}, {%0,%1,%2,%3};\n}\n"
                   : "+f"(o[4 * c]), "+f"(o[4 * c + 1]), "+f"(o[4 * c + 2]), "+f"(o[4 * c + 3]) : "r"(p0), "r"(p1), "r"(__ldg(vr + 4 * c)));
  }
}

__global__ void __launch_bounds__(384, 1)
fused_kernel(const Params p, const __grid_constant__ CUtensorMap tm_x, const __grid_constant__ CUtensorMap tm_xn,
             const __grid_constant__ CUtensorMap tm_wq, const __grid_constant__ CUtensorMap tm_k,
             const __grid_constant__ CUtensorMap tm_v, const __grid_constant__ CUtensorMap tm_wo,
             const __grid_constant__ CUtensorMap tm_xe, const __grid_constant__ CUtensorMap tm_out) {
  extern __shared__ __align__(1024) uint8_t smem_raw[];
  const uint32_t sb = (smem_u32(smem_raw) + 1023) & ~1023u;
  const uint32_t bar_full = sb + NSLOT * SLOT, bar_empty = bar_full + 8 * NSLOT, bar_o = bar_empty + 8 * NSLOT;
  const uint32_t bar_u = bar_o + 8, bar_z = bar_o + 16, bar_s = bar_o + 24, bar_p = bar_o + 32, bar_d = bar_o + 40,
                 bar_q = bar_o + 48, bar_r = bar_o + 56, bar_e = bar_o + 64;
  const uint32_t s_misc = bar_full + 256;
  const uint32_t bar_a = bar_full + 1792, bar_b = bar_a + 80;
  auto x_block = [&](int c) { return c < 6 ? sb + OFF_X + c * 2560 : bar_full + 2048 + (c - 6) * 2560; };
  const int wg = __shfl_sync(~0u, threadIdx.x >> 7, 0);
  const int lane = threadIdx.x & 31;
  const int cl = blockIdx.x >> 1;
  const int rank = blockIdx.x & 1;
  int budget = WAIT_BUDGET;

  if (cl >= 64) {
    const unsigned epoch = (unsigned)(__ldcg(&p.s->done) >> 7);
    side_cta(p, blockIdx.x - 128, epoch, (float*)(smem_raw + (sb - smem_u32(smem_raw))));
    return;
  }
  const int qt = (cl >> 3) * 2 + rank, hg = cl & 7;
  const int kq = hg >> 1, nh = hg & 1;

  if (threadIdx.x == 0) {
    asm volatile("prefetch.tensormap [%0];" ::"l"(&tm_wq) : "memory");
    asm volatile("prefetch.tensormap [%0];" ::"l"(&tm_x) : "memory");
    for (int i = 0; i < NSLOT; i++) { mbar_init(bar_full + 8 * i, 1); mbar_init(bar_empty + 8 * i, 16); }
  }
  if (threadIdx.x == 33) {
    mbar_init(bar_o, 8); mbar_init(bar_u, 1); mbar_init(bar_z, 1); mbar_init(bar_s, 3); mbar_init(bar_p, 1); mbar_init(bar_d, 3);
    mbar_init(bar_q, 1); mbar_init(bar_r, 8);
    for (int i = 0; i < 3; i++) mbar_init(bar_e + 8 * i, 1);
  }
  asm volatile("fence.mbarrier_init.release.cluster;" ::: "memory");
  cluster_arrive();
  uint32_t xw[40];
  unsigned long long done = 0;
  const int lnrow = qt * 128 + hg * 16 + ((int)(threadIdx.x >> 5) - 4) * 2 + (lane >> 4);
  uint32_t cons; asm volatile("{\n.reg .pred q;\nsetp.ne.u32 q, %1, 0;\nselp.u32 %0, 1, 0, q;\n}" : "=r"(cons) : "r"(wg));
  if (cons) {
#pragma unroll
    for (int i = 0; i < 10; i++) {
      const uint4 v = ldg_nc((const uint4*)(i < 5 ? p.x + (size_t)lnrow * DM : p.wr) + (i % 5) * 16 + (lane & 15));
      xw[4 * i] = v.x; xw[4 * i + 1] = v.y; xw[4 * i + 2] = v.z; xw[4 * i + 3] = v.w;
    }
    asm volatile("ld.relaxed.gpu.global.u64 %0, [%1];" : "=l"(done) : "l"(&p.s->done));
  }
  if (wg > 0) {
    const int w = wg - 1;
    const int cw = (threadIdx.x >> 5) - 4;
    asm volatile("setmaxnreg.inc.sync.aligned.u32 232;");
    {
      cluster_wait();
      ln_row(p, xw, lnrow, lane & 15, (unsigned)(done >> 7) + 1);
      __syncwarp();
      if (lane == 0) mbar_arrive(bar_o);
    }
    uint32_t rel_addr;
    asm volatile("mapa.shared::cluster.u32 %0, %1, %2;" : "=r"(rel_addr) : "r"(bar_empty), "r"(lane & 1));
    auto release = [&](uint32_t slot) { if (lane < 2) mbar_arrive_cluster(rel_addr + 8 * slot); };
    const int g = lane >> 2, q = lane & 3;
    const uint32_t row0 = qt * 128 + w * 64 + (cw & 3) * 16 + g;
    constexpr uint64_t HI_A = desc_hi(16, 1024, 1);
    constexpr uint64_t HI_W = desc_hi(1024, 3072, 1);
    constexpr uint64_t HI_O = desc_hi(2048, 512, 2);
    if (w == 1) asm volatile("bar.arrive 1, 256;" ::: "memory");

    uint32_t zero; asm volatile("mov.u32 %0, %%tid.y;" : "=r"(zero));
    float acc[96];
    uint32_t fr[48];
    uint4* optr = p.s->o + (size_t)(qt * 192 + hg * 24) * 512 + (cw * 16 + g) * 4 + (q ^ ((g >> 1) & 3));
    auto store_o = [&](int pp) {
#pragma unroll
      for (int i = (12 * pp + 8) / 9; i < (12 * (pp + 1) + 8) / 9; i++)
        optr[(i >> 1) * 512 + (i & 1) * 32] = make_uint4(fr[4 * i], fr[4 * i + 1], fr[4 * i + 2], fr[4 * i + 3]);
      if (pp == 8) { __syncwarp(); if (lane == 0) mbar_arrive(bar_o); optr += 6 * 512; }
    };
    auto fresh = [&]() { uint32_t v = sb; asm volatile("" : "+r"(v)); return v; };

#pragma unroll 1
    for (int u = 0; u < 4; u++) {
      const uint32_t sq = fresh();
      const uint64_t dA = mkdesc(sq + w * 8192, HI_A), dW = mkdesc(sq, HI_W);
#pragma unroll
      for (int s = 0; s < 10; s++) {
        const int sa = (2 * s) % NSLOT, sw = (2 * s + 1) % NSLOT;
        mbar_wait(bar_full + 8 * sa, ((2 * s) / NSLOT) & 1, budget);
        mbar_wait(bar_full + 8 * sw, ((2 * s + 1) / NSLOT) & 1, budget);
        if (s == 9) asm volatile("bar.sync %0, 256;" ::"r"(1 + w) : "memory");
        WG_FENCE();
#pragma unroll
        for (int kk = 0; kk < 4; kk++) wg_ss192t(acc, dA + (sa * (SLOT >> 4) + kk * 2), dW + (sw * (SLOT >> 4) + kk * 384), kk != 0 || s != 0);
        WG_COMMIT();
        if (s == 9) asm volatile("bar.arrive %0, 256;" ::"r"(2 - w) : "memory");
        if (s < 9 && u > 0) store_o(s);
        if (s > 0) { WG_WAIT(1); release((2 * s - 2) % NSLOT); release((2 * s - 1) % NSLOT); }
      }
      Ring r{2, 0};
      WG_WAIT(0);
      reg_fence(acc);
      release(0); release(1);
      if (u == 0) {
        mbar_wait(bar_s, 0, budget);
        const uint2 s0 = lds64(s_misc + 512 + (cw * 16 + g) * 8), s1 = lds64(s_misc + 576 + (cw * 16 + g) * 8);
        const uint32_t msk = q == 0 ? 0xffffffffu : q == 1 ? 0xffffu : 0u;
        const float c0 = SM_C * __uint_as_float(s0.y), c1 = SM_C * __uint_as_float(s1.y);
        uint32_t am[4] = {(s0.x ^ 0x80008000u) & msk, (s1.x ^ 0x80008000u) & msk, 0, 0};
        reg_fence(am);
        WG_FENCE();
        wg_rs192t(acc, am[0], am[1], am[2], am[3], mkdesc(bar_full + 2048, desc_hi(1024, 0, 1)), 1);
        WG_COMMIT();
        WG_WAIT(0);
        reg_fence(acc);
#pragma unroll
        for (int i = 0; i < 24; i++) { acc[4 * i] *= c0; acc[4 * i + 1] *= c0; acc[4 * i + 2] *= c1; acc[4 * i + 3] *= c1; }
      }
#pragma unroll
      for (int i = 0; i < 48; i++) fr[i] = pack_bf16(acc[2 * i], acc[2 * i + 1]);
      float sc[32], l0 = 0.f, l1 = 0.f;
      uint32_t pf[16];
      auto pack_p = [&]() {
#pragma unroll
        for (int i = 0; i < 16; i++) pf[i] = pack_bf16(sc[2 * i], sc[2 * i + 1]);
      };
      {
        const uint32_t sk = r.slot; mbar_wait(bar_full + 8 * sk, r.phase, budget); r.next();
        const uint64_t dk = mkdesc(sb + sk * SLOT, HI_W);
        asm volatile("bar.sync %0, 256;" ::"r"(1 + w) : "memory");
        WG_FENCE();
#pragma unroll
        for (int t = 0; t < 12; t++) {
          wg_rs64(sc, fr[4 * t], fr[4 * t + 1], fr[4 * t + 2], fr[4 * t + 3], dk + (t >> 2) * 64 + (t & 3) * 2, t != 0);
          if (t == 7) asm volatile("bar.arrive %0, 256;" ::"r"(2 - w) : "memory");
        }
        WG_COMMIT();
        WG_WAIT(0);
        reg_fence(sc);
        release(sk);
        exp_block(sc, l0, l1);
        pack_p();
      }
#pragma unroll 1
      for (int j = 1; j < 8; j++) {
        const uint32_t sk = r.slot; mbar_wait(bar_full + 8 * sk, r.phase, budget); r.next();
        const uint32_t sv = r.slot; mbar_wait(bar_full + 8 * sv, r.phase, budget); r.next();
        const uint64_t dk = mkdesc(sb + sk * SLOT, HI_W), dv = mkdesc(sb + sv * SLOT, HI_W);
        asm volatile("bar.sync %0, 256;" ::"r"(1 + w) : "memory");
        WG_FENCE();
#pragma unroll
        for (int t = 0; t < 12; t++) wg_rs64(sc, fr[4 * t], fr[4 * t + 1], fr[4 * t + 2], fr[4 * t + 3], dk + (t >> 2) * 64 + (t & 3) * 2, t != 0);
        WG_COMMIT();
        asm volatile("bar.arrive %0, 256;" ::"r"(2 - w) : "memory");
#pragma unroll
        for (int kk = 0; kk < 4; kk++) wg_rs192t(acc, pf[4 * kk], pf[4 * kk + 1], pf[4 * kk + 2], pf[4 * kk + 3], dv + kk * 384, kk != 0 || j > 1);
        WG_COMMIT();
        WG_WAIT(1);
        reg_fence(sc);
        exp_block(sc, l0, l1);
        release(sk + (__float_as_uint(l0) & __float_as_uint(l1) & zero));
        WG_WAIT(0);
        reg_fence(acc); reg_fence(pf);
        release(sv);
        pack_p();
      }
      const uint32_t sv = r.slot; mbar_wait(bar_full + 8 * sv, r.phase, budget); r.next();
      {
        const uint64_t dv = mkdesc(sb + sv * SLOT, HI_W);
        asm volatile("bar.sync %0, 256;" ::"r"(1 + w) : "memory");
        WG_FENCE();
#pragma unroll
        for (int kk = 0; kk < 4; kk++) {
          wg_rs192t(acc, pf[4 * kk], pf[4 * kk + 1], pf[4 * kk + 2], pf[4 * kk + 3], dv + kk * 384, 1);
          if (kk == 1 && (u < 3 || w == 0)) asm volatile("bar.arrive %0, 256;" ::"r"(2 - w) : "memory");
        }
        WG_COMMIT();
      }
      l0 = quad_sum(l0); l1 = quad_sum(l1);
      const bool unsafe = __any_sync(~0u, !(l0 >= SM_LO && l1 >= SM_LO && l0 + l1 <= SM_HI));
      l0 = rcp(l0); l1 = rcp(l1);
      WG_WAIT(0);
      reg_fence(acc);
      release(sv);
      if (__builtin_expect(unsafe, 0)) {
        int o = hg * 4 + u; asm volatile("" : "+r"(o));
        o = (o * SKC + (SKC - WIN) + g) * (DH / 2) + q;
        safe_head((const uint32_t*)p.k + o, (const uint32_t*)p.v + o, fr, acc, l0, l1);
        l0 = rcp(l0); l1 = rcp(l1);
      }
#pragma unroll
      for (int i = 0; i < 24; i++) {
        fr[8 * (i >> 2) + (i & 3)] = pack_bf16(acc[4 * i] * l0, acc[4 * i + 1] * l0);
        fr[8 * (i >> 2) + 4 + (i & 3)] = pack_bf16(acc[4 * i + 2] * l1, acc[4 * i + 3] * l1);
      }
    }

    float aF[80], aS[80];
    const uint32_t xs = x_block(cw);
    const uint32_t eoff = xs + g * 160 + q * 4;
    const uint32_t rel_b = rel_addr + (bar_b + 48 - bar_empty);
    auto rel_a = [&](uint32_t o8) { if (lane == 0) mbar_arrive(bar_a + 40 + o8); };
    auto rel_w = [&](uint32_t o8) { if (lane < 2) mbar_arrive_cluster(rel_b + o8); };
    uint32_t pha = 0, phb = 0, a8 = 0, b8 = 0, pa8 = 0, pb8 = 0;
#pragma unroll 1
    for (int s = 0; s < 19; s++) {
      const uint64_t d0 = mkdesc(sb, HI_O), dO = d0 + (a8 * (TA >> 7) + w * 256), dB = d0 + ((OFF_B >> 4) + b8 * (TB >> 7));
      mbar_wait(bar_a + a8, pha, budget);
      mbar_wait(bar_b + b8, phb, budget);
      WG_FENCE();
#pragma unroll
      for (int kk = 0; kk < 4; kk++) wg_ss160t(aF, dO + ((kk >> 1) * 512 + (kk & 1) * 2), dB + ((kk >> 1) * 640 + (kk & 1) * 64), kk != 0 || s != 0);
      WG_COMMIT();
      mbar_wait(bar_b + b8 + 8, phb, budget);
      WG_WAIT(1);
      if (s > 0) { rel_a(pa8); rel_w(pb8 + 8); }
      WG_FENCE();
#pragma unroll
      for (int kk = 0; kk < 4; kk++) wg_ss160t(aS, dO + ((kk >> 1) * 512 + (kk & 1) * 2), dB + ((TB >> 4) + (kk >> 1) * 640 + (kk & 1) * 64), kk != 0 || s != 0);
      WG_COMMIT();
      if (s < 9) {
#pragma unroll
        for (int pp = 0; pp < 9; pp++) if (s == pp) store_o(pp);
      }
      WG_WAIT(1);
      rel_w(b8);
      pa8 = a8; a8 += 8; if (a8 == 40) { a8 = 0; pha ^= 1; }
      pb8 = b8; b8 += 16; if (b8 == 48) { b8 = 0; phb ^= 1; }
    }
    const uint64_t d0 = mkdesc(fresh(), HI_O);
    auto half = [&](float (&acc_)[80], int i, int n) {
      mbar_wait(bar_b + 8 * (n % 6), (n / 6) & 1, budget);
      WG_FENCE();
#pragma unroll
      for (int kk = 0; kk < 4; kk++)
        wg_ss160t(acc_, d0 + w * 256 + (((4 + i) % 5) * (TA >> 4) + (kk >> 1) * 512 + (kk & 1) * 2), d0 + ((OFF_B >> 4) + (n % 6) * (TB >> 4) + (kk >> 1) * 640 + (kk & 1) * 64), 1);
      WG_COMMIT();
    };
    pb8 += 8;
#pragma unroll 1
    for (int i = 0; i < 5; i++) {
      const uint64_t dd = mkdesc(sb, HI_O), dO = dd + (a8 * (TA >> 7) + w * 256), dB = dd + ((OFF_B >> 4) + b8 * (TB >> 7));
      mbar_wait(bar_a + a8, pha, budget);
      mbar_wait(bar_b + b8, phb, budget);
      WG_FENCE();
#pragma unroll
      for (int kk = 0; kk < 4; kk++) wg_ss160t(aF, dO + ((kk >> 1) * 512 + (kk & 1) * 2), dB + ((kk >> 1) * 640 + (kk & 1) * 64), 1);
      WG_COMMIT();
      WG_WAIT(1);
      if (i == 0) rel_a(pa8);
      rel_w(pb8);
      a8 += 8; if (a8 == 40) { a8 = 0; pha ^= 1; }
      pb8 = b8; b8 += 8; if (b8 == 48) { b8 = 0; phb ^= 1; }
    }
    constexpr uint32_t tag = 0xFFFF0000u;
    const int tid = threadIdx.x - 128;
    uint4* const xbase = p.s->o + (size_t)(qt * 192 + nh * 24 + 9) * 512 + tid;
    mbar_wait(bar_z, 0, budget);
    auto pack7 = [&](const float* v, int pk, uint32_t* o4) {
      const int o = 7 * pk;
      o4[0] = pack_bf16(v[o], v[o + 1]); o4[1] = pack_bf16(v[o + 2], v[o + 3]);
      o4[2] = pack_bf16(v[o + 4], pk < 5 ? v[o + 5] : 0.f);
      o4[3] = pack_bf16(pk < 5 ? v[o + 6] : 0.f, 0.f) | tag;
    };
    uint32_t tx[48] = {};
    uint4* const dst = xbase + kq * (48 * 512);
    auto send_f = [&](int i) { st_pkt(dst + ((i & 1) * 6 + (i >> 1)) * 256, tx[4 * i], tx[4 * i + 1], tx[4 * i + 2], tx[4 * i + 3]); };
    half(aS, 0, 43);
    WG_WAIT(1);
    reg_fence(aF);
#pragma unroll
    for (int i = 0; i < 12; i++) pack7(aF + 40 * (i & 1), i >> 1, tx + 4 * i);
    reg_fence(tx);
#pragma unroll
    for (int i = 1; i < 5; i++) {
#pragma unroll
      for (int k = 3 * i - 3; k < 3 * i; k++) send_f(k);
      half(aS, i, 43 + i);
      if (i == 2) { WG_WAIT(1); if (lane == 0) mbar_arrive(bar_r); }
    }
    WG_WAIT(0);
    reg_fence(aS);
    {
      float own[40];
      const bool odd = kq & 1;
#pragma unroll
      for (int i = 0; i < 40; i++) { own[i] = odd ? aS[40 + i] : aS[i]; aS[i] = odd ? aS[i] : aS[40 + i]; }
#pragma unroll
      for (int pk = 0; pk < 6; pk++) pack7(aS, pk, tx + 4 * pk);
      reg_fence(tx);
#pragma unroll
      for (int pk = 0; pk < 6; pk++) st_pkt(dst + (12 + pk) * 256, tx[4 * pk], tx[4 * pk + 1], tx[4 * pk + 2], tx[4 * pk + 3]);
      const uint4* src = xbase + (2 - (kq & 2)) * (48 * 512) + (kq & 1) * 6 * 256;
      const uint4* srcL = xbase + (kq ^ 1) * (48 * 512) + 12 * 256;
      uint32_t gr[20] = {};
      mbar_wait(bar_u, 0, budget);
      const uint2 sel = lds64(s_misc);
#pragma unroll 1
      for (int hi = 0; hi < 2; hi++) {
        const uint2 st = lds64(s_misc + 512 + (cw * 16 + g + 8 * hi) * 8);
#pragma unroll
        for (int jj = 0; jj < 10; jj++) {
          const uint32_t d = hsub2(lds32(eoff + hi * 1280 + jj * 16), st.x);
          gr[jj] = gr[10 + jj];
          gr[10 + jj] = pack_bf16(bf_lo(d) * __uint_as_float(st.y), bf_hi(d) * __uint_as_float(st.y));
        }
        const uint32_t row = row0 + hi * 8;
        if (row == sel.x || row == sel.y) {
#pragma unroll
          for (int jj = 0; jj < 10; jj++) gr[10 + jj] = hadd2(gr[10 + jj], lds32(s_misc + 16 + (row == sel.y ? 160 : 0) + jj * 16 + q * 4));
        }
#pragma unroll
        for (int i = 10; i < 20; i++) gr[i] = pack_bf16(silu_f(bf_lo(gr[i])), silu_f(bf_hi(gr[i])));
      }
#pragma unroll 1
      for (int e = 0; e < 3; e++) {
        uint4 v[6];
        mbar_wait(bar_e + 8 * e, 0, budget);
#pragma unroll
        for (int i = 0; i < 6; i++) v[i] = lds128(sb + OFF_PK + e * SLOT + (i * 256 + tid) * 16);
        while (true) {
          uint32_t bad = 0;
#pragma unroll
          for (int i = 0; i < 6; i++) bad |= v[i].w ^ tag;
          if (!(bad >> 16) || --budget < 0) break;
#pragma unroll
          for (int i = 0; i < 6; i++) v[i] = ld_pkt(src + i * 256);
        }
#pragma unroll
        for (int i = 0; i < 6; i++) {
          const int o = 7 * i;
          own[o] += bf_lo(v[i].x); own[o + 1] += bf_hi(v[i].x); own[o + 2] += bf_lo(v[i].y); own[o + 3] += bf_hi(v[i].y); own[o + 4] += bf_lo(v[i].z);
          if (i < 5) { own[o + 5] += bf_hi(v[i].z); own[o + 6] += bf_lo(v[i].w); }
        }
        src = e ? srcL : src + 48 * 512;
      }
#pragma unroll
      for (int i = 0; i < 20; i++) {
        const uint32_t ad = eoff + (i & 1) * 1280 + (i >> 1) * 16;
        sts32(ad, hadd2(lds32(ad), hmul2(pack_bf16(own[2 * i], own[2 * i + 1]), gr[(i & 1) * 10 + (i >> 1)])));
      }
      asm volatile("fence.proxy.async.shared::cta;" ::: "memory");
      __syncwarp();
      if (lane == 0) {
        tma2d_store(&tm_out, xs, nh * 320 + kq * 80, qt * 128 + cw * 16);
        asm volatile("cp.async.bulk.commit_group;\ncp.async.bulk.wait_group.read 0;" ::: "memory");
      }
      __syncwarp();
    }
    cluster_sync();
    if (threadIdx.x == 128) asm volatile("red.relaxed.gpu.global.add.u64 [%0], 1;" ::"l"(&p.s->done) : "memory");
  } else {
    asm volatile("setmaxnreg.dec.sync.aligned.u32 40;");
    uint32_t tid_; asm volatile("mov.u32 %0, %%tid.x;" : "=r"(tid_));
    const int warp = __shfl_sync(~0u, tid_ >> 5, 0);
    auto is_warp = [&](int k) { uint32_t e; asm volatile("{\n.reg .pred q;\nsetp.eq.u32 q, %1, %2;\nselp.u32 %0, 1, 0, q;\n}" : "=r"(e) : "r"(warp), "r"(k)); return e != 0; };
    if (warp > 0) {
      const unsigned epoch = (unsigned)(__ldcg(&p.s->done) >> 7);
      cluster_wait();
      const uint32_t tag = epoch + 1;
      if (tid_ == 96) {
        for (int i = 0; i < 5; i++) { mbar_init(bar_a + 8 * i, 1); mbar_init(bar_a + 40 + 8 * i, 8); }
        for (int i = 0; i < 6; i++) { mbar_init(bar_b + 8 * i, 1); mbar_init(bar_b + 48 + 8 * i, 16); }
        asm volatile("fence.mbarrier_init.release.cluster;" ::: "memory");
      }
      __syncwarp();
      mbar_wait(bar_full + 8, 0, budget); mbar_wait(bar_full + 24, 0, budget);
      float cs0 = 0.f, cs1 = 0.f;
      const int n = rank * 96 + (warp - 1) * 32 + (lane & 15) * 2;
#pragma unroll 1
      for (int kg = ((qt >> 1) & 3) * 2 + (lane >> 4) * 5, e = kg + 5; kg < e; kg++) {
        const uint32_t ad = sb + SLOT + (kg >> 3) * 2 * SLOT + (kg & 7) * 3072 + (n >> 6) * 1024 + (n & 63) * 2;
#pragma unroll
        for (int k = 0; k < 8; k++) { const uint32_t v = lds32(ad ^ (k * 0x90)); cs0 += bf_lo(v); cs1 += bf_hi(v); }
      }
      cs0 += __shfl_xor_sync(~0u, cs0, 16); cs1 += __shfl_xor_sync(~0u, cs1, 16);
      if (lane < 16) st_pkt(p.s->cs + (hg * 8 + (qt >> 1)) * 96 + (n >> 1), __float_as_uint(cs0), __float_as_uint(cs1), 0, tag);
      if (lane == 0) mbar_arrive(bar_d);
      cs0 = cs1 = 0.f;
#pragma unroll 1
      for (int e = is_warp(3) ? 0 : 1; e < 3; e++) {
        const uint4* src = e ? p.s->cs + (hg * 8 + 4 * e - 4) * 96 + (tid_ - 32) : p.s->stat + qt * 128 + lane;
        const int step = e ? 96 : 32;
        uint4 v[4];
        while (true) {
          uint32_t bad = 0;
#pragma unroll
          for (int i = 0; i < 4; i++) v[i] = ld_pkt(src + i * step);
#pragma unroll
          for (int i = 0; i < 4; i++) bad |= v[i].w ^ tag;
          if (!__any_sync(~0u, bad) || --budget < 0) break;
        }
#pragma unroll
        for (int i = 0; i < 4; i++) {
          if (e) { cs0 += __uint_as_float(v[i].x); cs1 += __uint_as_float(v[i].y); }
          else { sts32(s_misc + 512 + (i * 32 + lane) * 8, v[i].x); sts32(s_misc + 516 + (i * 32 + lane) * 8, v[i].y); }
        }
      }
#pragma unroll 1
      for (int k = 0; k < 8; k++) {
        const uint32_t v = pack_bf16(cs0, cs1);
        sts32((bar_full + 2048 + ((tid_ - 32) >> 5) * 1024 + lane * 4) ^ (k * 0x90), k < 3 ? v : 0);
        cs0 -= bf_lo(v); cs1 -= bf_hi(v);
      }
      asm volatile("fence.proxy.async.shared::cta;" ::: "memory");
      __syncwarp();
      if (lane == 0) mbar_arrive(bar_s);
      if (is_warp(1)) {
#pragma unroll 1
        for (int u = 0; u < 5; u++) {
          mbar_wait(bar_o, u & 1, budget);
          if (lane == 0) red_release(&p.s->flag[u ? FL_O + (qt * 8 + hg) * 8 : FL_XN + qt * 32]);
          __syncwarp();
        }
      } else if (is_warp(2)) {
        mbar_wait(bar_p, 0, budget);
        wait_flag(&p.s->flag[FL_FFN], epoch + 1, budget);
        if (lane < 2) sts32(s_misc + 4 * lane, __ldcg(&p.s->sel[lane]));
#pragma unroll 1
        for (int i = lane; i < 80; i += 32)
          sts32(s_misc + 16 + 4 * i, __ldcg((const uint32_t*)(p.s->upd + (i >= 40 ? DM : 0) + nh * 320 + kq * 80) + (i >= 40 ? i - 40 : i)));
        __syncwarp();
        if (lane == 0) mbar_arrive(bar_u);
      } else {
        mbar_wait(bar_q, 0, budget);
        if (lane == 0) asm volatile("red.relaxed.gpu.global.add.u32 [%0], 1;" ::"l"(&p.s->flag[FL_RD + (qt * 8 + hg) * 8]) : "memory");
        while (true) {
          unsigned v; asm volatile("ld.relaxed.gpu.global.u32 %0, [%1];" : "=r"(v) : "l"(&p.s->flag[FL_RD + (qt * 8 + (hg ^ 1)) * 8]) : "memory");
          if ((int)(v - (epoch + 1)) >= 0 || --budget < 0) break;
        }
        if (lane == 0) mbar_arrive(bar_z);
      }
    } else {
      cluster_wait();
      uint32_t fb = bar_full, dst = sb, ph = 1;
      auto next = [&]() { fb += 8; dst += SLOT; if (fb == bar_empty) { fb = bar_full; dst = sb; ph ^= 1; } };
      unsigned epoch = 0;
#pragma unroll 1
      for (int u = 0; u < 4; u++) {
        const int h = hg * 4 + u;
        if (u == 1) {
          epoch = (unsigned)(__ldcg(&p.s->done) >> 7);
          wait_flag(&p.s->flag[FL_XN + qt * 32], (epoch + 1) * 8, budget);
          fence_proxy_async();
        }
        const CUtensorMap* tx = u ? &tm_xn : &tm_x;
        int s = u ? 0 : (5 * (qt >> 1)) >> 2;
#pragma unroll 1
        for (int i = 0; i < 10; i++) {
          if (u == 0 && i == 5) mbar_wait(bar_d, 0, budget);
          mbar_wait(fb + 72, ph, budget);
          if (elect()) { mbar_expect_tx(fb, 16384); tma2d(dst, tx, 64 * s, qt * 128, fb); }
          next();
          mbar_wait(fb + 72, ph, budget);
          if (elect()) { mbar_expect_tx(fb, SLOT); tma4d_mc(dst + rank * (SLOT / 2), &tm_wq, 3 * h, 8 * s + 4 * rank, fb); }
          next();
          if (++s == 10) s = 0;
        }
        const int kv0 = (h * SKC + (SKC - WIN)) / 8 + 4 * rank;
#pragma unroll 1
        for (int i = 0; i < 16; i++) {
          const bool isk = (0x2AAB >> i) & 1;
          mbar_wait(fb + 72, ph, budget);
          if (elect()) { mbar_expect_tx(fb, SLOT); tma4d_mc(dst + rank * (SLOT / 2), isk ? &tm_k : &tm_v, 0, kv0 + 8 * (isk ? (i + 1) >> 1 : (i - 1) >> 1), fb); }
          next();
        }
      }
      const int cF = 10 * nh + 5 - 5 * (kq >> 1), cS = 10 * nh + 5 * (kq >> 1);
      uint32_t a8 = 0, b8 = 0, pha = 1, phb = 1;
      auto k_block = [&](int t) {
        const int i = (t * 11) >> 5;
        return ((i < 6 ? 2 * kq + (i & 1) : hg ^ (i & 1)) * 4 + (i >> 1)) * 6 + 2 * (t - 3 * i);
      };
      auto load_w = [&](int t, int k32, int col) {
        if (t < 3) mbar_wait(bar_empty + 8 * ((0x876544 >> (b8 >> 1)) & 15), ph, budget);
        mbar_wait(bar_b + 48 + b8, phb, budget);
        if (elect()) { mbar_expect_tx(bar_b + b8, TB); tma5d_mc(sb + OFF_B + b8 * (TB >> 3) + rank * (TB / 2), &tm_wo, 4 * (k32 + rank), col, bar_b + b8); }
        b8 += 8; if (b8 == 48) { b8 = 0; phb ^= 1; }
      };
#pragma unroll 1
      for (int n = 0; n < 29; n++) {
        const int t = n < 24 ? n : n - 5, k32 = k_block(t);
        if (n == 0 || n == 18) {
          wait_flag(&p.s->flag[FL_O + (qt * 8 + (t ? 2 * kq + (lane & 1) : lane & 7)) * 8], epoch * 4 + (t ? 4 : 3), budget);
          fence_proxy_async();
        }
        if (n < 24) {
          if (t < 5) mbar_wait(bar_empty + 8 * ((0x32110 >> (4 * t)) & 15), ph, budget);
          mbar_wait(bar_a + 40 + a8, pha, budget);
          if ((t == 14 || t == 22) && lane == 0) mbar_arrive(t == 14 ? bar_p : bar_q);
          if (elect()) {
            mbar_expect_tx(bar_a + a8, t == 9 ? TA + 20480 : TA);
            bulk_load(sb + a8 * (TA >> 3), p.s->o + (size_t)(qt * 192 + k32) * 512, TA, bar_a + a8);
            if (t == 9) {
#pragma unroll 1
              for (int e = 0; e < 8; e++) tma2d(x_block(e), &tm_xe, nh * 320 + kq * 80, qt * 128 + e * 16, bar_a + a8);
            }
          }
          a8 += 8; if (a8 == 40) { a8 = 0; pha ^= 1; }
        }
#pragma unroll 1
        for (int e = n >= 24; e < (n < 19 || n >= 24 ? 2 : 1); e++) load_w(t, k32, e ? cS : cF);
      }
      const int e = lane >> 3;
      const uint4* src = p.s->o + (size_t)(qt * 192 + nh * 24 + 9) * 512 +
                         (e < 2 ? (2 - (kq & 2) + e) * (48 * 512) + (kq & 1) * 6 * 256 : (kq ^ 1) * (48 * 512) + 12 * 256);
      mbar_wait(bar_r, 0, budget);
      uint32_t todo = 0x00ffffffu;
#pragma unroll 1
      while (todo && --budget >= 0) {
        bool ok = false;
        if ((todo >> lane) & 1) ok = ld_pkt(src + 5 * 256 + (lane & 7) * 32 + 31).w >= 0xFFFF0000u;
        const uint32_t got = __ballot_sync(~0u, ok);
        const bool go = ((got >> (8 * e)) & 0xff) == 0xff;
        if (go && (lane & 7) == 0) { mbar_expect_tx(bar_e + 8 * e, SLOT); bulk_load(sb + OFF_PK + e * SLOT, src, SLOT, bar_e + 8 * e); }
        todo &= ~__ballot_sync(~0u, go);
      }
    }
    cluster_sync();
  }
}

typedef CUresult (*EncodeFn)(CUtensorMap*, CUtensorMapDataType, cuuint32_t, void*, const cuuint64_t*, const cuuint64_t*,
                             const cuuint32_t*, const cuuint32_t*, CUtensorMapInterleave, CUtensorMapSwizzle,
                             CUtensorMapL2promotion, CUtensorMapFloatOOBfill);

void encode(EncodeFn fn, CUtensorMap* tm, void* base, int rank, const cuuint64_t* dims, const cuuint64_t* strides,
            const cuuint32_t* box, CUtensorMapSwizzle sw) {
  const cuuint32_t es[5] = {1, 1, 1, 1, 1};
  fn(tm, CU_TENSOR_MAP_DATA_TYPE_BFLOAT16, rank, base, dims, strides, box, es, CU_TENSOR_MAP_INTERLEAVE_NONE, sw,
     CU_TENSOR_MAP_L2_PROMOTION_L2_128B, CU_TENSOR_MAP_FLOAT_OOB_FILL_NONE);
}

}

extern "C" void kernel_launch(void* const* d_in, const int* in_sizes, int n_in, void* d_out, int out_size) {
  static EncodeFn fn = nullptr;
  static Scratch* scr = nullptr;
  if (!fn) {
    void* f = nullptr;
    cudaDriverEntryPointQueryResult st;
    cudaGetDriverEntryPoint("cuTensorMapEncodeTiled", &f, cudaEnableDefault, &st);
    fn = (EncodeFn)f;
    cudaGetSymbolAddress((void**)&scr, g_scratch);
    cudaFuncSetAttribute(fused_kernel, cudaFuncAttributeMaxDynamicSharedMemorySize, SMEM_BYTES);
  }
  CUtensorMap tm_x, tm_xn, tm_wq, tm_k, tm_v, tm_wo, tm_xe, tm_out;
  { const cuuint64_t d[2] = {DM, SQ}, s[1] = {DM * 2}; const cuuint32_t b[2] = {64, 128};
    encode(fn, &tm_x, d_in[0], 2, d, s, b, CU_TENSOR_MAP_SWIZZLE_128B);
    encode(fn, &tm_xn, scr->xn, 2, d, s, b, CU_TENSOR_MAP_SWIZZLE_128B); }
  { const cuuint64_t d[4] = {64, 8, QD / 64, DM / 8}, s[3] = {QD * 2, 128, 8 * QD * 2}; const cuuint32_t b[4] = {64, 8, 3, 4};
    encode(fn, &tm_wq, d_in[3], 4, d, s, b, CU_TENSOR_MAP_SWIZZLE_128B); }
  { const cuuint64_t d[4] = {64, 8, 3, NH * SKC / 8}, s[3] = {DH * 2, 128, 8 * DH * 2}; const cuuint32_t b[4] = {64, 8, 3, 4};
    encode(fn, &tm_k, d_in[1], 4, d, s, b, CU_TENSOR_MAP_SWIZZLE_128B);
    encode(fn, &tm_v, d_in[2], 4, d, s, b, CU_TENSOR_MAP_SWIZZLE_128B); }
  {
    const cuuint64_t d[5] = {32, 2, QD / 8, 4, DM / 32}, s[4] = {DM * 2, 8 * DM * 2, 2 * DM * 2, 64}; const cuuint32_t b[5] = {32, 2, 4, 4, 5};
    encode(fn, &tm_wo, d_in[4], 5, d, s, b, CU_TENSOR_MAP_SWIZZLE_64B); }
  { const cuuint64_t d[2] = {DM, SQ}, s[1] = {DM * 2}; const cuuint32_t bo[2] = {80, 16};
    encode(fn, &tm_xe, d_in[0], 2, d, s, bo, CU_TENSOR_MAP_SWIZZLE_NONE);
    encode(fn, &tm_out, d_out, 2, d, s, bo, CU_TENSOR_MAP_SWIZZLE_NONE); }
  Params p;
  p.x = (const __nv_bfloat16*)d_in[0]; p.wr = (const __nv_bfloat16*)d_in[6]; p.wg = (const __nv_bfloat16*)d_in[7];
  p.wu = (const __nv_bfloat16*)d_in[8]; p.wd = (const __nv_bfloat16*)d_in[9];

  p.k = (const __nv_bfloat16*)d_in[1]; p.v = (const __nv_bfloat16*)d_in[2]; p.s = scr;
  cudaLaunchConfig_t cfg = {};
  cfg.gridDim = dim3(132); cfg.blockDim = dim3(384); cfg.dynamicSmemBytes = SMEM_BYTES; cfg.stream = cudaStreamPerThread;
  cudaLaunchAttribute at[1];
  at[0].id = cudaLaunchAttributeClusterDimension; at[0].val.clusterDim.x = 2; at[0].val.clusterDim.y = 1; at[0].val.clusterDim.z = 1;
  cfg.attrs = at; cfg.numAttrs = 1;
  cudaLaunchKernelEx(&cfg, fused_kernel, p, tm_x, tm_xn, tm_wq, tm_k, tm_v, tm_wo, tm_xe, tm_out);
}
```

```cpp
#include <cuda_runtime.h>
#include <cuda_bf16.h>
#include <cuda.h>
#include <stdint.h>

namespace {

constexpr int SQ = 2048, DM = 640, NH = 32, DH = 192, SKC = 2048, WIN = 512, FF = 1536;
constexpr int QD = NH * DH;
constexpr uint32_t TA = 16384, TB = 24576, TW = 20480, OFF_B = 5 * TA, OFF_M = OFF_B + 6 * TB, SMEM_BYTES = OFF_M + 3072;
constexpr int WAIT_BUDGET = 1 << 20;

constexpr int FL_XN = 0;
constexpr int FL_O = 512;
constexpr int FL_RD = FL_O + 1024;
constexpr int FL_FFN = FL_RD + 1024;
constexpr int FL_SIDE = FL_FFN + 32;
struct __align__(1024) Scratch {
  unsigned long long done, pad0[15];
  unsigned flag[FL_SIDE + 32];
  uint4 cand[8];
  float ffn[4 * 2 * DM];
  int sel[4];
  __nv_bfloat16 gsel[2 * DM];
  uint4 cs[8 * 8 * DH / 2];
  uint4 stat[SQ];
  __align__(1024) __nv_bfloat16 xn[SQ * DM];
  __align__(1024) uint4 o[SQ * QD / 8];
};
__device__ Scratch g_scratch;

__device__ __forceinline__ uint32_t smem_u32(const void* p) { return (uint32_t)__cvta_generic_to_shared(p); }
__device__ __forceinline__ void mbar_init(uint32_t bar, int cnt) { asm volatile("mbarrier.init.shared::cta.b64 [%0], %1;" ::"r"(bar), "r"(cnt)); }
__device__ __forceinline__ void mbar_expect_tx(uint32_t bar, uint32_t bytes) {
  asm volatile("mbarrier.arrive.expect_tx.shared::cta.b64 _, [%0], %1;" ::"r"(bar), "r"(bytes) : "memory");
}
__device__ __forceinline__ void mbar_arrive(uint32_t bar) { asm volatile("mbarrier.arrive.shared::cta.b64 _, [%0];" ::"r"(bar) : "memory"); }
__device__ __forceinline__ void mbar_arrive_cluster(uint32_t addr) { asm volatile("mbarrier.arrive.shared::cluster.b64 _, [%0];" ::"r"(addr) : "memory"); }
__device__ __forceinline__ bool mbar_try(uint32_t bar, uint32_t parity) {
  uint32_t ok;
  asm volatile("{\n.reg .pred p;\nmbarrier.try_wait.parity.shared::cta.b64 p, [%1], %2;\nselp.u32 %0, 1, 0, p;\n}\n" : "=r"(ok) : "r"(bar), "r"(parity) : "memory");
  return ok;
}
__device__ __forceinline__ void mbar_wait(uint32_t bar, uint32_t parity, int& budget) {
#pragma unroll 1
  while (!mbar_try(bar, parity)) { if (--budget < 0) break; }
}
__device__ __forceinline__ void mbar_wait(uint32_t bar, uint32_t parity) {
#pragma unroll 1
  while (!mbar_try(bar, parity)) {}
}
__device__ __forceinline__ unsigned ld_acquire(const unsigned* p) { unsigned v; asm volatile("ld.acquire.gpu.global.u32 %0, [%1];" : "=r"(v) : "l"(p) : "memory"); return v; }
__device__ __forceinline__ void wait_flag(const unsigned* p, unsigned target) {
#pragma unroll 1
  while (__any_sync(~0u, (int)(ld_acquire(p) - target) < 0)) {}
}
__device__ __forceinline__ void red_release(unsigned* p) { asm volatile("red.release.gpu.global.add.u32 [%0], 1;" ::"l"(p) : "memory"); }
__device__ __forceinline__ void fence_proxy_async() { asm volatile("fence.proxy.async.global;" ::: "memory"); }
__device__ __forceinline__ bool elect() {
  uint32_t p;
  asm volatile("{\n.reg .pred P;\nelect.sync _|P, 0xffffffff;\nselp.u32 %0, 1, 0, P;\n}\n" : "=r"(p));
  return p;
}
__device__ __forceinline__ void cluster_arrive() { asm volatile("barrier.cluster.arrive.relaxed.aligned;" ::: "memory"); }
__device__ __forceinline__ void cluster_wait() { asm volatile("barrier.cluster.wait.aligned;" ::: "memory"); }
__device__ __forceinline__ void cluster_sync() { cluster_arrive(); cluster_wait(); }
__device__ __forceinline__ void tma2d(uint32_t dst, const CUtensorMap* tm, int c0, int c1, uint32_t bar) {
  asm volatile("cp.async.bulk.tensor.2d.shared::cluster.global.mbarrier::complete_tx::bytes [%0], [%1, {%3, %4}], [%2];"
               ::"r"(dst), "l"(tm), "r"(bar), "r"(c0), "r"(c1) : "memory");
}
constexpr uint64_t POL_FIRST = 0x12F0000000000000ull;
__device__ __forceinline__ void tma4d_mc(uint32_t dst, const CUtensorMap* tm, int c2, int c3, uint32_t bar) {
  asm volatile("cp.async.bulk.tensor.4d.shared::cluster.global.mbarrier::complete_tx::bytes.multicast::cluster.L2::cache_hint [%0], [%1, {%3, %3, %4, %5}], [%2], %6, %7;"
               ::"r"(dst), "l"(tm), "r"(bar), "r"(0), "r"(c2), "r"(c3), "h"((uint16_t)3), "l"(POL_FIRST) : "memory");
}
__device__ __forceinline__ void tma5d_mc(uint32_t dst, const CUtensorMap* tm, int c2, int c4, uint32_t bar) {
  asm volatile("cp.async.bulk.tensor.5d.shared::cluster.global.mbarrier::complete_tx::bytes.multicast::cluster.L2::cache_hint [%0], [%1, {%3, %3, %4, %3, %5}], [%2], %6, %7;"
               ::"r"(dst), "l"(tm), "r"(bar), "r"(0), "r"(c2), "r"(c4), "h"((uint16_t)3), "l"(POL_FIRST) : "memory");
}
__device__ __forceinline__ void bulk_load(uint32_t dst, const void* src, uint32_t bytes, uint32_t bar) {
  asm volatile("cp.async.bulk.shared::cluster.global.mbarrier::complete_tx::bytes.L2::cache_hint [%0], [%1], %2, [%3], %4;" ::"r"(dst), "l"(src), "r"(bytes), "r"(bar), "l"(POL_FIRST) : "memory");
}
__device__ __forceinline__ void tma2d_store(const CUtensorMap* tm, uint32_t src, int c0, int c1) {
  asm volatile("cp.async.bulk.tensor.2d.global.shared::cta.bulk_group [%0, {%2, %3}], [%1];" ::"l"(tm), "r"(src), "r"(c0), "r"(c1) : "memory");
}
__device__ __forceinline__ uint32_t lds32(uint32_t a) { uint32_t v; asm volatile("ld.shared.u32 %0, [%1];" : "=r"(v) : "r"(a) : "memory"); return v; }
__device__ __forceinline__ uint2 lds64(uint32_t a) { uint2 v; asm volatile("ld.shared.v2.u32 {%0,%1}, [%2];" : "=r"(v.x), "=r"(v.y) : "r"(a) : "memory"); return v; }
__device__ __forceinline__ uint4 lds128(uint32_t a) { uint4 v; asm volatile("ld.shared.v4.u32 {%0,%1,%2,%3}, [%4];" : "=r"(v.x), "=r"(v.y), "=r"(v.z), "=r"(v.w) : "r"(a) : "memory"); return v; }
__device__ __forceinline__ void ldsm4(uint32_t a, uint32_t* v) {
  asm volatile("ldmatrix.sync.aligned.m8n8.x4.shared.b16 {%0,%1,%2,%3}, [%4];" : "=r"(v[0]), "=r"(v[1]), "=r"(v[2]), "=r"(v[3]) : "r"(a) : "memory");
}
__device__ __forceinline__ void stsm4(uint32_t a, const uint32_t* v) {
  asm volatile("stmatrix.sync.aligned.m8n8.x4.shared.b16 [%0], {%1,%2,%3,%4};" ::"r"(a), "r"(v[0]), "r"(v[1]), "r"(v[2]), "r"(v[3]) : "memory");
}
__device__ __forceinline__ void sts32(uint32_t a, uint32_t v) { asm volatile("st.shared.u32 [%0], %1;" ::"r"(a), "r"(v) : "memory"); }
__device__ __forceinline__ void st_pkt(uint4* p, uint32_t a, uint32_t b, uint32_t c, uint32_t d) {
  asm volatile("{\n.reg .b128 v;\nmov.b128 v, {%1, %2, %3, %4};\nst.relaxed.gpu.global.b128 [%0], v;\n}\n" ::"l"(p), "r"(a), "r"(b), "r"(c), "r"(d) : "memory");
}
__device__ __forceinline__ uint4 ld_pkt(const uint4* p) {
  uint4 v;
  asm volatile("{\n.reg .b128 v;\nld.relaxed.gpu.global.b128 v, [%4];\nmov.b128 {%0, %1, %2, %3}, v;\n}\n" : "=r"(v.x), "=r"(v.y), "=r"(v.z), "=r"(v.w) : "l"(p) : "memory");
  return v;
}
__device__ __forceinline__ uint4 ldg_nc(const void* p) {
  uint4 v;
  asm volatile("ld.global.nc.v4.u32 {%0,%1,%2,%3}, [%4];" : "=r"(v.x), "=r"(v.y), "=r"(v.z), "=r"(v.w) : "l"(p));
  return v;
}
#define WG_FENCE() asm volatile("wgmma.fence.sync.aligned;" ::: "memory")
#define WG_COMMIT() asm volatile("wgmma.commit_group.sync.aligned;" ::: "memory")
#define WG_WAIT(n) asm volatile("wgmma.wait_group.sync.aligned " #n ";" ::: "memory")
template <int N> __device__ __forceinline__ void reg_fence(float (&d)[N]) {
#pragma unroll
  for (int i = 0; i < N; i++) asm volatile("" : "+f"(d[i])::"memory");
}
template <int N> __device__ __forceinline__ void reg_fence(uint32_t (&d)[N]) {
#pragma unroll
  for (int i = 0; i < N; i++) asm volatile("" : "+r"(d[i])::"memory");
}
__device__ __forceinline__ constexpr uint64_t desc_hi(uint32_t lbo, uint32_t sbo, uint64_t sw) {
  return ((uint64_t)(lbo >> 4) << 16) | ((uint64_t)(sbo >> 4) << 32) | (sw << 62);
}
__device__ __forceinline__ uint64_t mkdesc(uint32_t addr, uint64_t hi) { return hi | (uint64_t)((addr & 0x3FFFF) >> 4); }
__device__ __forceinline__ uint32_t pack_bf16(float lo, float hi) { uint32_t r; asm("cvt.rn.bf16x2.f32 %0, %1, %2;" : "=r"(r) : "f"(hi), "f"(lo)); return r; }
__device__ __forceinline__ float bf_lo(uint32_t v) { return __uint_as_float(v << 16); }
__device__ __forceinline__ float bf_hi(uint32_t v) { return __uint_as_float(v & 0xffff0000u); }
__device__ __forceinline__ uint32_t hadd2(uint32_t a, uint32_t b) { uint32_t r; asm("add.rn.bf16x2 %0, %1, %2;" : "=r"(r) : "r"(a), "r"(b)); return r; }
__device__ __forceinline__ uint32_t hsub2(uint32_t a, uint32_t b) { uint32_t r; asm("sub.rn.bf16x2 %0, %1, %2;" : "=r"(r) : "r"(a), "r"(b)); return r; }
__device__ __forceinline__ uint32_t hmul2(uint32_t a, uint32_t b) { uint32_t r; asm("mul.rn.bf16x2 %0, %1, %2;" : "=r"(r) : "r"(a), "r"(b)); return r; }
__device__ __forceinline__ float rbf(float x) { return __bfloat162float(__float2bfloat16_rn(x)); }
__device__ __forceinline__ float ex2(float x) { float y; asm("ex2.approx.ftz.f32 %0, %1;" : "=f"(y) : "f"(x)); return y; }
__device__ __forceinline__ float rcp(float x) { float y; asm("rcp.approx.ftz.f32 %0, %1;" : "=f"(y) : "f"(x)); return y; }
__device__ __forceinline__ float sigmoid_f(float x) { return rcp(1.f + ex2(x * -1.4426950408889634f)); }
__device__ __forceinline__ float silu_f(float x) { return x * sigmoid_f(x); }

__device__ __forceinline__ void wg_ss192t(float (&d)[96], uint64_t da, uint64_t db, int sd) {
  asm volatile("{\n.reg .pred p;\nsetp.ne.b32 p, %98, 0;\n"
    "wgmma.mma_async.sync.aligned.m64n192k16.f32.bf16.bf16 {%0,%1,%2,%3,%4,%5,%6,%7,%8,%9,%10,%11,%12,%13,%14,%15,%16,%17,%18,%19,%20,%21,%22,%23,%24,%25,%26,%27,%28,%29,%30,%31,%32,%33,%34,%35,%36,%37,%38,%39,%40,%41,%42,%43,%44,%45,%46,%47,%48,%49,%50,%51,%52,%53,%54,%55,%56,%57,%58,%59,%60,%61,%62,%63,%64,%65,%66,%67,%68,%69,%70,%71,%72,%73,%74,%75,%76,%77,%78,%79,%80,%81,%82,%83,%84,%85,%86,%87,%88,%89,%90,%91,%92,%93,%94,%95}, %96, %97, p, 1, 1, 0, 1;\n}\n"
    : "+f"(d[0]),"+f"(d[1]),"+f"(d[2]),"+f"(d[3]),"+f"(d[4]),"+f"(d[5]),"+f"(d[6]),"+f"(d[7]),"+f"(d[8]),"+f"(d[9]),"+f"(d[10]),"+f"(d[11]),"+f"(d[12]),"+f"(d[13]),"+f"(d[14]),"+f"(d[15]),"+f"(d[16]),"+f"(d[17]),"+f"(d[18]),"+f"(d[19]),"+f"(d[20]),"+f"(d[21]),"+f"(d[22]),"+f"(d[23]),"+f"(d[24]),"+f"(d[25]),"+f"(d[26]),"+f"(d[27]),"+f"(d[28]),"+f"(d[29]),"+f"(d[30]),"+f"(d[31]),"+f"(d[32]),"+f"(d[33]),"+f"(d[34]),"+f"(d[35]),"+f"(d[36]),"+f"(d[37]),"+f"(d[38]),"+f"(d[39]),"+f"(d[40]),"+f"(d[41]),"+f"(d[42]),"+f"(d[43]),"+f"(d[44]),"+f"(d[45]),"+f"(d[46]),"+f"(d[47]),"+f"(d[48]),"+f"(d[49]),"+f"(d[50]),"+f"(d[51]),"+f"(d[52]),"+f"(d[53]),"+f"(d[54]),"+f"(d[55]),"+f"(d[56]),"+f"(d[57]),"+f"(d[58]),"+f"(d[59]),"+f"(d[60]),"+f"(d[61]),"+f"(d[62]),"+f"(d[63]),"+f"(d[64]),"+f"(d[65]),"+f"(d[66]),"+f"(d[67]),"+f"(d[68]),"+f"(d[69]),"+f"(d[70]),"+f"(d[71]),"+f"(d[72]),"+f"(d[73]),"+f"(d[74]),"+f"(d[75]),"+f"(d[76]),"+f"(d[77]),"+f"(d[78]),"+f"(d[79]),"+f"(d[80]),"+f"(d[81]),"+f"(d[82]),"+f"(d[83]),"+f"(d[84]),"+f"(d[85]),"+f"(d[86]),"+f"(d[87]),"+f"(d[88]),"+f"(d[89]),"+f"(d[90]),"+f"(d[91]),"+f"(d[92]),"+f"(d[93]),"+f"(d[94]),"+f"(d[95])
    : "l"(da), "l"(db), "r"(sd));
}
__device__ __forceinline__ void wg_rs64(float (&d)[32], uint32_t a0, uint32_t a1, uint32_t a2, uint32_t a3, uint64_t db, int sd) {
  asm volatile("{\n.reg .pred p;\nsetp.ne.b32 p, %37, 0;\n"
    "wgmma.mma_async.sync.aligned.m64n64k16.f32.bf16.bf16 {%0,%1,%2,%3,%4,%5,%6,%7,%8,%9,%10,%11,%12,%13,%14,%15,%16,%17,%18,%19,%20,%21,%22,%23,%24,%25,%26,%27,%28,%29,%30,%31}, {%32,%33,%34,%35}, %36, p, 1, 1, 0;\n}\n"
    : "+f"(d[0]),"+f"(d[1]),"+f"(d[2]),"+f"(d[3]),"+f"(d[4]),"+f"(d[5]),"+f"(d[6]),"+f"(d[7]),"+f"(d[8]),"+f"(d[9]),"+f"(d[10]),"+f"(d[11]),"+f"(d[12]),"+f"(d[13]),"+f"(d[14]),"+f"(d[15]),"+f"(d[16]),"+f"(d[17]),"+f"(d[18]),"+f"(d[19]),"+f"(d[20]),"+f"(d[21]),"+f"(d[22]),"+f"(d[23]),"+f"(d[24]),"+f"(d[25]),"+f"(d[26]),"+f"(d[27]),"+f"(d[28]),"+f"(d[29]),"+f"(d[30]),"+f"(d[31])
    : "r"(a0), "r"(a1), "r"(a2), "r"(a3), "l"(db), "r"(sd));
}
__device__ __forceinline__ void wg_rs192t(float (&d)[96], uint32_t a0, uint32_t a1, uint32_t a2, uint32_t a3, uint64_t db, int sd) {
  asm volatile("{\n.reg .pred p;\nsetp.ne.b32 p, %101, 0;\n"
    "wgmma.mma_async.sync.aligned.m64n192k16.f32.bf16.bf16 {%0,%1,%2,%3,%4,%5,%6,%7,%8,%9,%10,%11,%12,%13,%14,%15,%16,%17,%18,%19,%20,%21,%22,%23,%24,%25,%26,%27,%28,%29,%30,%31,%32,%33,%34,%35,%36,%37,%38,%39,%40,%41,%42,%43,%44,%45,%46,%47,%48,%49,%50,%51,%52,%53,%54,%55,%56,%57,%58,%59,%60,%61,%62,%63,%64,%65,%66,%67,%68,%69,%70,%71,%72,%73,%74,%75,%76,%77,%78,%79,%80,%81,%82,%83,%84,%85,%86,%87,%88,%89,%90,%91,%92,%93,%94,%95}, {%96,%97,%98,%99}, %100, p, 1, 1, 1;\n}\n"
    : "+f"(d[0]),"+f"(d[1]),"+f"(d[2]),"+f"(d[3]),"+f"(d[4]),"+f"(d[5]),"+f"(d[6]),"+f"(d[7]),"+f"(d[8]),"+f"(d[9]),"+f"(d[10]),"+f"(d[11]),"+f"(d[12]),"+f"(d[13]),"+f"(d[14]),"+f"(d[15]),"+f"(d[16]),"+f"(d[17]),"+f"(d[18]),"+f"(d[19]),"+f"(d[20]),"+f"(d[21]),"+f"(d[22]),"+f"(d[23]),"+f"(d[24]),"+f"(d[25]),"+f"(d[26]),"+f"(d[27]),"+f"(d[28]),"+f"(d[29]),"+f"(d[30]),"+f"(d[31]),"+f"(d[32]),"+f"(d[33]),"+f"(d[34]),"+f"(d[35]),"+f"(d[36]),"+f"(d[37]),"+f"(d[38]),"+f"(d[39]),"+f"(d[40]),"+f"(d[41]),"+f"(d[42]),"+f"(d[43]),"+f"(d[44]),"+f"(d[45]),"+f"(d[46]),"+f"(d[47]),"+f"(d[48]),"+f"(d[49]),"+f"(d[50]),"+f"(d[51]),"+f"(d[52]),"+f"(d[53]),"+f"(d[54]),"+f"(d[55]),"+f"(d[56]),"+f"(d[57]),"+f"(d[58]),"+f"(d[59]),"+f"(d[60]),"+f"(d[61]),"+f"(d[62]),"+f"(d[63]),"+f"(d[64]),"+f"(d[65]),"+f"(d[66]),"+f"(d[67]),"+f"(d[68]),"+f"(d[69]),"+f"(d[70]),"+f"(d[71]),"+f"(d[72]),"+f"(d[73]),"+f"(d[74]),"+f"(d[75]),"+f"(d[76]),"+f"(d[77]),"+f"(d[78]),"+f"(d[79]),"+f"(d[80]),"+f"(d[81]),"+f"(d[82]),"+f"(d[83]),"+f"(d[84]),"+f"(d[85]),"+f"(d[86]),"+f"(d[87]),"+f"(d[88]),"+f"(d[89]),"+f"(d[90]),"+f"(d[91]),"+f"(d[92]),"+f"(d[93]),"+f"(d[94]),"+f"(d[95])
    : "r"(a0), "r"(a1), "r"(a2), "r"(a3), "l"(db), "r"(sd));
}
__device__ __forceinline__ void wg_ss160t(float (&d)[80], uint64_t da, uint64_t db, int sd) {
  asm volatile("{\n.reg .pred p;\nsetp.ne.b32 p, %82, 0;\n"
    "wgmma.mma_async.sync.aligned.m64n160k16.f32.bf16.bf16 {%0,%1,%2,%3,%4,%5,%6,%7,%8,%9,%10,%11,%12,%13,%14,%15,%16,%17,%18,%19,%20,%21,%22,%23,%24,%25,%26,%27,%28,%29,%30,%31,%32,%33,%34,%35,%36,%37,%38,%39,%40,%41,%42,%43,%44,%45,%46,%47,%48,%49,%50,%51,%52,%53,%54,%55,%56,%57,%58,%59,%60,%61,%62,%63,%64,%65,%66,%67,%68,%69,%70,%71,%72,%73,%74,%75,%76,%77,%78,%79}, %80, %81, p, 1, 1, 0, 1;\n}\n"
    : "+f"(d[0]),"+f"(d[1]),"+f"(d[2]),"+f"(d[3]),"+f"(d[4]),"+f"(d[5]),"+f"(d[6]),"+f"(d[7]),"+f"(d[8]),"+f"(d[9]),"+f"(d[10]),"+f"(d[11]),"+f"(d[12]),"+f"(d[13]),"+f"(d[14]),"+f"(d[15]),"+f"(d[16]),"+f"(d[17]),"+f"(d[18]),"+f"(d[19]),"+f"(d[20]),"+f"(d[21]),"+f"(d[22]),"+f"(d[23]),"+f"(d[24]),"+f"(d[25]),"+f"(d[26]),"+f"(d[27]),"+f"(d[28]),"+f"(d[29]),"+f"(d[30]),"+f"(d[31]),"+f"(d[32]),"+f"(d[33]),"+f"(d[34]),"+f"(d[35]),"+f"(d[36]),"+f"(d[37]),"+f"(d[38]),"+f"(d[39]),"+f"(d[40]),"+f"(d[41]),"+f"(d[42]),"+f"(d[43]),"+f"(d[44]),"+f"(d[45]),"+f"(d[46]),"+f"(d[47]),"+f"(d[48]),"+f"(d[49]),"+f"(d[50]),"+f"(d[51]),"+f"(d[52]),"+f"(d[53]),"+f"(d[54]),"+f"(d[55]),"+f"(d[56]),"+f"(d[57]),"+f"(d[58]),"+f"(d[59]),"+f"(d[60]),"+f"(d[61]),"+f"(d[62]),"+f"(d[63]),"+f"(d[64]),"+f"(d[65]),"+f"(d[66]),"+f"(d[67]),"+f"(d[68]),"+f"(d[69]),"+f"(d[70]),"+f"(d[71]),"+f"(d[72]),"+f"(d[73]),"+f"(d[74]),"+f"(d[75]),"+f"(d[76]),"+f"(d[77]),"+f"(d[78]),"+f"(d[79])
    : "l"(da), "l"(db), "r"(sd));
}
__device__ __forceinline__ void wg_ss80t(float (&d)[40], uint64_t da, uint64_t db, int sd) {
  asm volatile("{\n.reg .pred p;\nsetp.ne.b32 p, %42, 0;\n"
    "wgmma.mma_async.sync.aligned.m64n80k16.f32.bf16.bf16 {%0,%1,%2,%3,%4,%5,%6,%7,%8,%9,%10,%11,%12,%13,%14,%15,%16,%17,%18,%19,%20,%21,%22,%23,%24,%25,%26,%27,%28,%29,%30,%31,%32,%33,%34,%35,%36,%37,%38,%39}, %40, %41, p, 1, 1, 0, 1;\n}\n"
    : "+f"(d[0]),"+f"(d[1]),"+f"(d[2]),"+f"(d[3]),"+f"(d[4]),"+f"(d[5]),"+f"(d[6]),"+f"(d[7]),"+f"(d[8]),"+f"(d[9]),"+f"(d[10]),"+f"(d[11]),"+f"(d[12]),"+f"(d[13]),"+f"(d[14]),"+f"(d[15]),"+f"(d[16]),"+f"(d[17]),"+f"(d[18]),"+f"(d[19]),"+f"(d[20]),"+f"(d[21]),"+f"(d[22]),"+f"(d[23]),"+f"(d[24]),"+f"(d[25]),"+f"(d[26]),"+f"(d[27]),"+f"(d[28]),"+f"(d[29]),"+f"(d[30]),"+f"(d[31]),"+f"(d[32]),"+f"(d[33]),"+f"(d[34]),"+f"(d[35]),"+f"(d[36]),"+f"(d[37]),"+f"(d[38]),"+f"(d[39])
    : "l"(da), "l"(db), "r"(sd));
}

struct MapPair { CUtensorMap m[2]; };
struct Params {
  const __nv_bfloat16 *x, *wr, *wg, *wu, *wd, *k, *v;
  Scratch* s;
};

__device__ __forceinline__ void side_cta(const Params& p, int sc, unsigned epoch, float* sm) {
  const int tid = threadIdx.x, lane = tid & 31, warp = tid >> 5;
  int budget = WAIT_BUDGET;
  float* s_x = sm;
  float* s_red = sm + 1280;
  float* s_h = s_red + 6144;
  uint4* s_c = (uint4*)(s_h + 768);
  uint2* s_st = (uint2*)(s_c + 16);
  constexpr int DEPTH = 7, STEP = 4 * 6144;
  const uint32_t ring = smem_u32(s_st + 512) + tid * 16;
  const int cg = tid % 96, ks = tid / 96, cd = tid % 80, kd = tid / 80;
  const __nv_bfloat16* wp = (cg < 48 ? p.wg : p.wu) + (size_t)(ks * 160) * FF + sc * 384 + (cg % 48) * 8;
  int kf = 0, pitch = FF;
  uint32_t slot = ring;
  auto refill = [&]() {
    if (kf == 40) { wp = p.wd + (size_t)(sc * 384 + kd * 96) * DM + cd * 8; pitch = DM; }
    if (kf < (tid < 320 ? 64 : 40)) {
#pragma unroll
      for (int j = 0; j < 4; j++) asm volatile("cp.async.cg.shared.global.L2::cache_hint [%0], [%1], 16, %2;" ::"r"(slot + j * 6144), "l"(wp + j * pitch), "l"(POL_FIRST) : "memory");
    }
    asm volatile("cp.async.commit_group;" ::: "memory");
    wp += 4 * pitch; kf++;
    slot += STEP; if (slot == ring + DEPTH * STEP) slot = ring;
  };
  auto gemv = [&](int n, const float* x0, const float* x1, float* out) {
    float a[2][8] = {};
#pragma unroll 1
    for (int k = 0; k < n; k += 4) {
      refill();
      asm volatile("cp.async.wait_group %0;" ::"n"(DEPTH - 1) : "memory");
      const float4 f0 = *(const float4*)(x0 + k), f1 = *(const float4*)(x1 + k);
      const float y0[4] = {f0.x, f0.y, f0.z, f0.w}, y1[4] = {f1.x, f1.y, f1.z, f1.w};
#pragma unroll
      for (int j = 0; j < 4; j++) {
        const uint4 v = lds128(slot + j * 6144);
        const uint32_t u[4] = {v.x, v.y, v.z, v.w};
#pragma unroll
        for (int i = 0; i < 4; i++) {
          a[0][2 * i] += y0[j] * bf_lo(u[i]); a[0][2 * i + 1] += y0[j] * bf_hi(u[i]);
          a[1][2 * i] += y1[j] * bf_lo(u[i]); a[1][2 * i + 1] += y1[j] * bf_hi(u[i]);
        }
      }
    }
#pragma unroll
    for (int i = 0; i < 16; i++) out[(i >> 3) * 768 + (i & 7)] = a[i >> 3][i & 7];
  };
  auto load_row = [&](const __nv_bfloat16* r, uint32_t (&v)[10]) {
    const uint4 a = __ldg((const uint4*)r + lane), b = __ldg((const uint4*)r + 32 + lane);
    const uint2 c = __ldg((const uint2*)r + 128 + lane);
    v[0] = a.x; v[1] = a.y; v[2] = a.z; v[3] = a.w; v[4] = b.x; v[5] = b.y; v[6] = b.z; v[7] = b.w; v[8] = c.x; v[9] = c.y;
  };
  uint32_t wr[10], xb[3][10];
  load_row(p.wr, wr);
#pragma unroll 1
  for (int i = tid; i < 512; i += 384) {
    uint4 v;
    do v = ld_pkt(p.s->stat + sc * 512 + i); while (v.w != epoch + 1 && --budget >= 0);
    s_st[i] = make_uint2(v.x, v.y);
  }
  __syncthreads();
#pragma unroll
  for (int b = 0; b < 3; b++) load_row(p.x + (size_t)(sc * 512 + warp + 12 * b) * DM, xb[b]);
#pragma unroll 1
  for (int k = 0; k < DEPTH - 1; k++) refill();
  float v0 = -INFINITY, v1 = -INFINITY; int i0 = 0xfff, i1 = 0xfff;
  auto better = [](float a, int ia, float b, int ib) { return a > b || (a == b && ia < ib); };
  auto push = [&](float v, int i) {
    if (better(v, i, v0, i0)) { v1 = v0; i1 = i0; v0 = v; i0 = i; }
    else if (better(v, i, v1, i1)) { v1 = v; i1 = i; }
  };
  auto push2 = [&](uint4 c) { push(__uint_as_float(c.x), c.y & 0xfff); push(__uint_as_float(c.z), c.w & 0xfff); };
#pragma unroll 1
  for (int l3 = warp; l3 < 512; l3 += 36) {
#pragma unroll
    for (int b = 0; b < 3; b++) {
      const int lr = l3 + 12 * b;
      if (lr >= 512) break;
      const uint2 st = s_st[lr];
      uint32_t v[10];
#pragma unroll
      for (int i = 0; i < 10; i++) v[i] = hsub2(xb[b][i], st.x);
      if (lr + 36 < 512) load_row(p.x + (size_t)(sc * 512 + lr + 36) * DM, xb[b]);
      float r0 = 0.f, r1 = 0.f;
#pragma unroll
      for (int i = 0; i < 10; i++) {
        const uint32_t xn = pack_bf16(bf_lo(v[i]) * __uint_as_float(st.y), bf_hi(v[i]) * __uint_as_float(st.y));
        r0 = fmaf(bf_lo(xn), bf_lo(wr[i]), r0); r1 = fmaf(bf_hi(xn), bf_hi(wr[i]), r1);
      }
      r0 += r1;
#pragma unroll
      for (int o = 16; o > 0; o >>= 1) r0 += __shfl_xor_sync(~0u, r0, o);
      push(rbf(r0), sc * 512 + lr);
    }
  }
  if (lane == 0) s_c[warp] = make_uint4(__float_as_uint(v0), i0, __float_as_uint(v1), i1);
  __syncthreads();
#pragma unroll 1
  for (int w = 1; w < 12; w++) push2(s_c[(warp + w) % 12]);
  const uint32_t tag = (epoch + 1) << 12;
  if (tid == 0) st_pkt(p.s->cand + sc, __float_as_uint(v0), i0 | tag, __float_as_uint(v1), i1);
  {
    uint4 c;
    do c = ld_pkt(p.s->cand + (lane & 3)); while (((c.y ^ tag) >> 12) && --budget >= 0);
#pragma unroll 1
    for (int w = 1; w < 4; w++) { const int o = (sc + w) & 3; push2(make_uint4(__shfl_sync(~0u, c.x, o), __shfl_sync(~0u, c.y, o), __shfl_sync(~0u, c.z, o), __shfl_sync(~0u, c.w, o))); }
  }
  if (i0 >= SQ) i0 = 0;
  if (i1 >= SQ) i1 = (i0 == 0) ? 1 : 0;
  if (tid < 320) {
    const int row = tid < 160 ? i0 : i1;
    const uint2 u = __ldg((const uint2*)(p.x + (size_t)row * DM) + tid % 160);
    uint4 st;
    do st = ld_pkt(p.s->stat + row); while (st.w != epoch + 1 && --budget >= 0);
    const uint32_t d0 = hsub2(u.x, st.x), d1 = hsub2(u.y, st.x);
    const float inv = __uint_as_float(st.y);
    ((float4*)s_x)[tid] = make_float4(rbf(bf_lo(d0) * inv), rbf(bf_hi(d0) * inv), rbf(bf_lo(d1) * inv), rbf(bf_hi(d1) * inv));
  }
  __syncthreads();
  gemv(160, s_x + ks * 160, s_x + DM + ks * 160, s_red + ks * 1536 + cg * 8);
  __syncthreads();
#pragma unroll
  for (int t = 0; t < 2; t++) {
    float g = 0.f, u = 0.f;
#pragma unroll
    for (int k = 0; k < 4; k++) { g += s_red[(k * 2 + t) * 768 + tid]; u += s_red[(k * 2 + t) * 768 + 384 + tid]; }
    s_h[t * 384 + tid] = rbf(rbf(silu_f(rbf(g))) * rbf(u));
  }
  __syncthreads();
  if (tid < 320) gemv(96, s_h + kd * 96, s_h + 384 + kd * 96, s_red + kd * 1536 + cd * 8);
  __syncthreads();
  const int o4 = tid + (tid < 160 ? 0 : 32);
  if (tid < 320) {
    const float4 *r = (const float4*)s_red + o4, a = r[0], b = r[384], c = r[768], d = r[1152];
    ((float4*)p.s->ffn)[sc * 320 + tid] = make_float4(a.x + b.x + c.x + d.x, a.y + b.y + c.y + d.y, a.z + b.z + c.z + d.z, a.w + b.w + c.w + d.w);
  }
  __syncthreads();
  if (tid == 0) { __threadfence(); s_c[0].x = (atomicAdd(&p.s->flag[FL_SIDE], 1u) & 3u) == 3u; __threadfence(); }
  __syncthreads();
  if (s_c[0].x) {
    if (tid < 320) {
      const float4 *r = (const float4*)p.s->ffn + tid, a = __ldcg(r), b = __ldcg(r + 320), c = __ldcg(r + 640), d = __ldcg(r + 960), x = ((float4*)s_x)[tid];
      const float rs = rbf(sigmoid_f(tid < 160 ? v0 : v1));
      auto gate = [&](float xn, float y) { return silu_f(rbf(xn + rbf(rbf(y) * rs))); };
      if (tid == 0) { p.s->sel[0] = i0; p.s->sel[1] = i1; }
      ((uint2*)p.s->gsel)[tid] =
          make_uint2(pack_bf16(gate(x.x, a.x + b.x + c.x + d.x), gate(x.y, a.y + b.y + c.y + d.y)), pack_bf16(gate(x.z, a.z + b.z + c.z + d.z), gate(x.w, a.w + b.w + c.w + d.w)));
    }
    __syncthreads();
    if (tid == 0) red_release(&p.s->flag[FL_FFN]);
  }
}

constexpr float SM_C = 0.07216878364870322f * 1.4426950408889634f;

__device__ __forceinline__ void ln_row(const Params& p, uint32_t (&uu)[20], int row, int l16, uint32_t tag) {
  const float x0 = bf_lo(__shfl_sync(~0u, uu[0], 0, 16));
  float s0 = 0.f, s1 = 0.f, q0 = 0.f, q1 = 0.f;
#pragma unroll
  for (int i = 0; i < 20; i++) {
    const float a = bf_lo(uu[i]) - x0, b = bf_hi(uu[i]) - x0;
    s0 += a; s1 += b; q0 = fmaf(a, a, q0); q1 = fmaf(b, b, q1);
  }
  s0 += s1; q0 += q1;
#pragma unroll
  for (int o = 8; o > 0; o >>= 1) { s0 += __shfl_xor_sync(~0u, s0, o); q0 += __shfl_xor_sync(~0u, q0, o); }
  s0 *= 1.f / DM;
  const float mean = x0 + s0, var = rbf(fmaxf(fmaf(q0, 1.f / DM, -s0 * s0), 0.f));
  float sd; asm("sqrt.approx.ftz.f32 %0, %1;" : "=f"(sd) : "f"(rbf(var + 1e-5f)));
  const float inv = rcp(rbf(sd)), invc = inv * SM_C;
  const __nv_bfloat162 mb = __float2bfloat162_rn(mean);
  const uint32_t mean2 = *reinterpret_cast<const uint32_t*>(&mb);
  if (l16 == 0) st_pkt(&p.s->stat[row], mean2, __float_as_uint(inv), 0, tag);
#pragma unroll
  for (int i = 0; i < 20; i++) { const uint32_t d = hsub2(uu[i], mean2); uu[i] = pack_bf16(bf_lo(d) * invc, bf_hi(d) * invc); }
#pragma unroll
  for (int i = 0; i < 5; i++) *((uint4*)(p.s->xn + (size_t)row * DM) + i * 16 + l16) = make_uint4(uu[4 * i], uu[4 * i + 1], uu[4 * i + 2], uu[4 * i + 3]);
}

constexpr float SM_HI = 0x1p64f, SM_LO = 0x1p-64f;
__device__ __forceinline__ void exp_block(float (&s)[32], float& l0, float& l1) {
#pragma unroll
  for (int i = 0; i < 32; i++) { s[i] = ex2(s[i]); if (i & 2) l1 += s[i]; else l0 += s[i]; }
}
__device__ __forceinline__ float quad_sum(float v) { v += __shfl_xor_sync(~0u, v, 1); return v + __shfl_xor_sync(~0u, v, 2); }
__device__ __forceinline__ float quad_max(float v) { v = fmaxf(v, __shfl_xor_sync(~0u, v, 1)); return fmaxf(v, __shfl_xor_sync(~0u, v, 2)); }
__device__ __forceinline__ void safe_head(const uint32_t* kp, const uint32_t* vp, const uint32_t (&fq)[48], float (&o)[96], float& l0, float& l1) {
  float m0 = -INFINITY, m1 = -INFINITY;
  l0 = l1 = 0.f;
#pragma unroll
  for (int c = 0; c < 24; c++)
    asm volatile("mma.sync.aligned.m16n8k8.row.col.f32.bf16.bf16.f32 {%0,%1,%2,%3}, {%4,%4}, {%5}, {%6,%6,%6,%6};"
                 : "=f"(o[4 * c]), "=f"(o[4 * c + 1]), "=f"(o[4 * c + 2]), "=f"(o[4 * c + 3])
                 : "r"(0), "r"(c ? __float_as_uint(o[4 * c - 4]) : 0), "f"(0.f));
#pragma unroll 1
  for (int n = 0; n < 128; n++) {
    const uint32_t *kr = kp + (n & 63) * (8 * DH / 2), *vr = vp + (n & 63) * (8 * DH / 2);
    float d[4] = {};
#pragma unroll
    for (int t = 0; t < 12; t++)
      asm volatile("mma.sync.aligned.m16n8k16.row.col.f32.bf16.bf16.f32 {%0,%1,%2,%3}, {%4,%5,%6,%7}, {%8,%9}, {%0,%1,%2,%3};"
                   : "+f"(d[0]), "+f"(d[1]), "+f"(d[2]), "+f"(d[3])
                   : "r"(fq[4 * t]), "r"(fq[4 * t + 1]), "r"(fq[4 * t + 2]), "r"(fq[4 * t + 3]), "r"(__ldg(kr + 8 * t)), "r"(__ldg(kr + 8 * t + 4)));
    if (n < 64) { m0 = quad_max(fmaxf(m0, fmaxf(d[0], d[1]))); m1 = quad_max(fmaxf(m1, fmaxf(d[2], d[3]))); continue; }
    d[0] = ex2(d[0] - m0); d[1] = ex2(d[1] - m0); d[2] = ex2(d[2] - m1); d[3] = ex2(d[3] - m1);
    l0 += quad_sum(d[0] + d[1]); l1 += quad_sum(d[2] + d[3]);
    const uint32_t p0 = pack_bf16(d[0], d[1]), p1 = pack_bf16(d[2], d[3]);
#pragma unroll
    for (int c = 0; c < 24; c++)
      asm volatile("{\n.reg .b32 t;\nmovmatrix.sync.aligned.m8n8.trans.b16 t, %6;\n"
                   "mma.sync.aligned.m16n8k8.row.col.f32.bf16.bf16.f32 {%0,%1,%2,%3}, {%4,%5}, {t}, {%0,%1,%2,%3};\n}\n"
                   : "+f"(o[4 * c]), "+f"(o[4 * c + 1]), "+f"(o[4 * c + 2]), "+f"(o[4 * c + 3]) : "r"(p0), "r"(p1), "r"(__ldg(vr + 4 * c)));
  }
}

__device__ __forceinline__ constexpr int end_stage(int n) { return n < 4 ? n : n == 4 ? 0 : n == 5 ? 4 : n % 5; }
#define Q2N 1
#define SWN 8
#define SCH 0
__device__ __forceinline__ constexpr int send_at(int n) {
  return n <= 6 ? 0 : n <= 10 ? n - 5 : n <= 15 ? n - 5 : SCH == 0 ? n - 5 : SCH == 1 ? (n < 19 ? n - 4 : 15) : SCH == 2 ? (n == 16 ? 12 : n == 17 ? 14 : 15) : 15;
}

__global__ void __launch_bounds__(384, 1)
fused_kernel(const Params p, const __grid_constant__ CUtensorMap tm_x, const __grid_constant__ CUtensorMap tm_xn,
             const __grid_constant__ CUtensorMap tm_wq, const __grid_constant__ CUtensorMap tm_k,
             const __grid_constant__ CUtensorMap tm_v, const __grid_constant__ CUtensorMap tm_wo,
             const __grid_constant__ MapPair tm_w2,
             const __grid_constant__ CUtensorMap tm_xg, const __grid_constant__ CUtensorMap tm_xe,
             const __grid_constant__ CUtensorMap tm_out) {
  extern __shared__ __align__(1024) uint8_t smem_raw[];
  const uint32_t sb = smem_u32(smem_raw);
  const CUtensorMap* const tm_w = tm_w2.m;
  const uint32_t bar_a = sb + OFF_M, bar_b = bar_a + 80, bar_o = bar_b + 96;
  const uint32_t bar_x = bar_o + 8, bar_z = bar_o + 16, bar_s = bar_o + 24, bar_d = bar_o + 32, bar_w = bar_o + 40, bar_e = bar_o + 48,
                 bar_u = bar_o + 96;
  const uint32_t s_stat = bar_a + 512;
  const uint32_t s_sel = s_stat + 1024;
  const int wi = __shfl_sync(~0u, threadIdx.x >> 5, 0), wg = wi >> 2;
  const int lane = threadIdx.x & 31;
  const int cl = blockIdx.x >> 1;
  const int rank = blockIdx.x & 1;

  if (cl >= 64) {
    const unsigned epoch = (unsigned)(__ldcg(&p.s->done) >> 7);
    side_cta(p, blockIdx.x - 128, epoch, (float*)smem_raw);
    return;
  }
  const int qt = (cl >> 3) * 2 + rank, hg = cl & 7;
  const int kq = hg >> 1, nh = hg & 1;

  if (elect()) {
    if (wi < 2) asm volatile("prefetch.tensormap [%0];" ::"l"(wi ? &tm_wq : &tm_x) : "memory");
    const uint32_t c = (uint32_t)((wi < 5 ? 0x7777700000ull : wi < 10 ? 0x752007ffffff0ull : 0ull) >> (12 * (wi % 5)));
    for (int i = 0; i < 3; i++) mbar_init(bar_a + 24 * wi + 8 * i, ((c >> (4 * i)) & 15) + 1);
  }
  asm volatile("fence.mbarrier_init.release.cluster;" ::: "memory");
  cluster_arrive();
  uint32_t xw[20];
  unsigned long long done = 0;
  const int lnrow = qt * 128 + hg * 16 + ((int)(threadIdx.x >> 5) - 4) * 2 + (lane >> 4);
  uint32_t cons; asm volatile("{\n.reg .pred q;\nsetp.ne.u32 q, %1, 0;\nselp.u32 %0, 1, 0, q;\n}" : "=r"(cons) : "r"(wg));
  if (cons) {
#pragma unroll
    for (int i = 0; i < 5; i++) {
      const uint4 v = ldg_nc((const uint4*)(p.x + (size_t)lnrow * DM) + i * 16 + (lane & 15));
      xw[4 * i] = v.x; xw[4 * i + 1] = v.y; xw[4 * i + 2] = v.z; xw[4 * i + 3] = v.w;
    }
    asm volatile("ld.relaxed.gpu.global.u64 %0, [%1];" : "=l"(done) : "l"(&p.s->done));
  }
  if (wg > 0) {
    const int w = wg - 1;
    const int cw = wi - 4;
    asm volatile("setmaxnreg.inc.sync.aligned.u32 232;");
    {
      cluster_wait();
      ln_row(p, xw, lnrow, lane & 15, (unsigned)(done >> 7) + 1);
      __syncwarp();
      if (lane == 0) mbar_arrive(bar_o);
    }
    uint32_t rel_addr;
    asm volatile("mapa.shared::cluster.u32 %0, %1, %2;" : "=r"(rel_addr) : "r"(bar_b + 48), "r"(lane & 1));
    auto rel_a = [&](uint32_t o8) { if (lane == 0) mbar_arrive(bar_a + 40 + o8); };
    auto rel_b = [&](uint32_t o8) { if (lane < 2) mbar_arrive_cluster(rel_addr + o8); };
    uint32_t b8 = 0, phb = 0;
    auto next_pair = [&]() { b8 += 16; if (b8 == 48) { b8 = 0; phb ^= 1; } };
    const int g = lane >> 2, q = lane & 3;
    constexpr uint64_t HI_A = desc_hi(16, 1024, 1);
    constexpr uint64_t HI_W = desc_hi(1024, 3072, 1);
    constexpr uint64_t HI_O = desc_hi(2048, 512, 2);
    if (w == 1) asm volatile("bar.arrive 1, 256;" ::: "memory");

    uint32_t zero; asm volatile("mov.u32 %0, %%tid.y;" : "=r"(zero));
    float acc[96];
    uint32_t fr[48];
    uint4* optr = p.s->o + (size_t)(qt * 192 + hg * 24) * 512 + (cw * 16 + g) * 4 + (q ^ ((g >> 1) & 3));
    uint32_t rl[4];
    auto store_o = [&](int pp, bool on) {
#pragma unroll
      for (int i = (12 * pp + 8) / 9; i < (12 * (pp + 1) + 8) / 9; i++) {
#pragma unroll
        for (int k = 4 * i; k < 4 * i + 4; k++)
          asm volatile("{\n.reg .b32 t;\nmul.rn.bf16x2 t, %0, %2;\nfma.rn.bf16x2 %0, %0, %1, t;\n}\n" : "+r"(fr[k]) : "r"(rl[i & 1]), "r"(rl[2 + (i & 1)]));
        fr[4 * i] &= ~1u;
        if (on) optr[(i >> 1) * 512 + (i & 1) * 32] = make_uint4(fr[4 * i], fr[4 * i + 1], fr[4 * i + 2], fr[4 * i + 3]);
      }
      if (pp == 8 && on) { __syncwarp(); if (lane == 0) mbar_arrive(bar_o); optr += 6 * 512; }
    };
    auto fresh = [&]() { uint32_t v = sb; asm volatile("" : "+r"(v)); return v; };
    reg_fence(fr); reg_fence(rl);

#pragma unroll 1
    for (int u = 0; u < 4; u++) {
      const uint32_t sq = fresh();
      const uint64_t dA = mkdesc(sq + w * 8192, HI_A), dB0 = mkdesc(sq + OFF_B, HI_W);
      uint32_t pb8 = 0;
#pragma unroll
      for (int s = 0; s < 10; s++) {
        const uint32_t o8 = b8 + 8 * (s & 1);
        const uint64_t dW = dB0 + o8 * (TB >> 7);
        mbar_wait(bar_a + 8 * (s % 5), s / 5);
        mbar_wait(bar_b + o8, phb);
        if (s == 9) asm volatile("bar.sync %0, 256;" ::"r"(1 + w) : "memory");
        WG_FENCE();
#pragma unroll
        for (int kk = 0; kk < 4; kk++) wg_ss192t(acc, dA + ((s % 5) * (TA >> 4) + kk * 2), dW + kk * 384, kk != 0 || s != 0);
        WG_COMMIT();
        if (s == 9) asm volatile("bar.arrive %0, 256;" ::"r"(2 - w) : "memory");
        if (s < 9) store_o(s, u > 0);
        if (s > 0) { WG_WAIT(1); rel_a(8 * ((s - 1) % 5)); rel_b(pb8); }
        pb8 = o8;
        if (s & 1) next_pair();
      }
      WG_WAIT(0);
      reg_fence(acc);
      rel_b(pb8);
      if (u == 0) {
        mbar_wait(bar_s, 0);
        const uint2 s0 = lds64(s_stat + (cw * 16 + g) * 8), s1 = lds64(s_stat + 64 + (cw * 16 + g) * 8);
        const uint32_t msk = q == 0 ? 0xffffffffu : q == 1 ? 0xffffu : 0u;
        const float c0 = SM_C * __uint_as_float(s0.y), c1 = SM_C * __uint_as_float(s1.y);
        uint32_t am[4] = {(s0.x ^ 0x80008000u) & msk, (s1.x ^ 0x80008000u) & msk, 0, 0};
        reg_fence(am);
        WG_FENCE();
        wg_rs192t(acc, am[0], am[1], am[2], am[3], mkdesc(sb, desc_hi(1024, 0, 1)), 1);
        WG_COMMIT();
        WG_WAIT(0);
        reg_fence(acc);
#pragma unroll
        for (int i = 0; i < 24; i++) { acc[4 * i] *= c0; acc[4 * i + 1] *= c0; acc[4 * i + 2] *= c1; acc[4 * i + 3] *= c1; }
      }
      rel_a(32);
#pragma unroll
      for (int i = 0; i < 48; i++) fr[i] = pack_bf16(acc[2 * i], acc[2 * i + 1]);
      float sc[32], l0 = 0.f, l1 = 0.f;
      uint32_t pf[16];
      auto pack_p = [&]() {
#pragma unroll
        for (int i = 0; i < 16; i++) pf[i] = pack_bf16(sc[2 * i], sc[2 * i + 1]);
      };
      {
        mbar_wait(bar_b + b8, phb);
        const uint64_t dk = mkdesc(sb + OFF_B, HI_W) + b8 * (TB >> 7);
        asm volatile("bar.sync %0, 256;" ::"r"(1 + w) : "memory");
        WG_FENCE();
#pragma unroll
        for (int t = 0; t < 12; t++) {
          wg_rs64(sc, fr[4 * t], fr[4 * t + 1], fr[4 * t + 2], fr[4 * t + 3], dk + (t >> 2) * 64 + (t & 3) * 2, t != 0);
          if (t == 7) asm volatile("bar.arrive %0, 256;" ::"r"(2 - w) : "memory");
        }
        WG_COMMIT();
        WG_WAIT(0);
        reg_fence(sc);
        rel_b(b8);
        exp_block(sc, l0, l1);
        pack_p();
      }
#pragma unroll 1
      for (int j = 1; j < 8; j++) {
        const uint32_t k8 = b8 + 8;
        mbar_wait(bar_b + k8, phb);
        next_pair();
        mbar_wait(bar_b + b8, phb);
        const uint64_t d0 = mkdesc(sb + OFF_B, HI_W), dk = d0 + k8 * (TB >> 7), dv = d0 + b8 * (TB >> 7);
        asm volatile("bar.sync %0, 256;" ::"r"(1 + w) : "memory");
        WG_FENCE();
#pragma unroll
        for (int t = 0; t < 12; t++) wg_rs64(sc, fr[4 * t], fr[4 * t + 1], fr[4 * t + 2], fr[4 * t + 3], dk + (t >> 2) * 64 + (t & 3) * 2, t != 0);
        WG_COMMIT();
        asm volatile("bar.arrive %0, 256;" ::"r"(2 - w) : "memory");
#pragma unroll
        for (int kk = 0; kk < 4; kk++) wg_rs192t(acc, pf[4 * kk], pf[4 * kk + 1], pf[4 * kk + 2], pf[4 * kk + 3], dv + kk * 384, kk != 0 || j > 1);
        WG_COMMIT();
        WG_WAIT(1);
        reg_fence(sc);
        exp_block(sc, l0, l1);
        rel_b(k8 + (__float_as_uint(l0) & __float_as_uint(l1) & zero));
        WG_WAIT(0);
        reg_fence(acc); reg_fence(pf);
        rel_b(b8);
        pack_p();
      }
      const uint32_t v8 = b8 + 8;
      mbar_wait(bar_b + v8, phb);
      next_pair();
      {
        const uint64_t dv = mkdesc(sb + OFF_B, HI_W) + v8 * (TB >> 7);
        asm volatile("bar.sync %0, 256;" ::"r"(1 + w) : "memory");
        WG_FENCE();
#pragma unroll
        for (int kk = 0; kk < 4; kk++) {
          wg_rs192t(acc, pf[4 * kk], pf[4 * kk + 1], pf[4 * kk + 2], pf[4 * kk + 3], dv + kk * 384, 1);
          if (kk == 1 && (u < 3 || w == 0)) asm volatile("bar.arrive %0, 256;" ::"r"(2 - w) : "memory");
        }
        WG_COMMIT();
      }
      l0 = quad_sum(l0); l1 = quad_sum(l1);
      const bool unsafe = __any_sync(~0u, !(l0 >= SM_LO && l1 >= SM_LO && l0 + l1 <= SM_HI));
      auto set_rl = [&]() {
        l0 = rcp(l0); l1 = rcp(l1);
        rl[0] = pack_bf16(l0, l0); rl[1] = pack_bf16(l1, l1);
        l0 -= bf_lo(rl[0]); l1 -= bf_lo(rl[1]);
        rl[2] = pack_bf16(l0, l0); rl[3] = pack_bf16(l1, l1);
      };
      set_rl();
      WG_WAIT(0);
      reg_fence(acc);
      rel_b(v8);
      if (__builtin_expect(unsafe, 0)) {
        int o = hg * 4 + u; asm volatile("" : "+r"(o));
        o = (o * SKC + (SKC - WIN) + g) * (DH / 2) + q;
        safe_head((const uint32_t*)p.k + o, (const uint32_t*)p.v + o, fr, acc, l0, l1);
        set_rl();
      }
#pragma unroll
      for (int i = 0; i < 24; i++) {
        fr[8 * (i >> 2) + (i & 3)] = pack_bf16(acc[4 * i], acc[4 * i + 1]);
        fr[8 * (i >> 2) + 4 + (i & 3)] = pack_bf16(acc[4 * i + 2], acc[4 * i + 3]);
      }
    }

    float aF[80], aS[80];
    uint32_t pha = 0, a8 = 0, pa8 = 0, pb8 = 0;
#pragma unroll 1
    for (int s = 0; s < 19; s++) {
      const uint64_t d0 = mkdesc(sb, HI_O), dO = d0 + (a8 * (TA >> 7) + w * 256), dB = d0 + ((OFF_B >> 4) + b8 * (TB >> 7));
      mbar_wait(bar_a + a8, pha);
      mbar_wait(bar_b + b8, phb);
      WG_FENCE();
#pragma unroll
      for (int kk = 0; kk < 4; kk++) wg_ss160t(aF, dO + ((kk >> 1) * 512 + (kk & 1) * 2), dB + ((kk >> 1) * 640 + (kk & 1) * 64), kk != 0 || s != 0);
      WG_COMMIT();
      mbar_wait(bar_b + b8 + 8, phb);
      WG_WAIT(1);
      if (s > 0) { rel_a(pa8); rel_b(pb8 + 8); }
      WG_FENCE();
#pragma unroll
      for (int kk = 0; kk < 4; kk++) wg_ss160t(aS, dO + ((kk >> 1) * 512 + (kk & 1) * 2), dB + ((TB >> 4) + (kk >> 1) * 640 + (kk & 1) * 64), kk != 0 || s != 0);
      WG_COMMIT();
      if (s < 9) {
#pragma unroll
        for (int pp = 0; pp < 9; pp++) if (s == pp) store_o(pp, true);
      } else if (s < 15) {
        const int b = 2 * cw + ((lane >> 3) & 1);
        uint32_t ga = sb + OFF_B + TW + ((b * 11) >> 5) * (TB - 3840) + b * 1280 + (lane & 7) * 160 + (lane >> 4) * 16;
        if (s < 14) {
          mbar_wait(bar_x, 0);
          ga += 32 * (s - 9);
          ldsm4(ga, fr);
#pragma unroll
          for (int i = 0; i < 4; i++) {
            const uint2 st = lds64(s_stat + (cw * 16 + g + 8 * (i & 1)) * 8);
            const uint32_t d = hsub2(fr[i], st.x), xn = pack_bf16(bf_lo(d) * __uint_as_float(st.y), bf_hi(d) * __uint_as_float(st.y));
            fr[i] = pack_bf16(silu_f(bf_lo(xn)), silu_f(bf_hi(xn)));
          }
          stsm4(ga, fr);
        } else {
          mbar_wait(bar_u, 0);
          const uint2 sel = lds64(s_sel);
          const uint32_t row = qt * 128 + cw * 16 + (lane & 15);
          if (row == sel.x || row == sel.y) ga = s_sel + 16 + (row == sel.y ? 160 : 0) + (lane >> 4) * 16;
#pragma unroll
          for (int k = 0; k < 5; k++) ldsm4(ga + 32 * k, fr + 4 * k);
        }
      }
      WG_WAIT(1);
      rel_b(b8);
      pa8 = a8; a8 += 8; if (a8 == 40) { a8 = 0; pha ^= 1; }
      pb8 = b8; next_pair();
    }
    const int t128 = threadIdx.x & 127;
    uint4* const xbase = p.s->o + (size_t)(qt * 192 + nh * 24 + 10) * 512 + w * 640 + t128;
    uint4* const dst = xbase + kq * (48 * 512);
    float q1[40], q2[40], oth[40], own[40];
    auto take = [&](float (&x)[40], const float* a) {
#pragma unroll
      for (int k = 0; k < 40; k++) x[k] = __uint_as_float(__float_as_uint(a[k]) ^ zero);
      reg_fence(x);
    };
    reg_fence(aF);
    take(q1, aF);
    uint32_t tx[20] = {};
#pragma unroll
    for (int n = 0; n < 20; n++) {
      const int i = end_stage(n), e = 142 + n / 2, qi = n == 4 ? 1 : n == 5 ? 0 : n / 5;
      float (&acc_)[40] = qi == 0 ? q1 : qi == 1 ? q2 : qi == 2 ? oth : own;
      if (qi == 0) mbar_wait(bar_a + 8 * ((4 + i) % 5), i == 0);
      if (!(n & 1)) mbar_wait(bar_b + 8 * (e % 6), (e / 6) & 1);
      const uint64_t d0 = mkdesc(fresh(), HI_O);
      WG_FENCE();
#pragma unroll
      for (int kk = 0; kk < 4; kk++)
        wg_ss80t(acc_, d0 + w * 256 + (((4 + i) % 5) * (TA >> 4) + (kk >> 1) * 512 + (kk & 1) * 2),
                 d0 + ((OFF_B >> 4) + (e % 6) * (TB >> 4) + (n & 1) * 768 + (kk >> 1) * 384 + (kk & 1) * 64), 1);
      WG_COMMIT();
      if ((!(n & 1) && n <= 16) || n == 15) WG_WAIT(1);
      if (n == 0) rel_a(24);
      if (!(n & 1) && n <= 10) rel_b(8 * ((e - 1) % 6));
      if (n == Q2N) take(q2, aF + 40);
      if (n == SWN) {
        reg_fence(aS);
#pragma unroll
        for (int k = 0; k < 40; k++) { own[k] = kq & 1 ? aS[40 + k] : aS[k]; oth[k] = kq & 1 ? aS[k] : aS[40 + k]; }
        reg_fence(own); reg_fence(oth);
      }
      if (n == 5) mbar_wait(bar_z, 0);
      if (n == 10) cluster_arrive();
      if (n == 12 || n == 14 || n == 16) rel_a(4 * n - 48);
      if (n == 6 || n == 10 || n == 15) {
        float (&fin)[40] = n == 6 ? q1 : n == 10 ? q2 : oth;
        reg_fence(fin);
#pragma unroll
        for (int k = 0; k < 20; k++) tx[k] = pack_bf16(fin[2 * k], fin[2 * k + 1]) | (k & 3 ? 0 : 1);
      }
#pragma unroll
      for (int m = 0; m < 15; m++)
        if (m >= send_at(n) && m < send_at(n + 1)) st_pkt(dst + (m / 5) * 1280 + (m % 5) * 128, tx[4 * (m % 5)], tx[4 * (m % 5) + 1], tx[4 * (m % 5) + 2], tx[4 * (m % 5) + 3]);
    }
    uint32_t xr[20];
    const uint32_t xs = sb + OFF_B + 2 * TB + cw * 2560, xa = xs + (lane & 15) * 160 + (lane >> 4) * 16;
    mbar_wait(bar_b + 16, 1);
#pragma unroll
    for (int k = 0; k < 5; k++) ldsm4(xa + 32 * k, xr + 4 * k);
    {
      auto fetch = [&](int e, uint4 (&v)[5]) {
        mbar_wait(bar_e + 16 * e + 8 * w, 0);
#pragma unroll
        for (int i = 0; i < 5; i++) v[i] = lds128(sb + OFF_B + (3 + e) * TB + (w * 640 + i * 128 + t128) * 16);
      };
      auto add = [&](int e, uint4 (&v)[5]) {
        while (!(v[0].x & v[1].x & v[2].x & v[3].x & v[4].x & 1)) {
#pragma unroll
          for (int i = 0; i < 5; i++) v[i] = ld_pkt(xbase + (kq ^ ((0x132 >> (4 * e)) & 3)) * (48 * 512) + (e < 2 ? kq & 1 : 2) * 1280 + i * 128);
        }
#pragma unroll
        for (int i = 0; i < 5; i++) {
          float* o = own + 8 * i;
          o[0] += bf_lo(v[i].x); o[1] += bf_hi(v[i].x); o[2] += bf_lo(v[i].y); o[3] += bf_hi(v[i].y);
          o[4] += bf_lo(v[i].z); o[5] += bf_hi(v[i].z); o[6] += bf_lo(v[i].w); o[7] += bf_hi(v[i].w);
        }
      };
      WG_WAIT(0);
      reg_fence(own);
#pragma unroll 1
      for (int e = 0; e < 3; e++) { uint4 v[5]; fetch(e, v); add(e, v); }
      if (lane == 0) mbar_arrive(bar_w);
#pragma unroll
      for (int i = 0; i < 20; i++) xr[i] = hadd2(xr[i], hmul2(pack_bf16(own[2 * i], own[2 * i + 1]), fr[i]));
#pragma unroll
      for (int k = 0; k < 5; k++) stsm4(xa + 32 * k, xr + 4 * k);
      asm volatile("fence.proxy.async.shared::cta;" ::: "memory");
      __syncwarp();
      if (elect()) {
        tma2d_store(&tm_out, xs, nh * 320 + kq * 80, qt * 128 + cw * 16);
        asm volatile("cp.async.bulk.commit_group;\ncp.async.bulk.wait_group.read 0;" ::: "memory");
      }
      __syncwarp();
    }
    cluster_wait();
  } else {
    asm volatile("setmaxnreg.dec.sync.aligned.u32 40;");
    uint32_t tid_; asm volatile("mov.u32 %0, %%tid.x;" : "=r"(tid_));
    const int warp = __shfl_sync(~0u, tid_ >> 5, 0);
    auto is_warp = [&](int k) { uint32_t e; asm volatile("{\n.reg .pred q;\nsetp.eq.u32 q, %1, %2;\nselp.u32 %0, 1, 0, q;\n}" : "=r"(e) : "r"(warp), "r"(k)); return e != 0; };
    auto k_block = [&](int t) {
      const int i = (t * 11) >> 5;
      return ((i < 6 ? 2 * kq + (i & 1) : hg ^ (i & 1)) * 4 + (i >> 1)) * 6 + (t == 3 * i ? 4 : 2 * (t - 3 * i) - 2);
    };
    if (warp > 0) {
      const unsigned epoch = (unsigned)(__ldcg(&p.s->done) >> 7);
      int budget = WAIT_BUDGET;
      cluster_wait();
      const uint32_t tag = epoch + 1;
      mbar_wait(bar_b, 0, budget); mbar_wait(bar_b + 8, 0, budget);
      float cs0 = 0.f, cs1 = 0.f;
      const int n = rank * 96 + (warp - 1) * 32 + (lane & 15) * 2;
#pragma unroll 1
      for (int kg = ((qt >> 1) & 3) * 2 + (lane >> 4) * 5, e = kg + 5; kg < e; kg++) {
        const uint32_t ad = sb + OFF_B + kg * 3072 + (n >> 6) * 1024 + (n & 63) * 2;
#pragma unroll
        for (int k = 0; k < 8; k++) { const uint32_t v = lds32(ad ^ (k * 0x90)); cs0 += bf_lo(v); cs1 += bf_hi(v); }
      }
      cs0 += __shfl_xor_sync(~0u, cs0, 16); cs1 += __shfl_xor_sync(~0u, cs1, 16);
      if (lane < 16) st_pkt(p.s->cs + (hg * 8 + (qt >> 1)) * 96 + (n >> 1), __float_as_uint(cs0), __float_as_uint(cs1), 0, tag);
      mbar_wait(bar_a + 40, 0, budget);
      if (lane < 2) { uint32_t a; asm volatile("mapa.shared::cluster.u32 %0, %1, %2;" : "=r"(a) : "r"(bar_d), "r"(lane)); mbar_arrive_cluster(a); }
      cs0 = cs1 = 0.f;
#pragma unroll 1
      for (int e = is_warp(3) ? 0 : 1; e < 3; e++) {
        const uint4* src = e ? p.s->cs + (hg * 8 + 4 * e - 4) * 96 + (tid_ - 32) : p.s->stat + qt * 128 + lane;
        const int step = e ? 96 : 32;
        uint4 v[4];
        while (true) {
          uint32_t bad = 0;
#pragma unroll
          for (int i = 0; i < 4; i++) v[i] = ld_pkt(src + i * step);
#pragma unroll
          for (int i = 0; i < 4; i++) bad |= v[i].w ^ tag;
          if (!__any_sync(~0u, bad) || --budget < 0) break;
        }
#pragma unroll
        for (int i = 0; i < 4; i++) {
          if (e) { cs0 += __uint_as_float(v[i].x); cs1 += __uint_as_float(v[i].y); }
          else { sts32(s_stat + (i * 32 + lane) * 8, v[i].x); sts32(s_stat + 4 + (i * 32 + lane) * 8, v[i].y); }
        }
      }
      mbar_wait(bar_a + 40, 1, budget);
#pragma unroll 1
      for (int k = 0; k < 8; k++) {
        const uint32_t v = pack_bf16(cs0, cs1);
        sts32((sb + ((tid_ - 32) >> 5) * 1024 + lane * 4) ^ (k * 0x90), k < 3 ? v : 0);
        cs0 -= bf_lo(v); cs1 -= bf_hi(v);
      }
      asm volatile("fence.proxy.async.shared::cta;" ::: "memory");
      __syncwarp();
      if (lane == 0) mbar_arrive(bar_s);
      if (is_warp(1)) {
#pragma unroll 1
        for (int u = 0; u < 5; u++) {
          mbar_wait(bar_o, u & 1);
          if (lane == 0) red_release(&p.s->flag[u ? FL_O + (qt * 8 + hg) * 8 : FL_XN + qt * 32]);
          __syncwarp();
        }
      } else if (is_warp(2)) {
        mbar_wait(bar_x, 0, budget);
        while ((int)(ld_acquire(&p.s->flag[FL_FFN]) - tag) < 0 && --budget >= 0) {}
        if (lane < 21) {
          const uint4 v = __ldcg(lane ? (const uint4*)(p.s->gsel + (lane > 10 ? DM - 80 : 0) + nh * 320 + kq * 80) + lane - 1 : (const uint4*)p.s->sel);
          asm volatile("st.shared.v4.u32 [%0], {%1,%2,%3,%4};" ::"r"(s_sel + 16 * lane), "r"(v.x), "r"(v.y), "r"(v.z), "r"(v.w) : "memory");
        }
        __syncwarp();
        if (lane == 0) { mbar_arrive(bar_u); asm volatile("red.relaxed.gpu.global.add.u64 [%0], 1;" ::"l"(&p.s->done) : "memory"); }
        mbar_wait(bar_w, 0, budget);
        if (budget < 0) asm volatile("st.global.u32 [%0], %1;" ::"l"(0ull), "r"(budget) : "memory");
      } else {
        wait_flag(&p.s->flag[FL_XN + qt * 32], (epoch + 1) * 8);
        fence_proxy_async();
        mbar_wait(bar_a + 72, 1);
        uint32_t a8 = 0, pha = 1;
        const int kb = (qt * 192 + k_block(lane)) * 512;
#pragma unroll 1
        for (int n = 0; n < 54; n++) {
          const int t = n - 30, ko = __shfl_sync(~0u, kb, t);
          if (t == 0 || t == 18) {
            wait_flag(&p.s->flag[FL_O + (qt * 8 + (t ? 2 * kq + (lane & 1) : lane & 7)) * 8], epoch * 4 + (t ? 4 : 3));
            fence_proxy_async();
          }
          mbar_wait(bar_a + 40 + a8, pha);
          const uint32_t fb = bar_a + a8, dst = sb + a8 * (TA >> 3);
          if (elect()) {
            if (t >= 0) {
              mbar_expect_tx(fb, TA);
              bulk_load(dst, p.s->o + ko, TA, fb);
              if (t == 8) {
                mbar_expect_tx(bar_x, 6 * 3840);
#pragma unroll 1
                for (int e = 0; e < 6; e++) tma2d(sb + OFF_B + TW + e * TB, &tm_xg, nh * 320 + kq * 80, qt * 128 + e * 24, bar_x);
                asm volatile("prefetch.tensormap [%0];\nprefetch.tensormap [%1];\nprefetch.tensormap [%2];\nprefetch.tensormap [%3];"
                             ::"l"(tm_w), "l"(tm_w + 1), "l"(&tm_xe), "l"(&tm_out) : "memory");
              }
              if (t == 22) asm volatile("red.relaxed.gpu.global.add.u32 [%0], 1;" ::"l"(&p.s->flag[FL_RD + (qt * 8 + hg) * 8]) : "memory");
            } else if (n >= 10 && pha) mbar_arrive(fb);
            else { mbar_expect_tx(fb, TA); tma2d(dst, &tm_xn, 8 * a8 + (pha || (n >= 15 && n < 20) ? 0 : 320), qt * 128, fb); }
          }
          a8 += 8; if (a8 == 40) { a8 = 0; pha ^= 1; }
        }
        wait_flag(&p.s->flag[FL_RD + (qt * 8 + (hg ^ 1)) * 8], tag);
        if (lane == 0) mbar_arrive(bar_z);
      }
    } else {
      cluster_wait();
      uint32_t fb = bar_b, dst = sb + OFF_B, ph = 1;
      auto next = [&]() { fb += 8; dst += TB; if (fb == bar_b + 48) { fb = bar_b; dst = sb + OFF_B; ph ^= 1; } };
#pragma unroll 1
      for (int u = 0; u < 4; u++) {
        const int h = hg * 4 + u;
        int s = u ? (u == 2 ? 5 : 0) : (5 * (qt >> 1)) >> 2;
#pragma unroll 1
        for (int i = 0; i < 10; i++) {
          if (u == 0) {
            const uint32_t a8 = 8 * (i < 5 ? i : i - 5);
            mbar_wait(bar_a + 40 + a8, i < 5);
            if (elect()) { mbar_expect_tx(bar_a + a8, TA); tma2d(sb + a8 * (TA >> 3), &tm_x, 64 * s, qt * 128, bar_a + a8); }
            if (i == 6) mbar_wait(bar_d, 0);
          }
          mbar_wait(fb + 48, ph);
          if (elect()) { mbar_expect_tx(fb, TB); tma4d_mc(dst + rank * (TB / 2), &tm_wq, 3 * h, 8 * s + 4 * rank, fb); }
          next();
          if (++s == 10) s = 0;
        }
        const int kv0 = (h * SKC + (SKC - WIN)) / 8 + 4 * rank;
#pragma unroll 1
        for (int i = 0; i < 16; i++) {
          const bool isk = (0x2AAB >> i) & 1;
          mbar_wait(fb + 48, ph);
          if (elect()) { mbar_expect_tx(fb, TB); tma4d_mc(dst + rank * (TB / 2), isk ? &tm_k : &tm_v, 0, kv0 + 8 * (isk ? (i + 1) >> 1 : (i - 1) >> 1), fb); }
          next();
        }
      }
      const int cF = 10 * nh + 5 - 5 * (kq >> 1), cS = 10 * nh + 5 * (kq >> 1);
      const int kb = 4 * (k_block(lane) + rank);
#pragma unroll 1
      for (int m = 0; m < 38; m++) {
        const int c2 = __shfl_sync(~0u, kb, m >> 1);
        mbar_wait(fb + 48, ph);
        if (elect()) { mbar_expect_tx(fb, TW); tma5d_mc(dst + rank * (TW / 2), &tm_wo, c2, m & 1 ? cS : cF, fb); }
        next();
      }
      const int odd = ((0x7fd0 ^ (kq & 1 ? 0xffc00 : 0)) >> lane) & 1;
      const int tq = __shfl_sync(~0u, kb, 19 + end_stage(lane)) << 16 | odd << 7 | ((lane < 10 ? cF : cS) + 2 * odd);
#pragma unroll 1
      for (int n = 0; n < 20; n += 2) {
        const int t0 = __shfl_sync(~0u, tq, n), t1 = __shfl_sync(~0u, tq, n + 1);
        mbar_wait(fb + 48, ph);
        if (elect()) {
          mbar_expect_tx(fb, TB);
          tma5d_mc(dst + rank * (TB / 4), (const CUtensorMap*)((const char*)tm_w + (t0 & 128)), t0 >> 16, t0 & 31, fb);
          tma5d_mc(dst + TB / 2 + rank * (TB / 4), (const CUtensorMap*)((const char*)tm_w + (t1 & 128)), t1 >> 16, t1 & 31, fb);
        }
        next();
      }
      mbar_wait(fb + 48, ph);
      if (elect()) { mbar_expect_tx(fb, TW); tma2d(dst, &tm_xe, nh * 320 + kq * 80, qt * 128, fb); }
    }
    if (!is_warp(2)) {
      const int e = warp - (warp >> 1), ms = 2 * e + ((lane >> 2) & 1);
      const uint4* src = p.s->o + (size_t)(qt * 192 + nh * 24 + 10 + (kq ^ ((0x132 >> (4 * e)) & 3)) * 48) * 512 + (e < 2 ? kq & 1 : 2) * 1280 + (ms & 1) * 640;
      uint32_t todo = 0xff;
      bool ok = lane >= 8;
      mbar_wait(bar_z, 0);
#pragma unroll 1
      while (todo) {
        if (!ok) ok = ld_pkt(src + 4 * 128 + (lane & 3) * 32 + 31).x & 1;
        const uint32_t got = __ballot_sync(~0u, ok) & todo, go = __ballot_sync(~0u, ((got >> (lane & 28)) & 15) == 15);
        if (go) mbar_wait(bar_a + 40 + 8 * e, 0);
        if ((go & 0x11) >> lane & 1) {
          mbar_expect_tx(bar_e + 8 * ms, TW / 2); bulk_load(sb + OFF_B + (3 + e) * TB + (ms & 1) * (TW / 2), src, TW / 2, bar_e + 8 * ms);
        }
        todo &= ~go;
      }
    }
    cluster_sync();
  }
}

typedef CUresult (*EncodeFn)(CUtensorMap*, CUtensorMapDataType, cuuint32_t, void*, const cuuint64_t*, const cuuint64_t*,
                             const cuuint32_t*, const cuuint32_t*, CUtensorMapInterleave, CUtensorMapSwizzle,
                             CUtensorMapL2promotion, CUtensorMapFloatOOBfill);

void encode(EncodeFn fn, CUtensorMap* tm, void* base, int rank, const cuuint64_t* dims, const cuuint64_t* strides,
            const cuuint32_t* box, CUtensorMapSwizzle sw) {
  const cuuint32_t es[5] = {1, 1, 1, 1, 1};
  fn(tm, CU_TENSOR_MAP_DATA_TYPE_BFLOAT16, rank, base, dims, strides, box, es, CU_TENSOR_MAP_INTERLEAVE_NONE, sw,
     CU_TENSOR_MAP_L2_PROMOTION_L2_128B, CU_TENSOR_MAP_FLOAT_OOB_FILL_NONE);
}

}

extern "C" void kernel_launch(void* const* d_in, const int* in_sizes, int n_in, void* d_out, int out_size) {
  static EncodeFn fn = nullptr;
  static Scratch* scr = nullptr;
  if (!fn) {
    void* f = nullptr;
    cudaDriverEntryPointQueryResult st;
    cudaGetDriverEntryPoint("cuTensorMapEncodeTiled", &f, cudaEnableDefault, &st);
    fn = (EncodeFn)f;
    cudaGetSymbolAddress((void**)&scr, g_scratch);
    cudaFuncSetAttribute(fused_kernel, cudaFuncAttributeMaxDynamicSharedMemorySize, SMEM_BYTES);
  }
  CUtensorMap tm_x, tm_xn, tm_wq, tm_k, tm_v, tm_wo, tm_xg, tm_xe, tm_out;
  MapPair tm_w2;
  { const cuuint64_t d[2] = {DM, SQ}, s[1] = {DM * 2}; const cuuint32_t b[2] = {64, 128};
    encode(fn, &tm_x, d_in[0], 2, d, s, b, CU_TENSOR_MAP_SWIZZLE_128B);
    encode(fn, &tm_xn, scr->xn, 2, d, s, b, CU_TENSOR_MAP_SWIZZLE_128B); }
  { const cuuint64_t d[4] = {64, 8, QD / 64, DM / 8}, s[3] = {QD * 2, 128, 8 * QD * 2}; const cuuint32_t b[4] = {64, 8, 3, 4};
    encode(fn, &tm_wq, d_in[3], 4, d, s, b, CU_TENSOR_MAP_SWIZZLE_128B); }
  { const cuuint64_t d[4] = {64, 8, 3, NH * SKC / 8}, s[3] = {DH * 2, 128, 8 * DH * 2}; const cuuint32_t b[4] = {64, 8, 3, 4};
    encode(fn, &tm_k, d_in[1], 4, d, s, b, CU_TENSOR_MAP_SWIZZLE_128B);
    encode(fn, &tm_v, d_in[2], 4, d, s, b, CU_TENSOR_MAP_SWIZZLE_128B); }
  {
    const cuuint64_t d[5] = {32, 2, QD / 8, 4, DM / 32}, s[4] = {DM * 2, 8 * DM * 2, 2 * DM * 2, 64}; const cuuint32_t b[5] = {32, 2, 4, 4, 5};
    encode(fn, &tm_wo, d_in[4], 5, d, s, b, CU_TENSOR_MAP_SWIZZLE_64B);
    const cuuint32_t b3[5] = {32, 2, 4, 4, 3};
    encode(fn, &tm_w2.m[0], d_in[4], 5, d, s, b3, CU_TENSOR_MAP_SWIZZLE_64B);
    encode(fn, &tm_w2.m[1], (char*)d_in[4] + 32, 5, d, s, b3, CU_TENSOR_MAP_SWIZZLE_64B); }
  { const cuuint64_t d[2] = {DM, SQ}, s[1] = {DM * 2}; const cuuint32_t bg[2] = {80, 24}, bx[2] = {80, 128}, bo[2] = {80, 16};
    encode(fn, &tm_xg, d_in[0], 2, d, s, bg, CU_TENSOR_MAP_SWIZZLE_NONE);
    encode(fn, &tm_xe, d_in[0], 2, d, s, bx, CU_TENSOR_MAP_SWIZZLE_NONE);
    encode(fn, &tm_out, d_out, 2, d, s, bo, CU_TENSOR_MAP_SWIZZLE_NONE); }
  Params p;
  p.x = (const __nv_bfloat16*)d_in[0]; p.wr = (const __nv_bfloat16*)d_in[6]; p.wg = (const __nv_bfloat16*)d_in[7];
  p.wu = (const __nv_bfloat16*)d_in[8]; p.wd = (const __nv_bfloat16*)d_in[9];

  p.k = (const __nv_bfloat16*)d_in[1]; p.v = (const __nv_bfloat16*)d_in[2]; p.s = scr;
  cudaLaunchConfig_t cfg = {};
  cfg.gridDim = dim3(132); cfg.blockDim = dim3(384); cfg.dynamicSmemBytes = SMEM_BYTES; cfg.stream = cudaStreamPerThread;
  cudaLaunchAttribute at[1];
  at[0].id = cudaLaunchAttributeClusterDimension; at[0].val.clusterDim.x = 2; at[0].val.clusterDim.y = 1; at[0].val.clusterDim.z = 1;
  cfg.attrs = at; cfg.numAttrs = 1;
  cudaLaunchKernelEx(&cfg, fused_kernel, p, tm_x, tm_xn, tm_wq, tm_k, tm_v, tm_wo, tm_w2, tm_xg, tm_xe, tm_out);
}
```

```cpp
#include <cuda_runtime.h>
#include <cuda_bf16.h>
#include <cuda.h>
#include <stdint.h>

namespace {

constexpr int SQ = 2048, DM = 640, NH = 32, DH = 192, SKC = 2048, WIN = 512, FF = 1536;
constexpr int QD = NH * DH;
constexpr uint32_t TA = 16384, TB = 24576, TW = 20480, OFF_B = 5 * TA, OFF_M = OFF_B + 6 * TB, SMEM_BYTES = OFF_M + 3072;
constexpr int WAIT_BUDGET = 1 << 20;

constexpr int FL_XN = 0;
constexpr int FL_O = 512;
constexpr int FL_RD = FL_O + 1024;
constexpr int FL_FFN = FL_RD + 1024;
constexpr int FL_SIDE = FL_FFN + 32;
struct __align__(1024) Scratch {
  unsigned long long done, pad0[15];
  unsigned flag[FL_SIDE + 32];
  uint4 cand[8];
  float ffn[4 * 2 * DM];
  int sel[4];
  __nv_bfloat16 gsel[2 * DM];
  uint4 cs[8 * 8 * DH / 2];
  uint4 stat[SQ];
  __align__(1024) __nv_bfloat16 xn[SQ * DM];
  __align__(1024) uint4 o[SQ * QD / 8];
};
__device__ Scratch g_scratch;

__device__ __forceinline__ uint32_t smem_u32(const void* p) { return (uint32_t)__cvta_generic_to_shared(p); }
__device__ __forceinline__ void mbar_init(uint32_t bar, int cnt) { asm volatile("mbarrier.init.shared::cta.b64 [%0], %1;" ::"r"(bar), "r"(cnt)); }
__device__ __forceinline__ void mbar_expect_tx(uint32_t bar, uint32_t bytes) {
  asm volatile("mbarrier.arrive.expect_tx.shared::cta.b64 _, [%0], %1;" ::"r"(bar), "r"(bytes) : "memory");
}
__device__ __forceinline__ void mbar_arrive(uint32_t bar) { asm volatile("mbarrier.arrive.shared::cta.b64 _, [%0];" ::"r"(bar) : "memory"); }
__device__ __forceinline__ void mbar_arrive_cluster(uint32_t addr) { asm volatile("mbarrier.arrive.shared::cluster.b64 _, [%0];" ::"r"(addr) : "memory"); }
__device__ __forceinline__ bool mbar_try(uint32_t bar, uint32_t parity) {
  uint32_t ok;
  asm volatile("{\n.reg .pred p;\nmbarrier.try_wait.parity.shared::cta.b64 p, [%1], %2;\nselp.u32 %0, 1, 0, p;\n}\n" : "=r"(ok) : "r"(bar), "r"(parity) : "memory");
  return ok;
}
__device__ __forceinline__ void mbar_wait(uint32_t bar, uint32_t parity, int& budget) {
#pragma unroll 1
  while (!mbar_try(bar, parity)) { if (--budget < 0) break; }
}
__device__ __forceinline__ void mbar_wait(uint32_t bar, uint32_t parity) {
#pragma unroll 1
  while (!mbar_try(bar, parity)) {}
}
__device__ __forceinline__ unsigned ld_acquire(const unsigned* p) { unsigned v; asm volatile("ld.acquire.gpu.global.u32 %0, [%1];" : "=r"(v) : "l"(p) : "memory"); return v; }
__device__ __forceinline__ void wait_flag(const unsigned* p, unsigned target) {
#pragma unroll 1
  while (__any_sync(~0u, (int)(ld_acquire(p) - target) < 0)) {}
}
__device__ __forceinline__ void red_release(unsigned* p) { asm volatile("red.release.gpu.global.add.u32 [%0], 1;" ::"l"(p) : "memory"); }
__device__ __forceinline__ void fence_proxy_async() { asm volatile("fence.proxy.async.global;" ::: "memory"); }
__device__ __forceinline__ bool elect() {
  uint32_t p;
  asm volatile("{\n.reg .pred P;\nelect.sync _|P, 0xffffffff;\nselp.u32 %0, 1, 0, P;\n}\n" : "=r"(p));
  return p;
}
__device__ __forceinline__ void cluster_arrive() { asm volatile("barrier.cluster.arrive.relaxed.aligned;" ::: "memory"); }
__device__ __forceinline__ void cluster_wait() { asm volatile("barrier.cluster.wait.aligned;" ::: "memory"); }
__device__ __forceinline__ void cluster_sync() { cluster_arrive(); cluster_wait(); }
__device__ __forceinline__ void tma2d(uint32_t dst, const CUtensorMap* tm, int c0, int c1, uint32_t bar) {
  asm volatile("cp.async.bulk.tensor.2d.shared::cluster.global.mbarrier::complete_tx::bytes [%0], [%1, {%3, %4}], [%2];"
               ::"r"(dst), "l"(tm), "r"(bar), "r"(c0), "r"(c1) : "memory");
}
constexpr uint64_t POL_FIRST = 0x12F0000000000000ull;
__device__ __forceinline__ void tma4d_mc(uint32_t dst, const CUtensorMap* tm, int c2, int c3, uint32_t bar) {
  asm volatile("cp.async.bulk.tensor.4d.shared::cluster.global.mbarrier::complete_tx::bytes.multicast::cluster.L2::cache_hint [%0], [%1, {%3, %3, %4, %5}], [%2], %6, %7;"
               ::"r"(dst), "l"(tm), "r"(bar), "r"(0), "r"(c2), "r"(c3), "h"((uint16_t)3), "l"(POL_FIRST) : "memory");
}
__device__ __forceinline__ void tma5d_mc(uint32_t dst, const CUtensorMap* tm, int c2, int c4, uint32_t bar) {
  asm volatile("cp.async.bulk.tensor.5d.shared::cluster.global.mbarrier::complete_tx::bytes.multicast::cluster.L2::cache_hint [%0], [%1, {%3, %3, %4, %3, %5}], [%2], %6, %7;"
               ::"r"(dst), "l"(tm), "r"(bar), "r"(0), "r"(c2), "r"(c4), "h"((uint16_t)3), "l"(POL_FIRST) : "memory");
}
__device__ __forceinline__ void bulk_load(uint32_t dst, const void* src, uint32_t bytes, uint32_t bar) {
  asm volatile("cp.async.bulk.shared::cluster.global.mbarrier::complete_tx::bytes.L2::cache_hint [%0], [%1], %2, [%3], %4;" ::"r"(dst), "l"(src), "r"(bytes), "r"(bar), "l"(POL_FIRST) : "memory");
}
__device__ __forceinline__ void tma2d_store(const CUtensorMap* tm, uint32_t src, int c0, int c1) {
  asm volatile("cp.async.bulk.tensor.2d.global.shared::cta.bulk_group [%0, {%2, %3}], [%1];" ::"l"(tm), "r"(src), "r"(c0), "r"(c1) : "memory");
}
__device__ __forceinline__ uint32_t lds32(uint32_t a) { uint32_t v; asm volatile("ld.shared.u32 %0, [%1];" : "=r"(v) : "r"(a) : "memory"); return v; }
__device__ __forceinline__ uint2 lds64(uint32_t a) { uint2 v; asm volatile("ld.shared.v2.u32 {%0,%1}, [%2];" : "=r"(v.x), "=r"(v.y) : "r"(a) : "memory"); return v; }
__device__ __forceinline__ uint4 lds128(uint32_t a) { uint4 v; asm volatile("ld.shared.v4.u32 {%0,%1,%2,%3}, [%4];" : "=r"(v.x), "=r"(v.y), "=r"(v.z), "=r"(v.w) : "r"(a) : "memory"); return v; }
__device__ __forceinline__ void ldsm4(uint32_t a, uint32_t* v) {
  asm volatile("ldmatrix.sync.aligned.m8n8.x4.shared.b16 {%0,%1,%2,%3}, [%4];" : "=r"(v[0]), "=r"(v[1]), "=r"(v[2]), "=r"(v[3]) : "r"(a) : "memory");
}
__device__ __forceinline__ void stsm4(uint32_t a, const uint32_t* v) {
  asm volatile("stmatrix.sync.aligned.m8n8.x4.shared.b16 [%0], {%1,%2,%3,%4};" ::"r"(a), "r"(v[0]), "r"(v[1]), "r"(v[2]), "r"(v[3]) : "memory");
}
__device__ __forceinline__ void sts32(uint32_t a, uint32_t v) { asm volatile("st.shared.u32 [%0], %1;" ::"r"(a), "r"(v) : "memory"); }
__device__ __forceinline__ void st_pkt(uint4* p, uint32_t a, uint32_t b, uint32_t c, uint32_t d) {
  asm volatile("st.relaxed.gpu.global.v4.b32 [%0], {%1, %2, %3, %4};" ::"l"(p), "r"(a), "r"(b), "r"(c), "r"(d) : "memory");
}
__device__ __forceinline__ uint4 ld_pkt(const uint4* p) {
  uint4 v;
  asm volatile("{\n.reg .b128 v;\nld.relaxed.gpu.global.b128 v, [%4];\nmov.b128 {%0, %1, %2, %3}, v;\n}\n" : "=r"(v.x), "=r"(v.y), "=r"(v.z), "=r"(v.w) : "l"(p) : "memory");
  return v;
}
__device__ __forceinline__ uint4 ldg_nc(const void* p) {
  uint4 v;
  asm volatile("ld.global.nc.v4.u32 {%0,%1,%2,%3}, [%4];" : "=r"(v.x), "=r"(v.y), "=r"(v.z), "=r"(v.w) : "l"(p));
  return v;
}
#define WG_FENCE() asm volatile("wgmma.fence.sync.aligned;" ::: "memory")
#define WG_COMMIT() asm volatile("wgmma.commit_group.sync.aligned;" ::: "memory")
#define WG_WAIT(n) asm volatile("wgmma.wait_group.sync.aligned " #n ";" ::: "memory")
template <int N> __device__ __forceinline__ void reg_fence(float (&d)[N]) {
#pragma unroll
  for (int i = 0; i < N; i++) asm volatile("" : "+f"(d[i])::"memory");
}
template <int N> __device__ __forceinline__ void reg_fence(uint32_t (&d)[N]) {
#pragma unroll
  for (int i = 0; i < N; i++) asm volatile("" : "+r"(d[i])::"memory");
}
__device__ __forceinline__ constexpr uint64_t desc_hi(uint32_t lbo, uint32_t sbo, uint64_t sw) {
  return ((uint64_t)(lbo >> 4) << 16) | ((uint64_t)(sbo >> 4) << 32) | (sw << 62);
}
__device__ __forceinline__ uint64_t mkdesc(uint32_t addr, uint64_t hi) { return hi | (uint64_t)((addr & 0x3FFFF) >> 4); }
__device__ __forceinline__ uint32_t pack_bf16(float lo, float hi) { uint32_t r; asm("cvt.rn.bf16x2.f32 %0, %1, %2;" : "=r"(r) : "f"(hi), "f"(lo)); return r; }
__device__ __forceinline__ float bf_lo(uint32_t v) { return __uint_as_float(v << 16); }
__device__ __forceinline__ float bf_hi(uint32_t v) { return __uint_as_float(v & 0xffff0000u); }
__device__ __forceinline__ uint32_t hadd2(uint32_t a, uint32_t b) { uint32_t r; asm("add.rn.bf16x2 %0, %1, %2;" : "=r"(r) : "r"(a), "r"(b)); return r; }
__device__ __forceinline__ uint32_t hsub2(uint32_t a, uint32_t b) { uint32_t r; asm("sub.rn.bf16x2 %0, %1, %2;" : "=r"(r) : "r"(a), "r"(b)); return r; }
__device__ __forceinline__ uint32_t hmul2(uint32_t a, uint32_t b) { uint32_t r; asm("mul.rn.bf16x2 %0, %1, %2;" : "=r"(r) : "r"(a), "r"(b)); return r; }
__device__ __forceinline__ float rbf(float x) { return __bfloat162float(__float2bfloat16_rn(x)); }
__device__ __forceinline__ float ex2(float x) { float y; asm("ex2.approx.ftz.f32 %0, %1;" : "=f"(y) : "f"(x)); return y; }
__device__ __forceinline__ float rcp(float x) { float y; asm("rcp.approx.ftz.f32 %0, %1;" : "=f"(y) : "f"(x)); return y; }
__device__ __forceinline__ float sigmoid_f(float x) { return rcp(1.f + ex2(x * -1.4426950408889634f)); }
__device__ __forceinline__ float silu_f(float x) { return x * sigmoid_f(x); }

__device__ __forceinline__ void wg_ss192t(float (&d)[96], uint64_t da, uint64_t db, int sd) {
  asm volatile("{\n.reg .pred p;\nsetp.ne.b32 p, %98, 0;\n"
    "wgmma.mma_async.sync.aligned.m64n192k16.f32.bf16.bf16 {%0,%1,%2,%3,%4,%5,%6,%7,%8,%9,%10,%11,%12,%13,%14,%15,%16,%17,%18,%19,%20,%21,%22,%23,%24,%25,%26,%27,%28,%29,%30,%31,%32,%33,%34,%35,%36,%37,%38,%39,%40,%41,%42,%43,%44,%45,%46,%47,%48,%49,%50,%51,%52,%53,%54,%55,%56,%57,%58,%59,%60,%61,%62,%63,%64,%65,%66,%67,%68,%69,%70,%71,%72,%73,%74,%75,%76,%77,%78,%79,%80,%81,%82,%83,%84,%85,%86,%87,%88,%89,%90,%91,%92,%93,%94,%95}, %96, %97, p, 1, 1, 0, 1;\n}\n"
    : "+f"(d[0]),"+f"(d[1]),"+f"(d[2]),"+f"(d[3]),"+f"(d[4]),"+f"(d[5]),"+f"(d[6]),"+f"(d[7]),"+f"(d[8]),"+f"(d[9]),"+f"(d[10]),"+f"(d[11]),"+f"(d[12]),"+f"(d[13]),"+f"(d[14]),"+f"(d[15]),"+f"(d[16]),"+f"(d[17]),"+f"(d[18]),"+f"(d[19]),"+f"(d[20]),"+f"(d[21]),"+f"(d[22]),"+f"(d[23]),"+f"(d[24]),"+f"(d[25]),"+f"(d[26]),"+f"(d[27]),"+f"(d[28]),"+f"(d[29]),"+f"(d[30]),"+f"(d[31]),"+f"(d[32]),"+f"(d[33]),"+f"(d[34]),"+f"(d[35]),"+f"(d[36]),"+f"(d[37]),"+f"(d[38]),"+f"(d[39]),"+f"(d[40]),"+f"(d[41]),"+f"(d[42]),"+f"(d[43]),"+f"(d[44]),"+f"(d[45]),"+f"(d[46]),"+f"(d[47]),"+f"(d[48]),"+f"(d[49]),"+f"(d[50]),"+f"(d[51]),"+f"(d[52]),"+f"(d[53]),"+f"(d[54]),"+f"(d[55]),"+f"(d[56]),"+f"(d[57]),"+f"(d[58]),"+f"(d[59]),"+f"(d[60]),"+f"(d[61]),"+f"(d[62]),"+f"(d[63]),"+f"(d[64]),"+f"(d[65]),"+f"(d[66]),"+f"(d[67]),"+f"(d[68]),"+f"(d[69]),"+f"(d[70]),"+f"(d[71]),"+f"(d[72]),"+f"(d[73]),"+f"(d[74]),"+f"(d[75]),"+f"(d[76]),"+f"(d[77]),"+f"(d[78]),"+f"(d[79]),"+f"(d[80]),"+f"(d[81]),"+f"(d[82]),"+f"(d[83]),"+f"(d[84]),"+f"(d[85]),"+f"(d[86]),"+f"(d[87]),"+f"(d[88]),"+f"(d[89]),"+f"(d[90]),"+f"(d[91]),"+f"(d[92]),"+f"(d[93]),"+f"(d[94]),"+f"(d[95])
    : "l"(da), "l"(db), "r"(sd));
}
__device__ __forceinline__ void wg_rs64(float (&d)[32], uint32_t a0, uint32_t a1, uint32_t a2, uint32_t a3, uint64_t db, int sd) {
  asm volatile("{\n.reg .pred p;\nsetp.ne.b32 p, %37, 0;\n"
    "wgmma.mma_async.sync.aligned.m64n64k16.f32.bf16.bf16 {%0,%1,%2,%3,%4,%5,%6,%7,%8,%9,%10,%11,%12,%13,%14,%15,%16,%17,%18,%19,%20,%21,%22,%23,%24,%25,%26,%27,%28,%29,%30,%31}, {%32,%33,%34,%35}, %36, p, 1, 1, 0;\n}\n"
    : "+f"(d[0]),"+f"(d[1]),"+f"(d[2]),"+f"(d[3]),"+f"(d[4]),"+f"(d[5]),"+f"(d[6]),"+f"(d[7]),"+f"(d[8]),"+f"(d[9]),"+f"(d[10]),"+f"(d[11]),"+f"(d[12]),"+f"(d[13]),"+f"(d[14]),"+f"(d[15]),"+f"(d[16]),"+f"(d[17]),"+f"(d[18]),"+f"(d[19]),"+f"(d[20]),"+f"(d[21]),"+f"(d[22]),"+f"(d[23]),"+f"(d[24]),"+f"(d[25]),"+f"(d[26]),"+f"(d[27]),"+f"(d[28]),"+f"(d[29]),"+f"(d[30]),"+f"(d[31])
    : "r"(a0), "r"(a1), "r"(a2), "r"(a3), "l"(db), "r"(sd));
}
__device__ __forceinline__ void wg_rs192t(float (&d)[96], uint32_t a0, uint32_t a1, uint32_t a2, uint32_t a3, uint64_t db, int sd) {
  asm volatile("{\n.reg .pred p;\nsetp.ne.b32 p, %101, 0;\n"
    "wgmma.mma_async.sync.aligned.m64n192k16.f32.bf16.bf16 {%0,%1,%2,%3,%4,%5,%6,%7,%8,%9,%10,%11,%12,%13,%14,%15,%16,%17,%18,%19,%20,%21,%22,%23,%24,%25,%26,%27,%28,%29,%30,%31,%32,%33,%34,%35,%36,%37,%38,%39,%40,%41,%42,%43,%44,%45,%46,%47,%48,%49,%50,%51,%52,%53,%54,%55,%56,%57,%58,%59,%60,%61,%62,%63,%64,%65,%66,%67,%68,%69,%70,%71,%72,%73,%74,%75,%76,%77,%78,%79,%80,%81,%82,%83,%84,%85,%86,%87,%88,%89,%90,%91,%92,%93,%94,%95}, {%96,%97,%98,%99}, %100, p, 1, 1, 1;\n}\n"
    : "+f"(d[0]),"+f"(d[1]),"+f"(d[2]),"+f"(d[3]),"+f"(d[4]),"+f"(d[5]),"+f"(d[6]),"+f"(d[7]),"+f"(d[8]),"+f"(d[9]),"+f"(d[10]),"+f"(d[11]),"+f"(d[12]),"+f"(d[13]),"+f"(d[14]),"+f"(d[15]),"+f"(d[16]),"+f"(d[17]),"+f"(d[18]),"+f"(d[19]),"+f"(d[20]),"+f"(d[21]),"+f"(d[22]),"+f"(d[23]),"+f"(d[24]),"+f"(d[25]),"+f"(d[26]),"+f"(d[27]),"+f"(d[28]),"+f"(d[29]),"+f"(d[30]),"+f"(d[31]),"+f"(d[32]),"+f"(d[33]),"+f"(d[34]),"+f"(d[35]),"+f"(d[36]),"+f"(d[37]),"+f"(d[38]),"+f"(d[39]),"+f"(d[40]),"+f"(d[41]),"+f"(d[42]),"+f"(d[43]),"+f"(d[44]),"+f"(d[45]),"+f"(d[46]),"+f"(d[47]),"+f"(d[48]),"+f"(d[49]),"+f"(d[50]),"+f"(d[51]),"+f"(d[52]),"+f"(d[53]),"+f"(d[54]),"+f"(d[55]),"+f"(d[56]),"+f"(d[57]),"+f"(d[58]),"+f"(d[59]),"+f"(d[60]),"+f"(d[61]),"+f"(d[62]),"+f"(d[63]),"+f"(d[64]),"+f"(d[65]),"+f"(d[66]),"+f"(d[67]),"+f"(d[68]),"+f"(d[69]),"+f"(d[70]),"+f"(d[71]),"+f"(d[72]),"+f"(d[73]),"+f"(d[74]),"+f"(d[75]),"+f"(d[76]),"+f"(d[77]),"+f"(d[78]),"+f"(d[79]),"+f"(d[80]),"+f"(d[81]),"+f"(d[82]),"+f"(d[83]),"+f"(d[84]),"+f"(d[85]),"+f"(d[86]),"+f"(d[87]),"+f"(d[88]),"+f"(d[89]),"+f"(d[90]),"+f"(d[91]),"+f"(d[92]),"+f"(d[93]),"+f"(d[94]),"+f"(d[95])
    : "r"(a0), "r"(a1), "r"(a2), "r"(a3), "l"(db), "r"(sd));
}
__device__ __forceinline__ void wg_ss160t(float (&d)[80], uint64_t da, uint64_t db, int sd) {
  asm volatile("{\n.reg .pred p;\nsetp.ne.b32 p, %82, 0;\n"
    "wgmma.mma_async.sync.aligned.m64n160k16.f32.bf16.bf16 {%0,%1,%2,%3,%4,%5,%6,%7,%8,%9,%10,%11,%12,%13,%14,%15,%16,%17,%18,%19,%20,%21,%22,%23,%24,%25,%26,%27,%28,%29,%30,%31,%32,%33,%34,%35,%36,%37,%38,%39,%40,%41,%42,%43,%44,%45,%46,%47,%48,%49,%50,%51,%52,%53,%54,%55,%56,%57,%58,%59,%60,%61,%62,%63,%64,%65,%66,%67,%68,%69,%70,%71,%72,%73,%74,%75,%76,%77,%78,%79}, %80, %81, p, 1, 1, 0, 1;\n}\n"
    : "+f"(d[0]),"+f"(d[1]),"+f"(d[2]),"+f"(d[3]),"+f"(d[4]),"+f"(d[5]),"+f"(d[6]),"+f"(d[7]),"+f"(d[8]),"+f"(d[9]),"+f"(d[10]),"+f"(d[11]),"+f"(d[12]),"+f"(d[13]),"+f"(d[14]),"+f"(d[15]),"+f"(d[16]),"+f"(d[17]),"+f"(d[18]),"+f"(d[19]),"+f"(d[20]),"+f"(d[21]),"+f"(d[22]),"+f"(d[23]),"+f"(d[24]),"+f"(d[25]),"+f"(d[26]),"+f"(d[27]),"+f"(d[28]),"+f"(d[29]),"+f"(d[30]),"+f"(d[31]),"+f"(d[32]),"+f"(d[33]),"+f"(d[34]),"+f"(d[35]),"+f"(d[36]),"+f"(d[37]),"+f"(d[38]),"+f"(d[39]),"+f"(d[40]),"+f"(d[41]),"+f"(d[42]),"+f"(d[43]),"+f"(d[44]),"+f"(d[45]),"+f"(d[46]),"+f"(d[47]),"+f"(d[48]),"+f"(d[49]),"+f"(d[50]),"+f"(d[51]),"+f"(d[52]),"+f"(d[53]),"+f"(d[54]),"+f"(d[55]),"+f"(d[56]),"+f"(d[57]),"+f"(d[58]),"+f"(d[59]),"+f"(d[60]),"+f"(d[61]),"+f"(d[62]),"+f"(d[63]),"+f"(d[64]),"+f"(d[65]),"+f"(d[66]),"+f"(d[67]),"+f"(d[68]),"+f"(d[69]),"+f"(d[70]),"+f"(d[71]),"+f"(d[72]),"+f"(d[73]),"+f"(d[74]),"+f"(d[75]),"+f"(d[76]),"+f"(d[77]),"+f"(d[78]),"+f"(d[79])
    : "l"(da), "l"(db), "r"(sd));
}
__device__ __forceinline__ void wg_ss80t(float (&d)[40], uint64_t da, uint64_t db, int sd) {
  asm volatile("{\n.reg .pred p;\nsetp.ne.b32 p, %42, 0;\n"
    "wgmma.mma_async.sync.aligned.m64n80k16.f32.bf16.bf16 {%0,%1,%2,%3,%4,%5,%6,%7,%8,%9,%10,%11,%12,%13,%14,%15,%16,%17,%18,%19,%20,%21,%22,%23,%24,%25,%26,%27,%28,%29,%30,%31,%32,%33,%34,%35,%36,%37,%38,%39}, %40, %41, p, 1, 1, 0, 1;\n}\n"
    : "+f"(d[0]),"+f"(d[1]),"+f"(d[2]),"+f"(d[3]),"+f"(d[4]),"+f"(d[5]),"+f"(d[6]),"+f"(d[7]),"+f"(d[8]),"+f"(d[9]),"+f"(d[10]),"+f"(d[11]),"+f"(d[12]),"+f"(d[13]),"+f"(d[14]),"+f"(d[15]),"+f"(d[16]),"+f"(d[17]),"+f"(d[18]),"+f"(d[19]),"+f"(d[20]),"+f"(d[21]),"+f"(d[22]),"+f"(d[23]),"+f"(d[24]),"+f"(d[25]),"+f"(d[26]),"+f"(d[27]),"+f"(d[28]),"+f"(d[29]),"+f"(d[30]),"+f"(d[31]),"+f"(d[32]),"+f"(d[33]),"+f"(d[34]),"+f"(d[35]),"+f"(d[36]),"+f"(d[37]),"+f"(d[38]),"+f"(d[39])
    : "l"(da), "l"(db), "r"(sd));
}

struct MapPair { CUtensorMap m[2]; };
struct Params {
  const __nv_bfloat16 *x, *wr, *wg, *wu, *wd, *k, *v;
  Scratch* s;
};

__device__ __forceinline__ void side_cta(const Params& p, int sc, unsigned epoch, float* sm) {
  const int tid = threadIdx.x, lane = tid & 31, warp = tid >> 5;
  int budget = WAIT_BUDGET;
  float* s_x = sm;
  float* s_red = sm + 1280;
  float* s_h = s_red + 6144;
  uint4* s_c = (uint4*)(s_h + 768);
  uint2* s_st = (uint2*)(s_c + 16);
  constexpr int DEPTH = 7, STEP = 4 * 6144;
  const uint32_t ring = smem_u32(s_st + 512) + tid * 16;
  const int cg = tid % 96, ks = tid / 96, cd = tid % 80, kd = tid / 80;
  const __nv_bfloat16* wp = (cg < 48 ? p.wg : p.wu) + (size_t)(ks * 160) * FF + sc * 384 + (cg % 48) * 8;
  int kf = 0, pitch = FF;
  uint32_t slot = ring;
  auto refill = [&]() {
    if (kf == 40) { wp = p.wd + (size_t)(sc * 384 + kd * 96) * DM + cd * 8; pitch = DM; }
    if (kf < (tid < 320 ? 64 : 40)) {
#pragma unroll
      for (int j = 0; j < 4; j++) asm volatile("cp.async.cg.shared.global.L2::cache_hint [%0], [%1], 16, %2;" ::"r"(slot + j * 6144), "l"(wp + j * pitch), "l"(POL_FIRST) : "memory");
    }
    asm volatile("cp.async.commit_group;" ::: "memory");
    wp += 4 * pitch; kf++;
    slot += STEP; if (slot == ring + DEPTH * STEP) slot = ring;
  };
  auto gemv = [&](int n, const float* x0, const float* x1, float* out) {
    float a[2][8] = {};
#pragma unroll 1
    for (int k = 0; k < n; k += 4) {
      refill();
      asm volatile("cp.async.wait_group %0;" ::"n"(DEPTH - 1) : "memory");
      const float4 f0 = *(const float4*)(x0 + k), f1 = *(const float4*)(x1 + k);
      const float y0[4] = {f0.x, f0.y, f0.z, f0.w}, y1[4] = {f1.x, f1.y, f1.z, f1.w};
#pragma unroll
      for (int j = 0; j < 4; j++) {
        const uint4 v = lds128(slot + j * 6144);
        const uint32_t u[4] = {v.x, v.y, v.z, v.w};
#pragma unroll
        for (int i = 0; i < 4; i++) {
          a[0][2 * i] += y0[j] * bf_lo(u[i]); a[0][2 * i + 1] += y0[j] * bf_hi(u[i]);
          a[1][2 * i] += y1[j] * bf_lo(u[i]); a[1][2 * i + 1] += y1[j] * bf_hi(u[i]);
        }
      }
    }
#pragma unroll
    for (int i = 0; i < 16; i++) out[(i >> 3) * 768 + (i & 7)] = a[i >> 3][i & 7];
  };
  auto load_row = [&](const __nv_bfloat16* r, uint32_t (&v)[10]) {
    const uint4 a = __ldg((const uint4*)r + lane), b = __ldg((const uint4*)r + 32 + lane);
    const uint2 c = __ldg((const uint2*)r + 128 + lane);
    v[0] = a.x; v[1] = a.y; v[2] = a.z; v[3] = a.w; v[4] = b.x; v[5] = b.y; v[6] = b.z; v[7] = b.w; v[8] = c.x; v[9] = c.y;
  };
  uint32_t wr[10], xb[3][10];
  load_row(p.wr, wr);
#pragma unroll 1
  for (int i = tid; i < 512; i += 384) {
    uint4 v;
    do v = ld_pkt(p.s->stat + sc * 512 + i); while (v.w != epoch + 1 && --budget >= 0);
    s_st[i] = make_uint2(v.x, v.y);
  }
  __syncthreads();
#pragma unroll
  for (int b = 0; b < 3; b++) load_row(p.x + (size_t)(sc * 512 + warp + 12 * b) * DM, xb[b]);
#pragma unroll 1
  for (int k = 0; k < DEPTH - 1; k++) refill();
  float v0 = -INFINITY, v1 = -INFINITY; int i0 = 0xfff, i1 = 0xfff;
  auto better = [](float a, int ia, float b, int ib) { return a > b || (a == b && ia < ib); };
  auto push = [&](float v, int i) {
    if (better(v, i, v0, i0)) { v1 = v0; i1 = i0; v0 = v; i0 = i; }
    else if (better(v, i, v1, i1)) { v1 = v; i1 = i; }
  };
  auto push2 = [&](uint4 c) { push(__uint_as_float(c.x), c.y & 0xfff); push(__uint_as_float(c.z), c.w & 0xfff); };
#pragma unroll 1
  for (int l3 = warp; l3 < 512; l3 += 36) {
#pragma unroll
    for (int b = 0; b < 3; b++) {
      const int lr = l3 + 12 * b;
      if (lr >= 512) break;
      const uint2 st = s_st[lr];
      uint32_t v[10];
#pragma unroll
      for (int i = 0; i < 10; i++) v[i] = hsub2(xb[b][i], st.x);
      if (lr + 36 < 512) load_row(p.x + (size_t)(sc * 512 + lr + 36) * DM, xb[b]);
      float r0 = 0.f, r1 = 0.f;
#pragma unroll
      for (int i = 0; i < 10; i++) {
        const uint32_t xn = pack_bf16(bf_lo(v[i]) * __uint_as_float(st.y), bf_hi(v[i]) * __uint_as_float(st.y));
        r0 = fmaf(bf_lo(xn), bf_lo(wr[i]), r0); r1 = fmaf(bf_hi(xn), bf_hi(wr[i]), r1);
      }
      r0 += r1;
#pragma unroll
      for (int o = 16; o > 0; o >>= 1) r0 += __shfl_xor_sync(~0u, r0, o);
      push(rbf(r0), sc * 512 + lr);
    }
  }
  if (lane == 0) s_c[warp] = make_uint4(__float_as_uint(v0), i0, __float_as_uint(v1), i1);
  __syncthreads();
#pragma unroll 1
  for (int w = 1; w < 12; w++) push2(s_c[(warp + w) % 12]);
  const uint32_t tag = (epoch + 1) << 12;
  if (tid == 0) st_pkt(p.s->cand + sc, __float_as_uint(v0), i0 | tag, __float_as_uint(v1), i1);
  {
    uint4 c;
    do c = ld_pkt(p.s->cand + (lane & 3)); while (((c.y ^ tag) >> 12) && --budget >= 0);
#pragma unroll 1
    for (int w = 1; w < 4; w++) { const int o = (sc + w) & 3; push2(make_uint4(__shfl_sync(~0u, c.x, o), __shfl_sync(~0u, c.y, o), __shfl_sync(~0u, c.z, o), __shfl_sync(~0u, c.w, o))); }
  }
  if (i0 >= SQ) i0 = 0;
  if (i1 >= SQ) i1 = (i0 == 0) ? 1 : 0;
  if (tid < 320) {
    const int row = tid < 160 ? i0 : i1;
    const uint2 u = __ldg((const uint2*)(p.x + (size_t)row * DM) + tid % 160);
    uint4 st;
    do st = ld_pkt(p.s->stat + row); while (st.w != epoch + 1 && --budget >= 0);
    const uint32_t d0 = hsub2(u.x, st.x), d1 = hsub2(u.y, st.x);
    const float inv = __uint_as_float(st.y);
    ((float4*)s_x)[tid] = make_float4(rbf(bf_lo(d0) * inv), rbf(bf_hi(d0) * inv), rbf(bf_lo(d1) * inv), rbf(bf_hi(d1) * inv));
  }
  __syncthreads();
  gemv(160, s_x + ks * 160, s_x + DM + ks * 160, s_red + ks * 1536 + cg * 8);
  __syncthreads();
#pragma unroll
  for (int t = 0; t < 2; t++) {
    float g = 0.f, u = 0.f;
#pragma unroll
    for (int k = 0; k < 4; k++) { g += s_red[(k * 2 + t) * 768 + tid]; u += s_red[(k * 2 + t) * 768 + 384 + tid]; }
    s_h[t * 384 + tid] = rbf(rbf(silu_f(rbf(g))) * rbf(u));
  }
  __syncthreads();
  if (tid < 320) gemv(96, s_h + kd * 96, s_h + 384 + kd * 96, s_red + kd * 1536 + cd * 8);
  __syncthreads();
  const int o4 = tid + (tid < 160 ? 0 : 32);
  if (tid < 320) {
    const float4 *r = (const float4*)s_red + o4, a = r[0], b = r[384], c = r[768], d = r[1152];
    ((float4*)p.s->ffn)[sc * 320 + tid] = make_float4(a.x + b.x + c.x + d.x, a.y + b.y + c.y + d.y, a.z + b.z + c.z + d.z, a.w + b.w + c.w + d.w);
  }
  __syncthreads();
  if (tid == 0) { __threadfence(); s_c[0].x = (atomicAdd(&p.s->flag[FL_SIDE], 1u) & 3u) == 3u; __threadfence(); }
  __syncthreads();
  if (s_c[0].x) {
    if (tid < 320) {
      const float4 *r = (const float4*)p.s->ffn + tid, a = __ldcg(r), b = __ldcg(r + 320), c = __ldcg(r + 640), d = __ldcg(r + 960), x = ((float4*)s_x)[tid];
      const float rs = rbf(sigmoid_f(tid < 160 ? v0 : v1));
      auto gate = [&](float xn, float y) { return silu_f(rbf(xn + rbf(rbf(y) * rs))); };
      if (tid == 0) { p.s->sel[0] = i0; p.s->sel[1] = i1; }
      ((uint2*)p.s->gsel)[tid] =
          make_uint2(pack_bf16(gate(x.x, a.x + b.x + c.x + d.x), gate(x.y, a.y + b.y + c.y + d.y)), pack_bf16(gate(x.z, a.z + b.z + c.z + d.z), gate(x.w, a.w + b.w + c.w + d.w)));
    }
    __syncthreads();
    if (tid == 0) red_release(&p.s->flag[FL_FFN]);
  }
}

constexpr float SM_C = 0.07216878364870322f * 1.4426950408889634f;

__device__ __forceinline__ void ln_row(const Params& p, uint32_t (&uu)[20], int row, int l16, uint32_t tag) {
  const float x0 = bf_lo(__shfl_sync(~0u, uu[0], 0, 16));
  float s0 = 0.f, s1 = 0.f, q0 = 0.f, q1 = 0.f;
#pragma unroll
  for (int i = 0; i < 20; i++) {
    const float a = bf_lo(uu[i]) - x0, b = bf_hi(uu[i]) - x0;
    s0 += a; s1 += b; q0 = fmaf(a, a, q0); q1 = fmaf(b, b, q1);
  }
  s0 += s1; q0 += q1;
#pragma unroll
  for (int o = 8; o > 0; o >>= 1) { s0 += __shfl_xor_sync(~0u, s0, o); q0 += __shfl_xor_sync(~0u, q0, o); }
  s0 *= 1.f / DM;
  const float mean = x0 + s0, var = rbf(fmaxf(fmaf(q0, 1.f / DM, -s0 * s0), 0.f));
  float sd; asm("sqrt.approx.ftz.f32 %0, %1;" : "=f"(sd) : "f"(rbf(var + 1e-5f)));
  const float inv = rcp(rbf(sd)), invc = inv * SM_C;
  const __nv_bfloat162 mb = __float2bfloat162_rn(mean);
  const uint32_t mean2 = *reinterpret_cast<const uint32_t*>(&mb);
  if (l16 == 0) st_pkt(&p.s->stat[row], mean2, __float_as_uint(inv), 0, tag);
#pragma unroll
  for (int i = 0; i < 20; i++) { const uint32_t d = hsub2(uu[i], mean2); uu[i] = pack_bf16(bf_lo(d) * invc, bf_hi(d) * invc); }
#pragma unroll
  for (int i = 0; i < 5; i++) *((uint4*)(p.s->xn + (size_t)row * DM) + i * 16 + l16) = make_uint4(uu[4 * i], uu[4 * i + 1], uu[4 * i + 2], uu[4 * i + 3]);
}

constexpr float SM_HI = 0x1p64f, SM_LO = 0x1p-64f;
__device__ __forceinline__ void exp_block(float (&s)[32], float& l0, float& l1, int from = 0, int to = 32) {
#pragma unroll
  for (int i = from; i < to; i++) { s[i] = ex2(s[i]); if (i & 2) l1 += s[i]; else l0 += s[i]; }
}
__device__ __forceinline__ float quad_sum(float v) { v += __shfl_xor_sync(~0u, v, 1); return v + __shfl_xor_sync(~0u, v, 2); }
__device__ __forceinline__ float quad_max(float v) { v = fmaxf(v, __shfl_xor_sync(~0u, v, 1)); return fmaxf(v, __shfl_xor_sync(~0u, v, 2)); }
__device__ __forceinline__ void safe_head(const uint32_t* kp, const uint32_t* vp, const uint32_t (&fq)[48], float (&o)[96], float& l0, float& l1) {
  float m0 = -INFINITY, m1 = -INFINITY;
  l0 = l1 = 0.f;
#pragma unroll
  for (int c = 0; c < 24; c++)
    asm volatile("mma.sync.aligned.m16n8k8.row.col.f32.bf16.bf16.f32 {%0,%1,%2,%3}, {%4,%4}, {%5}, {%6,%6,%6,%6};"
                 : "=f"(o[4 * c]), "=f"(o[4 * c + 1]), "=f"(o[4 * c + 2]), "=f"(o[4 * c + 3])
                 : "r"(0), "r"(c ? __float_as_uint(o[4 * c - 4]) : 0), "f"(0.f));
#pragma unroll 1
  for (int n = 0; n < 128; n++) {
    const uint32_t *kr = kp + (n & 63) * (8 * DH / 2), *vr = vp + (n & 63) * (8 * DH / 2);
    float d[4] = {};
#pragma unroll
    for (int t = 0; t < 12; t++)
      asm volatile("mma.sync.aligned.m16n8k16.row.col.f32.bf16.bf16.f32 {%0,%1,%2,%3}, {%4,%5,%6,%7}, {%8,%9}, {%0,%1,%2,%3};"
                   : "+f"(d[0]), "+f"(d[1]), "+f"(d[2]), "+f"(d[3])
                   : "r"(fq[4 * t]), "r"(fq[4 * t + 1]), "r"(fq[4 * t + 2]), "r"(fq[4 * t + 3]), "r"(__ldg(kr + 8 * t)), "r"(__ldg(kr + 8 * t + 4)));
    if (n < 64) { m0 = quad_max(fmaxf(m0, fmaxf(d[0], d[1]))); m1 = quad_max(fmaxf(m1, fmaxf(d[2], d[3]))); continue; }
    d[0] = ex2(d[0] - m0); d[1] = ex2(d[1] - m0); d[2] = ex2(d[2] - m1); d[3] = ex2(d[3] - m1);
    l0 += quad_sum(d[0] + d[1]); l1 += quad_sum(d[2] + d[3]);
    const uint32_t p0 = pack_bf16(d[0], d[1]), p1 = pack_bf16(d[2], d[3]);
#pragma unroll
    for (int c = 0; c < 24; c++)
      asm volatile("{\n.reg .b32 t;\nmovmatrix.sync.aligned.m8n8.trans.b16 t, %6;\n"
                   "mma.sync.aligned.m16n8k8.row.col.f32.bf16.bf16.f32 {%0,%1,%2,%3}, {%4,%5}, {t}, {%0,%1,%2,%3};\n}\n"
                   : "+f"(o[4 * c]), "+f"(o[4 * c + 1]), "+f"(o[4 * c + 2]), "+f"(o[4 * c + 3]) : "r"(p0), "r"(p1), "r"(__ldg(vr + 4 * c)));
  }
}

#define CVG 48
#define NE 8
#define PS1 8
#define LQ 6
__device__ __forceinline__ constexpr int end_stage(int n) { return n < 4 ? n : n < LQ ? n - 4 : n == LQ ? 4 : n % 5; }
#define Q2N 1
#define SWN 12
#define SCH 0
__device__ __forceinline__ constexpr int sent(int n) {
  constexpr int t[4][15] = {{0, 2, 4, 5, 5, 6, 7, 8,  9, 10, 11, 12, 13, 14, 15},
                            {0, 2, 4, 5, 5, 6, 7, 8,  9, 10, 12, 13, 14, 15, 15},
                            {0, 2, 4, 5, 5, 7, 8, 9, 10, 10, 12, 14, 15, 15, 15},
                            {0, 2, 4, 5, 5, 7, 8, 9, 10, 10, 13, 15, 15, 15, 15}};
  return n < LQ + 2 ? 0 : LQ == 6 && n == 8 ? 3 : t[SCH][n - 6];
}
template <int N> struct IntC { static constexpr int value = N; };
template <int N, int I = 0, class F> __device__ __forceinline__ void static_for(F&& f) { if constexpr (I < N) { f(IntC<I>{}); static_for<N, I + 1>(f); } }

__global__ void __launch_bounds__(384, 1)
fused_kernel(const Params p, const __grid_constant__ CUtensorMap tm_x, const __grid_constant__ CUtensorMap tm_xn,
             const __grid_constant__ CUtensorMap tm_wq, const __grid_constant__ CUtensorMap tm_k,
             const __grid_constant__ CUtensorMap tm_v, const __grid_constant__ CUtensorMap tm_wo,
             const __grid_constant__ MapPair tm_w2,
             const __grid_constant__ CUtensorMap tm_xg, const __grid_constant__ CUtensorMap tm_xe,
             const __grid_constant__ CUtensorMap tm_out) {
  extern __shared__ __align__(1024) uint8_t smem_raw[];
  const uint32_t sb = smem_u32(smem_raw);
  const CUtensorMap* const tm_w = tm_w2.m;
  const uint32_t bar_a = sb + OFF_M, bar_b = bar_a + 80, bar_o = bar_b + 96;
  const uint32_t bar_x = bar_o + 8, bar_z = bar_o + 16, bar_s = bar_o + 24, bar_d = bar_o + 32, bar_w = bar_o + 40, bar_e = bar_o + 48,
                 bar_u = bar_o + 96;
  const uint32_t s_stat = bar_a + 512;
  const uint32_t s_sel = s_stat + 1024;
  const int wi = __shfl_sync(~0u, threadIdx.x >> 5, 0), wg = wi >> 2;
  const int lane = threadIdx.x & 31;
  const int cl = blockIdx.x >> 1;
  const int rank = blockIdx.x & 1;

  if (cl >= 64) {
    const unsigned epoch = (unsigned)(__ldcg(&p.s->done) >> 7);
    side_cta(p, blockIdx.x - 128, epoch, (float*)smem_raw);
    return;
  }
  const int qt = (cl >> 3) * 2 + rank, hg = cl & 7;
  const int kq = hg >> 1, nh = hg & 1;

  if (elect()) {
    if (wi < 2) asm volatile("prefetch.tensormap [%0];" ::"l"(wi ? &tm_wq : &tm_x) : "memory");
    const uint32_t c = (uint32_t)((wi < 5 ? 0x7777700000ull : wi < 10 ? 0x752107ffffff0ull : 0ull) >> (12 * (wi % 5)));
    for (int i = 0; i < 3; i++) mbar_init(bar_a + 24 * wi + 8 * i, ((c >> (4 * i)) & 15) + 1);
  }
  asm volatile("fence.mbarrier_init.release.cluster;" ::: "memory");
  cluster_arrive();
  uint32_t xw[20];
  unsigned long long done = 0;
  const int lnrow = qt * 128 + hg * 16 + ((int)(threadIdx.x >> 5) - 4) * 2 + (lane >> 4);
  uint32_t cons; asm volatile("{\n.reg .pred q;\nsetp.ne.u32 q, %1, 0;\nselp.u32 %0, 1, 0, q;\n}" : "=r"(cons) : "r"(wg));
  if (cons) {
#pragma unroll
    for (int i = 0; i < 5; i++) {
      const uint4 v = ldg_nc((const uint4*)(p.x + (size_t)lnrow * DM) + i * 16 + (lane & 15));
      xw[4 * i] = v.x; xw[4 * i + 1] = v.y; xw[4 * i + 2] = v.z; xw[4 * i + 3] = v.w;
    }
    asm volatile("ld.relaxed.gpu.global.u64 %0, [%1];" : "=l"(done) : "l"(&p.s->done));
  }
  if (wg > 0) {
    const int w = wg - 1;
    const int cw = wi - 4;
    asm volatile("setmaxnreg.inc.sync.aligned.u32 232;");
    {
      cluster_wait();
      ln_row(p, xw, lnrow, lane & 15, (unsigned)(done >> 7) + 1);
      __syncwarp();
      if (lane == 0) mbar_arrive(bar_o);
    }
    uint32_t rel_addr;
    asm volatile("mapa.shared::cluster.u32 %0, %1, %2;" : "=r"(rel_addr) : "r"(bar_b + 48), "r"(lane & 1));
    auto rel_a = [&](uint32_t o8) { if (lane == 0) mbar_arrive(bar_a + 40 + o8); };
    auto rel_b = [&](uint32_t o8) { if (lane < 2) mbar_arrive_cluster(rel_addr + o8); };
    uint32_t b8 = 0, phb = 0;
    auto next_pair = [&]() { b8 += 16; if (b8 == 48) { b8 = 0; phb ^= 1; } };
    const int g = lane >> 2, q = lane & 3;
    constexpr uint64_t HI_A = desc_hi(16, 1024, 1);
    constexpr uint64_t HI_W = desc_hi(1024, 3072, 1);
    constexpr uint64_t HI_O = desc_hi(2048, 512, 2);
    if (w == 1) asm volatile("bar.arrive 1, 256;" ::: "memory");

    uint32_t zero; asm volatile("mov.u32 %0, %%tid.y;" : "=r"(zero));
    float acc[96];
    uint32_t fr[48];
    uint4* optr = p.s->o + (size_t)(qt * 192 + hg * 24) * 512 + (cw * 16 + g) * 4 + (q ^ ((g >> 1) & 3));
    uint32_t rl[4];
    auto store_o = [&](int pp, bool on) {
#pragma unroll
      for (int i = (12 * pp + 8) / 9; i < (12 * (pp + 1) + 8) / 9; i++) {
#pragma unroll
        for (int k = 4 * i; k < 4 * i + 4; k++)
          asm volatile("{\n.reg .b32 t;\nmul.rn.bf16x2 t, %0, %2;\nfma.rn.bf16x2 %0, %0, %1, t;\n}\n" : "+r"(fr[k]) : "r"(rl[i & 1]), "r"(rl[2 + (i & 1)]));
        fr[4 * i] &= ~1u;
        if (on) optr[(i >> 1) * 512 + (i & 1) * 32] = make_uint4(fr[4 * i], fr[4 * i + 1], fr[4 * i + 2], fr[4 * i + 3]);
      }
      if (pp == 8 && on) { __syncwarp(); if (lane == 0) mbar_arrive(bar_o); optr += 6 * 512; }
    };
    auto fresh = [&]() { uint32_t v = sb; asm volatile("" : "+r"(v)); return v; };
    reg_fence(fr); reg_fence(rl);

#pragma unroll 1
    for (int u = 0; u < 4; u++) {
      const uint32_t sq = fresh();
      const uint64_t dA = mkdesc(sq + w * 8192, HI_A), dB0 = mkdesc(sq + OFF_B, HI_W);
      uint32_t pb8 = 0;
#pragma unroll
      for (int s = 0; s < 10; s++) {
        const uint32_t o8 = b8 + 8 * (s & 1);
        const uint64_t dW = dB0 + o8 * (TB >> 7);
        mbar_wait(bar_a + 8 * (s % 5), s / 5);
        mbar_wait(bar_b + o8, phb);
        if (s == 9) asm volatile("bar.sync %0, 256;" ::"r"(1 + w) : "memory");
        WG_FENCE();
#pragma unroll
        for (int kk = 0; kk < 4; kk++) wg_ss192t(acc, dA + ((s % 5) * (TA >> 4) + kk * 2), dW + kk * 384, kk != 0 || s != 0);
        WG_COMMIT();
        if (s == 9) asm volatile("bar.arrive %0, 256;" ::"r"(2 - w) : "memory");
        if (s < 9) store_o(s, u > 0);
        if (s > 0) { WG_WAIT(1); rel_a(8 * ((s - 1) % 5)); rel_b(pb8); }
        pb8 = o8;
        if (s & 1) next_pair();
      }
      WG_WAIT(0);
      reg_fence(acc);
      rel_b(pb8);
      if (u == 0) {
        mbar_wait(bar_s, 0);
        const uint2 s0 = lds64(s_stat + (cw * 16 + g) * 8), s1 = lds64(s_stat + 64 + (cw * 16 + g) * 8);
        const uint32_t msk = q == 0 ? 0xffffffffu : q == 1 ? 0xffffu : 0u;
        const float c0 = SM_C * __uint_as_float(s0.y), c1 = SM_C * __uint_as_float(s1.y);
        uint32_t am[4] = {(s0.x ^ 0x80008000u) & msk, (s1.x ^ 0x80008000u) & msk, 0, 0};
        reg_fence(am);
        WG_FENCE();
        wg_rs192t(acc, am[0], am[1], am[2], am[3], mkdesc(sb, desc_hi(1024, 0, 1)), 1);
        WG_COMMIT();
        WG_WAIT(0);
        reg_fence(acc);
#pragma unroll
        for (int i = 0; i < 24; i++) { acc[4 * i] *= c0; acc[4 * i + 1] *= c0; acc[4 * i + 2] *= c1; acc[4 * i + 3] *= c1; }
      }
      rel_a(32);
      auto pack_q = [&](int from, int to) {
#pragma unroll
        for (int i = from; i < to; i++) { fr[i] = pack_bf16(acc[2 * i], acc[2 * i + 1]); asm volatile("" : "+r"(fr[i])::"memory"); }
      };
      pack_q(0, CVG);
      float sc[32], l0 = 0.f, l1 = 0.f;
      uint32_t pf[16], k8;
      auto pack_p = [&](const float (&s_)[32], int from = 0, int to = 16) {
#pragma unroll
        for (int i = from; i < to; i++) pf[i] = pack_bf16(s_[2 * i], s_[2 * i + 1]);
      };
      auto scores = [&](int j, int pass = 11) {
        k8 = b8 + 8;
        mbar_wait(bar_b + k8, phb);
        next_pair();
        mbar_wait(bar_b + b8, phb);
        const uint64_t dk = mkdesc(sb + OFF_B, HI_W) + k8 * (TB >> 7);
        asm volatile("bar.sync %0, 256;" ::"r"(1 + w) : "memory");
        WG_FENCE();
#pragma unroll
        for (int t = 0; t < 12; t++) {
          wg_rs64(sc, fr[4 * t], fr[4 * t + 1], fr[4 * t + 2], fr[4 * t + 3], dk + (t >> 2) * 64 + (t & 3) * 2, t != 0);
          if (t == 11) WG_COMMIT();
          if (t == pass) asm volatile("bar.arrive %0, 256;" ::"r"(2 - w) : "memory");
        }
      };
      auto pv = [&](int add) {
        const uint64_t dv = mkdesc(sb + OFF_B, HI_W) + b8 * (TB >> 7);
#pragma unroll
        for (int kk = 0; kk < 4; kk++) wg_rs192t(acc, pf[4 * kk], pf[4 * kk + 1], pf[4 * kk + 2], pf[4 * kk + 3], dv + kk * 384, kk != 0 || add);
        WG_COMMIT();
      };
      auto finish = [&]() {
        WG_WAIT(1);
        reg_fence(sc);
        exp_block(sc, l0, l1);
        rel_b(k8 + (__float_as_uint(l0) & __float_as_uint(l1) & zero));
        WG_WAIT(0);
        reg_fence(acc); reg_fence(pf);
        rel_b(b8);
        pack_p(sc);
      };
      {
        mbar_wait(bar_b + b8, phb);
        const uint64_t dk = mkdesc(sb + OFF_B, HI_W) + b8 * (TB >> 7);
        asm volatile("bar.sync %0, 256;" ::"r"(1 + w) : "memory");
#pragma unroll
        for (int t = 0; t < 12; t++) {
          if (t && (4 * t) % CVG == 0) pack_q(4 * t, 4 * t + CVG);
          if ((4 * t) % CVG == 0) WG_FENCE();
          wg_rs64(sc, fr[4 * t], fr[4 * t + 1], fr[4 * t + 2], fr[4 * t + 3], dk + (t >> 2) * 64 + (t & 3) * 2, t != 0);
          if (t == 7) asm volatile("bar.arrive %0, 256;" ::"r"(2 - w) : "memory");
        }
        WG_COMMIT();
        WG_WAIT(0);
        reg_fence(sc);
        float s0[32];
#pragma unroll
        for (int i = 0; i < 32; i++) s0[i] = i < NE ? sc[i] : __uint_as_float(__float_as_uint(sc[i]) ^ zero);
        exp_block(s0, l0, l1, 0, NE);
        pack_p(s0, 0, NE / 2);
#pragma unroll
        for (int i = NE; i < 32; i++) asm volatile("" : "+f"(s0[i])::"memory");
#pragma unroll
        for (int i = 0; i < NE / 2; i++) asm volatile("" : "+r"(pf[i])::"memory");
        rel_b(b8);
        scores(1, PS1);
        const uint32_t z = lds32(s_stat) & zero;
#pragma unroll
        for (int i = NE; i < 32; i++) {
          asm("{\n.reg .pred p;\nsetp.eq.u32 p, %1, 0;\n@p ex2.approx.ftz.f32 %0, %0;\n}\n" : "+f"(s0[i]) : "r"(z));
          if (i & 2) l1 += s0[i]; else l0 += s0[i];
        }
        pack_p(s0, NE / 2, 16);
        reg_fence(pf);
        WG_FENCE();
        pv(0);
        finish();
      }
#pragma unroll 1
      for (int j = NE < 32 ? 2 : 1; j < 8; j++) { scores(j); pv(j > 1); finish(); }
      const uint32_t v8 = b8 + 8;
      mbar_wait(bar_b + v8, phb);
      next_pair();
      {
        const uint64_t dv = mkdesc(sb + OFF_B, HI_W) + v8 * (TB >> 7);
        asm volatile("bar.sync %0, 256;" ::"r"(1 + w) : "memory");
        WG_FENCE();
#pragma unroll
        for (int kk = 0; kk < 4; kk++) {
          wg_rs192t(acc, pf[4 * kk], pf[4 * kk + 1], pf[4 * kk + 2], pf[4 * kk + 3], dv + kk * 384, 1);
          if (kk == 1 && (u < 3 || w == 0)) asm volatile("bar.arrive %0, 256;" ::"r"(2 - w) : "memory");
        }
        WG_COMMIT();
      }
      l0 = quad_sum(l0); l1 = quad_sum(l1);
      const bool unsafe = __any_sync(~0u, !(l0 >= SM_LO && l1 >= SM_LO && l0 + l1 <= SM_HI));
      auto set_rl = [&]() {
        l0 = rcp(l0); l1 = rcp(l1);
        rl[0] = pack_bf16(l0, l0); rl[1] = pack_bf16(l1, l1);
        l0 -= bf_lo(rl[0]); l1 -= bf_lo(rl[1]);
        rl[2] = pack_bf16(l0, l0); rl[3] = pack_bf16(l1, l1);
      };
      set_rl();
      WG_WAIT(0);
      reg_fence(acc);
      rel_b(v8);
      if (__builtin_expect(unsafe, 0)) {
        int o = hg * 4 + u; asm volatile("" : "+r"(o));
        o = (o * SKC + (SKC - WIN) + g) * (DH / 2) + q;
        safe_head((const uint32_t*)p.k + o, (const uint32_t*)p.v + o, fr, acc, l0, l1);
        set_rl();
      }
#pragma unroll
      for (int i = 0; i < 24; i++) {
        fr[8 * (i >> 2) + (i & 3)] = pack_bf16(acc[4 * i], acc[4 * i + 1]);
        fr[8 * (i >> 2) + 4 + (i & 3)] = pack_bf16(acc[4 * i + 2], acc[4 * i + 3]);
      }
    }

    float aF[80], aS[80];
    uint32_t pha = 0, a8 = 0, pa8 = 0, pb8 = 0;
#pragma unroll 1
    for (int s = 0; s < 19; s++) {
      const uint64_t d0 = mkdesc(sb, HI_O), dO = d0 + (a8 * (TA >> 7) + w * 256), dB = d0 + ((OFF_B >> 4) + b8 * (TB >> 7));
      mbar_wait(bar_a + a8, pha);
      mbar_wait(bar_b + b8, phb);
      WG_FENCE();
#pragma unroll
      for (int kk = 0; kk < 4; kk++) wg_ss160t(aF, dO + ((kk >> 1) * 512 + (kk & 1) * 2), dB + ((kk >> 1) * 640 + (kk & 1) * 64), kk != 0 || s != 0);
      WG_COMMIT();
      mbar_wait(bar_b + b8 + 8, phb);
      WG_WAIT(1);
      if (s > 0) { rel_a(pa8); rel_b(pb8 + 8); }
      WG_FENCE();
#pragma unroll
      for (int kk = 0; kk < 4; kk++) wg_ss160t(aS, dO + ((kk >> 1) * 512 + (kk & 1) * 2), dB + ((TB >> 4) + (kk >> 1) * 640 + (kk & 1) * 64), kk != 0 || s != 0);
      WG_COMMIT();
      if (s < 9) {
#pragma unroll
        for (int pp = 0; pp < 9; pp++) if (s == pp) store_o(pp, true);
      } else if (s < 15) {
        const int b = 2 * cw + ((lane >> 3) & 1);
        uint32_t ga = sb + OFF_B + TW + ((b * 11) >> 5) * (TB - 3840) + b * 1280 + (lane & 7) * 160 + (lane >> 4) * 16;
        if (s < 14) {
          mbar_wait(bar_x, 0);
          ga += 32 * (s - 9);
          ldsm4(ga, fr);
#pragma unroll
          for (int i = 0; i < 4; i++) {
            const uint2 st = lds64(s_stat + (cw * 16 + g + 8 * (i & 1)) * 8);
            const uint32_t d = hsub2(fr[i], st.x), xn = pack_bf16(bf_lo(d) * __uint_as_float(st.y), bf_hi(d) * __uint_as_float(st.y));
            fr[i] = pack_bf16(silu_f(bf_lo(xn)), silu_f(bf_hi(xn)));
          }
          stsm4(ga, fr);
        } else {
          mbar_wait(bar_u, 0);
          const uint2 sel = lds64(s_sel);
          const uint32_t row = qt * 128 + cw * 16 + (lane & 15);
          if (row == sel.x || row == sel.y) ga = s_sel + 16 + (row == sel.y ? 160 : 0) + (lane >> 4) * 16;
#pragma unroll
          for (int k = 0; k < 5; k++) ldsm4(ga + 32 * k, fr + 4 * k);
        }
      }
      WG_WAIT(1);
      rel_b(b8);
      pa8 = a8; a8 += 8; if (a8 == 40) { a8 = 0; pha ^= 1; }
      pb8 = b8; next_pair();
    }
    const int t128 = threadIdx.x & 127;
    uint4* const xbase = p.s->o + (size_t)(qt * 192 + nh * 24 + 10) * 512 + w * 640 + t128;
    uint4* const dst = xbase + kq * (48 * 512);
    float q1[40], q2[40], oth[40], own[40];
    auto take = [&](float (&x)[40], const float* a) {
#pragma unroll
      for (int k = 0; k < 40; k++) x[k] = __uint_as_float(__float_as_uint(a[k]) ^ zero);
      reg_fence(x);
    };
    reg_fence(aF);
    take(q1, aF);
    auto fa = [&](int i) { return mbar_try(bar_a + 8 * ((4 + i) % 5), i == 0); };
    auto fb = [&](int e) { return mbar_try(bar_b + 8 * (e % 6), (e / 6) & 1); };
    auto send = [&](int m) {
      const float* v = (m < 5 ? q1 : m < 10 ? q2 : oth) + 8 * (m % 5);
      st_pkt(dst + (m / 5) * 1280 + (m % 5) * 128, pack_bf16(v[0], v[1]) | 1, pack_bf16(v[2], v[3]), pack_bf16(v[4], v[5]), pack_bf16(v[6], v[7]));
    };
    static_for<20>([&](auto n_) {
      constexpr int n = n_.value, i = end_stage(n), e = 142 + n / 2, qi = n == 4 ? 1 : n == LQ ? 0 : n / 5;
      float (&acc_)[40] = qi == 0 ? q1 : qi == 1 ? q2 : qi == 2 ? oth : own;
      if (n == 0) while (!(fa(0) & fa(1) & fb(142) & fb(143))) {}
      if (n == 2) while (!(fa(2) & fa(3) & fb(144))) {}
      if (n == LQ) while (!(fa(4) & fb(145) & fb(146) & mbar_try(bar_z, 0))) {}
      if (n == 10) while (!(fb(147) & fb(148) & fb(149))) {}
      const uint64_t d0 = mkdesc(fresh(), HI_O);
      WG_FENCE();
#pragma unroll
      for (int kk = 0; kk < 4; kk++)
        wg_ss80t(acc_, d0 + w * 256 + (((4 + i) % 5) * (TA >> 4) + (kk >> 1) * 512 + (kk & 1) * 2),
                 d0 + ((OFF_B >> 4) + (e % 6) * (TB >> 4) + (n & 1) * 768 + (kk >> 1) * 384 + (kk & 1) * 64), 1);
      WG_COMMIT();
      if ((!(n & 1) && n <= 16) || n == 15 || n == LQ + 1) WG_WAIT(1);
      if (n == 0) rel_a(24);
      if (!(n & 1) && n <= 10) rel_b(8 * ((e - 1) % 6));
      if (n == Q2N) take(q2, aF + 40);
      if (n == 10) cluster_arrive();
      if (n == 12 || n == 14 || n == 16) rel_a(4u * n - 48);
      if (n == LQ + 1) reg_fence(q1);
      if (n == 10) reg_fence(q2);
      if (n == 15) reg_fence(oth);
      if (n == 15) while (!(fb(150) & fb(151))) {}
      static_for<sent(n + 1) - sent(n)>([&](auto k_) { send(sent(n) + k_.value); });
      if (n == 8) {
        reg_fence(aS);
#pragma unroll
        for (int k = 0; k < 40; k++) oth[k] = kq & 1 ? aS[k] : aS[40 + k];
        reg_fence(oth);
      }
      if (n == SWN) {
        reg_fence(aS);
#pragma unroll
        for (int k = 0; k < 40; k++) own[k] = kq & 1 ? aS[40 + k] : aS[k];
        reg_fence(own);
      }
    });
    uint32_t xr[20];
    const uint32_t xs = sb + OFF_B + 2 * TB + cw * 2560, xa = xs + (lane & 15) * 160 + (lane >> 4) * 16;
    mbar_wait(bar_b + 16, 1);
#pragma unroll
    for (int k = 0; k < 5; k++) ldsm4(xa + 32 * k, xr + 4 * k);
    {
      auto fetch = [&](int e, uint4 (&v)[5]) {
        mbar_wait(bar_e + 16 * e + 8 * w, 0);
#pragma unroll
        for (int i = 0; i < 5; i++) v[i] = lds128(sb + OFF_B + (3 + e) * TB + (w * 640 + i * 128 + t128) * 16);
      };
      auto add = [&](int e, uint4 (&v)[5]) {
        while (!(v[0].x & v[1].x & v[2].x & v[3].x & v[4].x & 1)) {
#pragma unroll
          for (int i = 0; i < 5; i++) v[i] = ld_pkt(xbase + (kq ^ ((0x132 >> (4 * e)) & 3)) * (48 * 512) + (e < 2 ? kq & 1 : 2) * 1280 + i * 128);
        }
#pragma unroll
        for (int i = 0; i < 5; i++) {
          float* o = own + 8 * i;
          o[0] += bf_lo(v[i].x); o[1] += bf_hi(v[i].x); o[2] += bf_lo(v[i].y); o[3] += bf_hi(v[i].y);
          o[4] += bf_lo(v[i].z); o[5] += bf_hi(v[i].z); o[6] += bf_lo(v[i].w); o[7] += bf_hi(v[i].w);
        }
      };
      WG_WAIT(0);
      reg_fence(own);
#pragma unroll 1
      for (int e = 0; e < 3; e++) { uint4 v[5]; fetch(e, v); add(e, v); }
      if (lane == 0) mbar_arrive(bar_w);
#pragma unroll
      for (int i = 0; i < 20; i++) xr[i] = hadd2(xr[i], hmul2(pack_bf16(own[2 * i], own[2 * i + 1]), fr[i]));
#pragma unroll
      for (int k = 0; k < 5; k++) stsm4(xa + 32 * k, xr + 4 * k);
      asm volatile("fence.proxy.async.shared::cta;" ::: "memory");
      __syncwarp();
      if (elect()) {
        tma2d_store(&tm_out, xs, nh * 320 + kq * 80, qt * 128 + cw * 16);
        asm volatile("cp.async.bulk.commit_group;\ncp.async.bulk.wait_group.read 0;" ::: "memory");
      }
      __syncwarp();
    }
    cluster_wait();
  } else {
    asm volatile("setmaxnreg.dec.sync.aligned.u32 40;");
    uint32_t tid_; asm volatile("mov.u32 %0, %%tid.x;" : "=r"(tid_));
    const int warp = __shfl_sync(~0u, tid_ >> 5, 0);
    auto is_warp = [&](int k) { uint32_t e; asm volatile("{\n.reg .pred q;\nsetp.eq.u32 q, %1, %2;\nselp.u32 %0, 1, 0, q;\n}" : "=r"(e) : "r"(warp), "r"(k)); return e != 0; };
    auto k_block = [&](int t) {
      const int i = (t * 11) >> 5;
      return ((i < 6 ? 2 * kq + (i & 1) : hg ^ (i & 1)) * 4 + (i >> 1)) * 6 + (t == 3 * i ? 4 : 2 * (t - 3 * i) - 2);
    };
    if (warp > 0) {
      const unsigned epoch = (unsigned)(__ldcg(&p.s->done) >> 7);
      int budget = WAIT_BUDGET;
      cluster_wait();
      const uint32_t tag = epoch + 1;
      mbar_wait(bar_b, 0, budget); mbar_wait(bar_b + 8, 0, budget);
      float cs0 = 0.f, cs1 = 0.f;
      const int n = rank * 96 + (warp - 1) * 32 + (lane & 15) * 2;
#pragma unroll 1
      for (int kg = ((qt >> 1) & 3) * 2 + (lane >> 4) * 5, e = kg + 5; kg < e; kg++) {
        const uint32_t ad = sb + OFF_B + kg * 3072 + (n >> 6) * 1024 + (n & 63) * 2;
#pragma unroll
        for (int k = 0; k < 8; k++) { const uint32_t v = lds32(ad ^ (k * 0x90)); cs0 += bf_lo(v); cs1 += bf_hi(v); }
      }
      cs0 += __shfl_xor_sync(~0u, cs0, 16); cs1 += __shfl_xor_sync(~0u, cs1, 16);
      if (lane < 16) st_pkt(p.s->cs + (hg * 8 + (qt >> 1)) * 96 + (n >> 1), __float_as_uint(cs0), __float_as_uint(cs1), 0, tag);
      mbar_wait(bar_a + 40, 0, budget);
      if (lane < 2) { uint32_t a; asm volatile("mapa.shared::cluster.u32 %0, %1, %2;" : "=r"(a) : "r"(bar_d), "r"(lane)); mbar_arrive_cluster(a); }
      cs0 = cs1 = 0.f;
#pragma unroll 1
      for (int e = is_warp(3) ? 0 : 1; e < 3; e++) {
        const uint4* src = e ? p.s->cs + (hg * 8 + 4 * e - 4) * 96 + (tid_ - 32) : p.s->stat + qt * 128 + lane;
        const int step = e ? 96 : 32;
        uint4 v[4];
        while (true) {
          uint32_t bad = 0;
#pragma unroll
          for (int i = 0; i < 4; i++) v[i] = ld_pkt(src + i * step);
#pragma unroll
          for (int i = 0; i < 4; i++) bad |= v[i].w ^ tag;
          if (!__any_sync(~0u, bad) || --budget < 0) break;
        }
#pragma unroll
        for (int i = 0; i < 4; i++) {
          if (e) { cs0 += __uint_as_float(v[i].x); cs1 += __uint_as_float(v[i].y); }
          else { sts32(s_stat + (i * 32 + lane) * 8, v[i].x); sts32(s_stat + 4 + (i * 32 + lane) * 8, v[i].y); }
        }
      }
      mbar_wait(bar_a + 40, 1, budget);
#pragma unroll 1
      for (int k = 0; k < 8; k++) {
        const uint32_t v = pack_bf16(cs0, cs1);
        sts32((sb + ((tid_ - 32) >> 5) * 1024 + lane * 4) ^ (k * 0x90), k < 3 ? v : 0);
        cs0 -= bf_lo(v); cs1 -= bf_hi(v);
      }
      asm volatile("fence.proxy.async.shared::cta;" ::: "memory");
      __syncwarp();
      if (lane == 0) mbar_arrive(bar_s);
      if (is_warp(1)) {
#pragma unroll 1
        for (int u = 0; u < 5; u++) {
          mbar_wait(bar_o, u & 1);
          if (lane == 0) red_release(&p.s->flag[u ? FL_O + (qt * 8 + hg) * 8 : FL_XN + qt * 32]);
          __syncwarp();
        }
      } else if (is_warp(2)) {
        mbar_wait(bar_x, 0, budget);
        while ((int)(ld_acquire(&p.s->flag[FL_FFN]) - tag) < 0 && --budget >= 0) {}
        if (lane < 21) {
          const uint4 v = __ldcg(lane ? (const uint4*)(p.s->gsel + (lane > 10 ? DM - 80 : 0) + nh * 320 + kq * 80) + lane - 1 : (const uint4*)p.s->sel);
          asm volatile("st.shared.v4.u32 [%0], {%1,%2,%3,%4};" ::"r"(s_sel + 16 * lane), "r"(v.x), "r"(v.y), "r"(v.z), "r"(v.w) : "memory");
        }
        __syncwarp();
        if (lane == 0) { mbar_arrive(bar_u); asm volatile("red.relaxed.gpu.global.add.u64 [%0], 1;" ::"l"(&p.s->done) : "memory"); }
        while ((int)(ld_acquire(&p.s->flag[FL_RD + (qt * 8 + (hg ^ 1)) * 8]) - tag) < 0 && --budget >= 0) __nanosleep(200);
        if (lane == 0) mbar_arrive(bar_z);
        mbar_wait(bar_w, 0, budget);
        if (budget < 0) asm volatile("st.global.u32 [%0], %1;" ::"l"(0ull), "r"(budget) : "memory");
      } else {
        wait_flag(&p.s->flag[FL_XN + qt * 32], (epoch + 1) * 8);
        fence_proxy_async();
        mbar_wait(bar_a + 72, 1);
        uint32_t a8 = 0, pha = 1;
        const int kb = (qt * 192 + k_block(lane)) * 512;
#pragma unroll 1
        for (int n = 0; n < 54; n++) {
          const int t = n - 30, ko = __shfl_sync(~0u, kb, t);
          if (t == 0 || t == 18) {
            wait_flag(&p.s->flag[FL_O + (qt * 8 + (t ? 2 * kq + (lane & 1) : lane & 7)) * 8], epoch * 4 + (t ? 4 : 3));
            fence_proxy_async();
          }
          mbar_wait(bar_a + 40 + a8, pha);
          const uint32_t fb = bar_a + a8, dst = sb + a8 * (TA >> 3);
          if (elect()) {
            if (t >= 0) {
              mbar_expect_tx(fb, TA);
              bulk_load(dst, p.s->o + ko, TA, fb);
              if (t == 8) {
                mbar_expect_tx(bar_x, 6 * 3840);
#pragma unroll 1
                for (int e = 0; e < 6; e++) tma2d(sb + OFF_B + TW + e * TB, &tm_xg, nh * 320 + kq * 80, qt * 128 + e * 24, bar_x);
                asm volatile("prefetch.tensormap [%0];\nprefetch.tensormap [%1];\nprefetch.tensormap [%2];\nprefetch.tensormap [%3];"
                             ::"l"(tm_w), "l"(tm_w + 1), "l"(&tm_xe), "l"(&tm_out) : "memory");
              }
              if (t == 22) asm volatile("red.relaxed.gpu.global.add.u32 [%0], 1;" ::"l"(&p.s->flag[FL_RD + (qt * 8 + hg) * 8]) : "memory");
            } else if (n >= 10 && pha) mbar_arrive(fb);
            else { mbar_expect_tx(fb, TA); tma2d(dst, &tm_xn, 8 * a8 + (pha || (n >= 15 && n < 20) ? 0 : 320), qt * 128, fb); }
          }
          a8 += 8; if (a8 == 40) { a8 = 0; pha ^= 1; }
        }
        if (lane == 0) mbar_arrive(bar_z);
      }
    } else {
      cluster_wait();
      uint32_t fb = bar_b, dst = sb + OFF_B, ph = 1;
      auto next = [&]() { fb += 8; dst += TB; if (fb == bar_b + 48) { fb = bar_b; dst = sb + OFF_B; ph ^= 1; } };
#pragma unroll 1
      for (int u = 0; u < 4; u++) {
        const int h = hg * 4 + u;
        int s = u ? (u == 2 ? 5 : 0) : (5 * (qt >> 1)) >> 2;
#pragma unroll 1
        for (int i = 0; i < 10; i++) {
          if (u == 0) {
            const uint32_t a8 = 8 * (i < 5 ? i : i - 5);
            mbar_wait(bar_a + 40 + a8, i < 5);
            if (elect()) { mbar_expect_tx(bar_a + a8, TA); tma2d(sb + a8 * (TA >> 3), &tm_x, 64 * s, qt * 128, bar_a + a8); }
            if (i == 6) mbar_wait(bar_d, 0);
          }
          mbar_wait(fb + 48, ph);
          if (elect()) { mbar_expect_tx(fb, TB); tma4d_mc(dst + rank * (TB / 2), &tm_wq, 3 * h, 8 * s + 4 * rank, fb); }
          next();
          if (++s == 10) s = 0;
        }
        const int kv0 = (h * SKC + (SKC - WIN)) / 8 + 4 * rank;
#pragma unroll 1
        for (int i = 0; i < 16; i++) {
          const bool isk = (0x2AAB >> i) & 1;
          mbar_wait(fb + 48, ph);
          if (elect()) { mbar_expect_tx(fb, TB); tma4d_mc(dst + rank * (TB / 2), isk ? &tm_k : &tm_v, 0, kv0 + 8 * (isk ? (i + 1) >> 1 : (i - 1) >> 1), fb); }
          next();
        }
      }
      const int cF = 10 * nh + 5 - 5 * (kq >> 1), cS = 10 * nh + 5 * (kq >> 1);
      const int kb = 4 * (k_block(lane) + rank);
#pragma unroll 1
      for (int m = 0; m < 38; m++) {
        const int c2 = __shfl_sync(~0u, kb, m >> 1);
        mbar_wait(fb + 48, ph);
        if (elect()) { mbar_expect_tx(fb, TW); tma5d_mc(dst + rank * (TW / 2), &tm_wo, c2, m & 1 ? cS : cF, fb); }
        next();
      }
      const int odd = (((0x7ff0 ^ 1 << LQ) ^ (kq & 1 ? 0xffc00 : 0)) >> lane) & 1;
      const int tq = __shfl_sync(~0u, kb, 19 + end_stage(lane)) << 16 | odd << 7 | ((lane < 10 ? cF : cS) + 2 * odd);
#pragma unroll 1
      for (int n = 0; n < 20; n += 2) {
        const int t0 = __shfl_sync(~0u, tq, n), t1 = __shfl_sync(~0u, tq, n + 1);
        mbar_wait(fb + 48, ph);
        if (elect()) {
          mbar_expect_tx(fb, TB);
          tma5d_mc(dst + rank * (TB / 4), (const CUtensorMap*)((const char*)tm_w + (t0 & 128)), t0 >> 16, t0 & 31, fb);
          tma5d_mc(dst + TB / 2 + rank * (TB / 4), (const CUtensorMap*)((const char*)tm_w + (t1 & 128)), t1 >> 16, t1 & 31, fb);
        }
        next();
      }
      mbar_wait(fb + 48, ph);
      if (elect()) { mbar_expect_tx(fb, TW); tma2d(dst, &tm_xe, nh * 320 + kq * 80, qt * 128, fb); }
    }
    if (!is_warp(2)) {
      const int e = warp - (warp >> 1), ms = 2 * e + ((lane >> 2) & 1);
      const uint4* src = p.s->o + (size_t)(qt * 192 + nh * 24 + 10 + (kq ^ ((0x132 >> (4 * e)) & 3)) * 48) * 512 + (e < 2 ? kq & 1 : 2) * 1280 + (ms & 1) * 640;
      uint32_t todo = 0xff;
      bool ok = lane >= 8;
      mbar_wait(bar_z, 0);
#pragma unroll 1
      while (todo) {
        if (!ok) ok = ld_pkt(src + 4 * 128 + (lane & 3) * 32 + 31).x & 1;
        const uint32_t got = __ballot_sync(~0u, ok) & todo, go = __ballot_sync(~0u, ((got >> (lane & 28)) & 15) == 15);
        if (go) mbar_wait(bar_a + 40 + 8 * e, 0);
        if ((go & 0x11) >> lane & 1) {
          mbar_expect_tx(bar_e + 8 * ms, TW / 2); bulk_load(sb + OFF_B + (3 + e) * TB + (ms & 1) * (TW / 2), src, TW / 2, bar_e + 8 * ms);
        }
        todo &= ~go;
      }
    }
    cluster_sync();
  }
}

typedef CUresult (*EncodeFn)(CUtensorMap*, CUtensorMapDataType, cuuint32_t, void*, const cuuint64_t*, const cuuint64_t*,
                             const cuuint32_t*, const cuuint32_t*, CUtensorMapInterleave, CUtensorMapSwizzle,
                             CUtensorMapL2promotion, CUtensorMapFloatOOBfill);

void encode(EncodeFn fn, CUtensorMap* tm, void* base, int rank, const cuuint64_t* dims, const cuuint64_t* strides,
            const cuuint32_t* box, CUtensorMapSwizzle sw) {
  const cuuint32_t es[5] = {1, 1, 1, 1, 1};
  fn(tm, CU_TENSOR_MAP_DATA_TYPE_BFLOAT16, rank, base, dims, strides, box, es, CU_TENSOR_MAP_INTERLEAVE_NONE, sw,
     CU_TENSOR_MAP_L2_PROMOTION_L2_128B, CU_TENSOR_MAP_FLOAT_OOB_FILL_NONE);
}

}

extern "C" void kernel_launch(void* const* d_in, const int* in_sizes, int n_in, void* d_out, int out_size) {
  static EncodeFn fn = nullptr;
  static Scratch* scr = nullptr;
  if (!fn) {
    void* f = nullptr;
    cudaDriverEntryPointQueryResult st;
    cudaGetDriverEntryPoint("cuTensorMapEncodeTiled", &f, cudaEnableDefault, &st);
    fn = (EncodeFn)f;
    cudaGetSymbolAddress((void**)&scr, g_scratch);
    cudaFuncSetAttribute(fused_kernel, cudaFuncAttributeMaxDynamicSharedMemorySize, SMEM_BYTES);
  }
  CUtensorMap tm_x, tm_xn, tm_wq, tm_k, tm_v, tm_wo, tm_xg, tm_xe, tm_out;
  MapPair tm_w2;
  { const cuuint64_t d[2] = {DM, SQ}, s[1] = {DM * 2}; const cuuint32_t b[2] = {64, 128};
    encode(fn, &tm_x, d_in[0], 2, d, s, b, CU_TENSOR_MAP_SWIZZLE_128B);
    encode(fn, &tm_xn, scr->xn, 2, d, s, b, CU_TENSOR_MAP_SWIZZLE_128B); }
  { const cuuint64_t d[4] = {64, 8, QD / 64, DM / 8}, s[3] = {QD * 2, 128, 8 * QD * 2}; const cuuint32_t b[4] = {64, 8, 3, 4};
    encode(fn, &tm_wq, d_in[3], 4, d, s, b, CU_TENSOR_MAP_SWIZZLE_128B); }
  { const cuuint64_t d[4] = {64, 8, 3, NH * SKC / 8}, s[3] = {DH * 2, 128, 8 * DH * 2}; const cuuint32_t b[4] = {64, 8, 3, 4};
    encode(fn, &tm_k, d_in[1], 4, d, s, b, CU_TENSOR_MAP_SWIZZLE_128B);
    encode(fn, &tm_v, d_in[2], 4, d, s, b, CU_TENSOR_MAP_SWIZZLE_128B); }
  {
    const cuuint64_t d[5] = {32, 2, QD / 8, 4, DM / 32}, s[4] = {DM * 2, 8 * DM * 2, 2 * DM * 2, 64}; const cuuint32_t b[5] = {32, 2, 4, 4, 5};
    encode(fn, &tm_wo, d_in[4], 5, d, s, b, CU_TENSOR_MAP_SWIZZLE_64B);
    const cuuint32_t b3[5] = {32, 2, 4, 4, 3};
    encode(fn, &tm_w2.m[0], d_in[4], 5, d, s, b3, CU_TENSOR_MAP_SWIZZLE_64B);
    encode(fn, &tm_w2.m[1], (char*)d_in[4] + 32, 5, d, s, b3, CU_TENSOR_MAP_SWIZZLE_64B); }
  { const cuuint64_t d[2] = {DM, SQ}, s[1] = {DM * 2}; const cuuint32_t bg[2] = {80, 24}, bx[2] = {80, 128}, bo[2] = {80, 16};
    encode(fn, &tm_xg, d_in[0], 2, d, s, bg, CU_TENSOR_MAP_SWIZZLE_NONE);
    encode(fn, &tm_xe, d_in[0], 2, d, s, bx, CU_TENSOR_MAP_SWIZZLE_NONE);
    encode(fn, &tm_out, d_out, 2, d, s, bo, CU_TENSOR_MAP_SWIZZLE_NONE); }
  Params p;
  p.x = (const __nv_bfloat16*)d_in[0]; p.wr = (const __nv_bfloat16*)d_in[6]; p.wg = (const __nv_bfloat16*)d_in[7];
  p.wu = (const __nv_bfloat16*)d_in[8]; p.wd = (const __nv_bfloat16*)d_in[9];

  p.k = (const __nv_bfloat16*)d_in[1]; p.v = (const __nv_bfloat16*)d_in[2]; p.s = scr;
  cudaLaunchConfig_t cfg = {};
  cfg.gridDim = dim3(132); cfg.blockDim = dim3(384); cfg.dynamicSmemBytes = SMEM_BYTES; cfg.stream = cudaStreamPerThread;
  cudaLaunchAttribute at[1];
  at[0].id = cudaLaunchAttributeClusterDimension; at[0].val.clusterDim.x = 2; at[0].val.clusterDim.y = 1; at[0].val.clusterDim.z = 1;
  cfg.attrs = at; cfg.numAttrs = 1;
  cudaLaunchKernelEx(&cfg, fused_kernel, p, tm_x, tm_xn, tm_wq, tm_k, tm_v, tm_wo, tm_w2, tm_xg, tm_xe, tm_out);
}
```

```cpp
#include <cuda_runtime.h>
#include <cuda_bf16.h>
#include <cuda.h>
#include <stdint.h>

namespace {

constexpr int SQ = 2048, DM = 640, NH = 32, DH = 192, SKC = 2048, WIN = 512, FF = 1536;
constexpr int QD = NH * DH;
constexpr uint32_t TA = 16384, TB = 24576, TW = 20480, OFF_B = 5 * TA, OFF_M = OFF_B + 6 * TB, SMEM_BYTES = OFF_M + 3072;
constexpr int WAIT_BUDGET = 1 << 20;

constexpr int FL_XN = 0;
constexpr int FL_O = 512;
constexpr int FL_RD = FL_O + 1024;
constexpr int FL_FFN = FL_RD + 1024;
constexpr int FL_SIDE = FL_FFN + 32;
struct __align__(1024) Scratch {
  unsigned long long done, pad0[15];
  unsigned flag[FL_SIDE + 32];
  uint4 cand[8];
  float ffn[4 * 2 * DM];
  int sel[4];
  __nv_bfloat16 gsel[2 * DM];
  uint4 cs[8 * 8 * DH / 2];
  uint4 stat[SQ];
  __align__(1024) __nv_bfloat16 xn[SQ * DM];
  __align__(1024) uint4 o[SQ * QD / 8];
};
__device__ Scratch g_scratch;

__device__ __forceinline__ uint32_t smem_u32(const void* p) { return (uint32_t)__cvta_generic_to_shared(p); }
__device__ __forceinline__ void mbar_init(uint32_t bar, int cnt) { asm volatile("mbarrier.init.shared::cta.b64 [%0], %1;" ::"r"(bar), "r"(cnt)); }
__device__ __forceinline__ void mbar_expect_tx(uint32_t bar, uint32_t bytes) {
  asm volatile("mbarrier.arrive.expect_tx.shared::cta.b64 _, [%0], %1;" ::"r"(bar), "r"(bytes) : "memory");
}
__device__ __forceinline__ void mbar_arrive(uint32_t bar) { asm volatile("mbarrier.arrive.shared::cta.b64 _, [%0];" ::"r"(bar) : "memory"); }
__device__ __forceinline__ void mbar_arrive_cluster(uint32_t addr) { asm volatile("mbarrier.arrive.shared::cluster.b64 _, [%0];" ::"r"(addr) : "memory"); }
__device__ __forceinline__ bool mbar_try(uint32_t bar, uint32_t parity) {
  uint32_t ok;
  asm volatile("{\n.reg .pred p;\nmbarrier.try_wait.parity.shared::cta.b64 p, [%1], %2;\nselp.u32 %0, 1, 0, p;\n}\n" : "=r"(ok) : "r"(bar), "r"(parity) : "memory");
  return ok;
}
__device__ __forceinline__ void mbar_wait(uint32_t bar, uint32_t parity, int& budget) {
#pragma unroll 1
  while (!mbar_try(bar, parity)) { if (--budget < 0) break; }
}
__device__ __forceinline__ void mbar_wait(uint32_t bar, uint32_t parity) {
#pragma unroll 1
  while (!mbar_try(bar, parity)) {}
}
__device__ __forceinline__ unsigned ld_acquire(const unsigned* p) { unsigned v; asm volatile("ld.acquire.gpu.global.u32 %0, [%1];" : "=r"(v) : "l"(p) : "memory"); return v; }
__device__ __forceinline__ void wait_flag(const unsigned* p, unsigned target) {
#pragma unroll 1
  while (__any_sync(~0u, (int)(ld_acquire(p) - target) < 0)) {}
}
__device__ __forceinline__ void red_release(unsigned* p) { asm volatile("red.release.gpu.global.add.u32 [%0], 1;" ::"l"(p) : "memory"); }
__device__ __forceinline__ void fence_proxy_async() { asm volatile("fence.proxy.async.global;" ::: "memory"); }
__device__ __forceinline__ bool elect() {
  uint32_t p;
  asm volatile("{\n.reg .pred P;\nelect.sync _|P, 0xffffffff;\nselp.u32 %0, 1, 0, P;\n}\n" : "=r"(p));
  return p;
}
__device__ __forceinline__ void cluster_arrive() { asm volatile("barrier.cluster.arrive.relaxed.aligned;" ::: "memory"); }
__device__ __forceinline__ void cluster_wait() { asm volatile("barrier.cluster.wait.aligned;" ::: "memory"); }
__device__ __forceinline__ void cluster_sync() { cluster_arrive(); cluster_wait(); }
__device__ __forceinline__ void tma2d(uint32_t dst, const CUtensorMap* tm, int c0, int c1, uint32_t bar) {
  asm volatile("cp.async.bulk.tensor.2d.shared::cluster.global.mbarrier::complete_tx::bytes [%0], [%1, {%3, %4}], [%2];"
               ::"r"(dst), "l"(tm), "r"(bar), "r"(c0), "r"(c1) : "memory");
}
constexpr uint64_t POL_FIRST = 0x12F0000000000000ull;
__device__ __forceinline__ void tma4d_mc(uint32_t dst, const CUtensorMap* tm, int c2, int c3, uint32_t bar) {
  asm volatile("cp.async.bulk.tensor.4d.shared::cluster.global.mbarrier::complete_tx::bytes.multicast::cluster.L2::cache_hint [%0], [%1, {%3, %3, %4, %5}], [%2], %6, %7;"
               ::"r"(dst), "l"(tm), "r"(bar), "r"(0), "r"(c2), "r"(c3), "h"((uint16_t)3), "l"(POL_FIRST) : "memory");
}
__device__ __forceinline__ void tma5d_mc(uint32_t dst, const CUtensorMap* tm, int c2, int c4, uint32_t bar) {
  asm volatile("cp.async.bulk.tensor.5d.shared::cluster.global.mbarrier::complete_tx::bytes.multicast::cluster.L2::cache_hint [%0], [%1, {%3, %3, %4, %3, %5}], [%2], %6, %7;"
               ::"r"(dst), "l"(tm), "r"(bar), "r"(0), "r"(c2), "r"(c4), "h"((uint16_t)3), "l"(POL_FIRST) : "memory");
}
__device__ __forceinline__ void bulk_load(uint32_t dst, const void* src, uint32_t bytes, uint32_t bar) {
  asm volatile("cp.async.bulk.shared::cluster.global.mbarrier::complete_tx::bytes.L2::cache_hint [%0], [%1], %2, [%3], %4;" ::"r"(dst), "l"(src), "r"(bytes), "r"(bar), "l"(POL_FIRST) : "memory");
}
__device__ __forceinline__ void tma2d_store(const CUtensorMap* tm, uint32_t src, int c0, int c1) {
  asm volatile("cp.async.bulk.tensor.2d.global.shared::cta.bulk_group [%0, {%2, %3}], [%1];" ::"l"(tm), "r"(src), "r"(c0), "r"(c1) : "memory");
}
__device__ __forceinline__ uint32_t lds32(uint32_t a) { uint32_t v; asm volatile("ld.shared.u32 %0, [%1];" : "=r"(v) : "r"(a) : "memory"); return v; }
__device__ __forceinline__ uint2 lds64(uint32_t a) { uint2 v; asm volatile("ld.shared.v2.u32 {%0,%1}, [%2];" : "=r"(v.x), "=r"(v.y) : "r"(a) : "memory"); return v; }
__device__ __forceinline__ uint4 lds128(uint32_t a) { uint4 v; asm volatile("ld.shared.v4.u32 {%0,%1,%2,%3}, [%4];" : "=r"(v.x), "=r"(v.y), "=r"(v.z), "=r"(v.w) : "r"(a) : "memory"); return v; }
__device__ __forceinline__ void ldsm4(uint32_t a, uint32_t* v) {
  asm volatile("ldmatrix.sync.aligned.m8n8.x4.shared.b16 {%0,%1,%2,%3}, [%4];" : "=r"(v[0]), "=r"(v[1]), "=r"(v[2]), "=r"(v[3]) : "r"(a) : "memory");
}
__device__ __forceinline__ void stsm4(uint32_t a, const uint32_t* v) {
  asm volatile("stmatrix.sync.aligned.m8n8.x4.shared.b16 [%0], {%1,%2,%3,%4};" ::"r"(a), "r"(v[0]), "r"(v[1]), "r"(v[2]), "r"(v[3]) : "memory");
}
__device__ __forceinline__ void sts32(uint32_t a, uint32_t v) { asm volatile("st.shared.u32 [%0], %1;" ::"r"(a), "r"(v) : "memory"); }
__device__ __forceinline__ void st_pkt(uint4* p, uint32_t a, uint32_t b, uint32_t c, uint32_t d) {
  asm volatile("st.relaxed.gpu.global.v4.b32 [%0], {%1, %2, %3, %4};" ::"l"(p), "r"(a), "r"(b), "r"(c), "r"(d) : "memory");
}
__device__ __forceinline__ uint4 ld_pkt(const uint4* p) {
  uint4 v;
  asm volatile("{\n.reg .b128 v;\nld.relaxed.gpu.global.b128 v, [%4];\nmov.b128 {%0, %1, %2, %3}, v;\n}\n" : "=r"(v.x), "=r"(v.y), "=r"(v.z), "=r"(v.w) : "l"(p) : "memory");
  return v;
}
__device__ __forceinline__ uint4 ldg_nc(const void* p) {
  uint4 v;
  asm volatile("ld.global.nc.v4.u32 {%0,%1,%2,%3}, [%4];" : "=r"(v.x), "=r"(v.y), "=r"(v.z), "=r"(v.w) : "l"(p));
  return v;
}
#define WG_FENCE() asm volatile("wgmma.fence.sync.aligned;" ::: "memory")
#define WG_COMMIT() asm volatile("wgmma.commit_group.sync.aligned;" ::: "memory")
#define WG_WAIT(n) asm volatile("wgmma.wait_group.sync.aligned " #n ";" ::: "memory")
template <int N> __device__ __forceinline__ void reg_fence(float (&d)[N]) {
#pragma unroll
  for (int i = 0; i < N; i++) asm volatile("" : "+f"(d[i])::"memory");
}
template <int N> __device__ __forceinline__ void reg_fence(uint32_t (&d)[N]) {
#pragma unroll
  for (int i = 0; i < N; i++) asm volatile("" : "+r"(d[i])::"memory");
}
__device__ __forceinline__ constexpr uint64_t desc_hi(uint32_t lbo, uint32_t sbo, uint64_t sw) {
  return ((uint64_t)(lbo >> 4) << 16) | ((uint64_t)(sbo >> 4) << 32) | (sw << 62);
}
__device__ __forceinline__ uint64_t mkdesc(uint32_t addr, uint64_t hi) { return hi | (uint64_t)((addr & 0x3FFFF) >> 4); }
__device__ __forceinline__ uint32_t pack_bf16(float lo, float hi) { uint32_t r; asm("cvt.rn.bf16x2.f32 %0, %1, %2;" : "=r"(r) : "f"(hi), "f"(lo)); return r; }
__device__ __forceinline__ float bf_lo(uint32_t v) { return __uint_as_float(v << 16); }
__device__ __forceinline__ float bf_hi(uint32_t v) { return __uint_as_float(v & 0xffff0000u); }
__device__ __forceinline__ uint32_t hadd2(uint32_t a, uint32_t b) { uint32_t r; asm("add.rn.bf16x2 %0, %1, %2;" : "=r"(r) : "r"(a), "r"(b)); return r; }
__device__ __forceinline__ uint32_t hsub2(uint32_t a, uint32_t b) { uint32_t r; asm("sub.rn.bf16x2 %0, %1, %2;" : "=r"(r) : "r"(a), "r"(b)); return r; }
__device__ __forceinline__ uint32_t hmul2(uint32_t a, uint32_t b) { uint32_t r; asm("mul.rn.bf16x2 %0, %1, %2;" : "=r"(r) : "r"(a), "r"(b)); return r; }
__device__ __forceinline__ float rbf(float x) { return __bfloat162float(__float2bfloat16_rn(x)); }
__device__ __forceinline__ float ex2(float x) { float y; asm("ex2.approx.ftz.f32 %0, %1;" : "=f"(y) : "f"(x)); return y; }
__device__ __forceinline__ float rcp(float x) { float y; asm("rcp.approx.ftz.f32 %0, %1;" : "=f"(y) : "f"(x)); return y; }
__device__ __forceinline__ float sigmoid_f(float x) { return rcp(1.f + ex2(x * -1.4426950408889634f)); }
__device__ __forceinline__ float silu_f(float x) { return x * sigmoid_f(x); }

__device__ __forceinline__ void wg_ss192t(float (&d)[96], uint64_t da, uint64_t db, int sd) {
  asm volatile("{\n.reg .pred p;\nsetp.ne.b32 p, %98, 0;\n"
    "wgmma.mma_async.sync.aligned.m64n192k16.f32.bf16.bf16 {%0,%1,%2,%3,%4,%5,%6,%7,%8,%9,%10,%11,%12,%13,%14,%15,%16,%17,%18,%19,%20,%21,%22,%23,%24,%25,%26,%27,%28,%29,%30,%31,%32,%33,%34,%35,%36,%37,%38,%39,%40,%41,%42,%43,%44,%45,%46,%47,%48,%49,%50,%51,%52,%53,%54,%55,%56,%57,%58,%59,%60,%61,%62,%63,%64,%65,%66,%67,%68,%69,%70,%71,%72,%73,%74,%75,%76,%77,%78,%79,%80,%81,%82,%83,%84,%85,%86,%87,%88,%89,%90,%91,%92,%93,%94,%95}, %96, %97, p, 1, 1, 0, 1;\n}\n"
    : "+f"(d[0]),"+f"(d[1]),"+f"(d[2]),"+f"(d[3]),"+f"(d[4]),"+f"(d[5]),"+f"(d[6]),"+f"(d[7]),"+f"(d[8]),"+f"(d[9]),"+f"(d[10]),"+f"(d[11]),"+f"(d[12]),"+f"(d[13]),"+f"(d[14]),"+f"(d[15]),"+f"(d[16]),"+f"(d[17]),"+f"(d[18]),"+f"(d[19]),"+f"(d[20]),"+f"(d[21]),"+f"(d[22]),"+f"(d[23]),"+f"(d[24]),"+f"(d[25]),"+f"(d[26]),"+f"(d[27]),"+f"(d[28]),"+f"(d[29]),"+f"(d[30]),"+f"(d[31]),"+f"(d[32]),"+f"(d[33]),"+f"(d[34]),"+f"(d[35]),"+f"(d[36]),"+f"(d[37]),"+f"(d[38]),"+f"(d[39]),"+f"(d[40]),"+f"(d[41]),"+f"(d[42]),"+f"(d[43]),"+f"(d[44]),"+f"(d[45]),"+f"(d[46]),"+f"(d[47]),"+f"(d[48]),"+f"(d[49]),"+f"(d[50]),"+f"(d[51]),"+f"(d[52]),"+f"(d[53]),"+f"(d[54]),"+f"(d[55]),"+f"(d[56]),"+f"(d[57]),"+f"(d[58]),"+f"(d[59]),"+f"(d[60]),"+f"(d[61]),"+f"(d[62]),"+f"(d[63]),"+f"(d[64]),"+f"(d[65]),"+f"(d[66]),"+f"(d[67]),"+f"(d[68]),"+f"(d[69]),"+f"(d[70]),"+f"(d[71]),"+f"(d[72]),"+f"(d[73]),"+f"(d[74]),"+f"(d[75]),"+f"(d[76]),"+f"(d[77]),"+f"(d[78]),"+f"(d[79]),"+f"(d[80]),"+f"(d[81]),"+f"(d[82]),"+f"(d[83]),"+f"(d[84]),"+f"(d[85]),"+f"(d[86]),"+f"(d[87]),"+f"(d[88]),"+f"(d[89]),"+f"(d[90]),"+f"(d[91]),"+f"(d[92]),"+f"(d[93]),"+f"(d[94]),"+f"(d[95])
    : "l"(da), "l"(db), "r"(sd));
}
__device__ __forceinline__ void wg_rs64(float (&d)[32], uint32_t a0, uint32_t a1, uint32_t a2, uint32_t a3, uint64_t db, int sd) {
  asm volatile("{\n.reg .pred p;\nsetp.ne.b32 p, %37, 0;\n"
    "wgmma.mma_async.sync.aligned.m64n64k16.f32.bf16.bf16 {%0,%1,%2,%3,%4,%5,%6,%7,%8,%9,%10,%11,%12,%13,%14,%15,%16,%17,%18,%19,%20,%21,%22,%23,%24,%25,%26,%27,%28,%29,%30,%31}, {%32,%33,%34,%35}, %36, p, 1, 1, 0;\n}\n"
    : "+f"(d[0]),"+f"(d[1]),"+f"(d[2]),"+f"(d[3]),"+f"(d[4]),"+f"(d[5]),"+f"(d[6]),"+f"(d[7]),"+f"(d[8]),"+f"(d[9]),"+f"(d[10]),"+f"(d[11]),"+f"(d[12]),"+f"(d[13]),"+f"(d[14]),"+f"(d[15]),"+f"(d[16]),"+f"(d[17]),"+f"(d[18]),"+f"(d[19]),"+f"(d[20]),"+f"(d[21]),"+f"(d[22]),"+f"(d[23]),"+f"(d[24]),"+f"(d[25]),"+f"(d[26]),"+f"(d[27]),"+f"(d[28]),"+f"(d[29]),"+f"(d[30]),"+f"(d[31])
    : "r"(a0), "r"(a1), "r"(a2), "r"(a3), "l"(db), "r"(sd));
}
__device__ __forceinline__ void wg_rs192t(float (&d)[96], uint32_t a0, uint32_t a1, uint32_t a2, uint32_t a3, uint64_t db, int sd) {
  asm volatile("{\n.reg .pred p;\nsetp.ne.b32 p, %101, 0;\n"
    "wgmma.mma_async.sync.aligned.m64n192k16.f32.bf16.bf16 {%0,%1,%2,%3,%4,%5,%6,%7,%8,%9,%10,%11,%12,%13,%14,%15,%16,%17,%18,%19,%20,%21,%22,%23,%24,%25,%26,%27,%28,%29,%30,%31,%32,%33,%34,%35,%36,%37,%38,%39,%40,%41,%42,%43,%44,%45,%46,%47,%48,%49,%50,%51,%52,%53,%54,%55,%56,%57,%58,%59,%60,%61,%62,%63,%64,%65,%66,%67,%68,%69,%70,%71,%72,%73,%74,%75,%76,%77,%78,%79,%80,%81,%82,%83,%84,%85,%86,%87,%88,%89,%90,%91,%92,%93,%94,%95}, {%96,%97,%98,%99}, %100, p, 1, 1, 1;\n}\n"
    : "+f"(d[0]),"+f"(d[1]),"+f"(d[2]),"+f"(d[3]),"+f"(d[4]),"+f"(d[5]),"+f"(d[6]),"+f"(d[7]),"+f"(d[8]),"+f"(d[9]),"+f"(d[10]),"+f"(d[11]),"+f"(d[12]),"+f"(d[13]),"+f"(d[14]),"+f"(d[15]),"+f"(d[16]),"+f"(d[17]),"+f"(d[18]),"+f"(d[19]),"+f"(d[20]),"+f"(d[21]),"+f"(d[22]),"+f"(d[23]),"+f"(d[24]),"+f"(d[25]),"+f"(d[26]),"+f"(d[27]),"+f"(d[28]),"+f"(d[29]),"+f"(d[30]),"+f"(d[31]),"+f"(d[32]),"+f"(d[33]),"+f"(d[34]),"+f"(d[35]),"+f"(d[36]),"+f"(d[37]),"+f"(d[38]),"+f"(d[39]),"+f"(d[40]),"+f"(d[41]),"+f"(d[42]),"+f"(d[43]),"+f"(d[44]),"+f"(d[45]),"+f"(d[46]),"+f"(d[47]),"+f"(d[48]),"+f"(d[49]),"+f"(d[50]),"+f"(d[51]),"+f"(d[52]),"+f"(d[53]),"+f"(d[54]),"+f"(d[55]),"+f"(d[56]),"+f"(d[57]),"+f"(d[58]),"+f"(d[59]),"+f"(d[60]),"+f"(d[61]),"+f"(d[62]),"+f"(d[63]),"+f"(d[64]),"+f"(d[65]),"+f"(d[66]),"+f"(d[67]),"+f"(d[68]),"+f"(d[69]),"+f"(d[70]),"+f"(d[71]),"+f"(d[72]),"+f"(d[73]),"+f"(d[74]),"+f"(d[75]),"+f"(d[76]),"+f"(d[77]),"+f"(d[78]),"+f"(d[79]),"+f"(d[80]),"+f"(d[81]),"+f"(d[82]),"+f"(d[83]),"+f"(d[84]),"+f"(d[85]),"+f"(d[86]),"+f"(d[87]),"+f"(d[88]),"+f"(d[89]),"+f"(d[90]),"+f"(d[91]),"+f"(d[92]),"+f"(d[93]),"+f"(d[94]),"+f"(d[95])
    : "r"(a0), "r"(a1), "r"(a2), "r"(a3), "l"(db), "r"(sd));
}
__device__ __forceinline__ void wg_ss160t(float (&d)[80], uint64_t da, uint64_t db, int sd) {
  asm volatile("{\n.reg .pred p;\nsetp.ne.b32 p, %82, 0;\n"
    "wgmma.mma_async.sync.aligned.m64n160k16.f32.bf16.bf16 {%0,%1,%2,%3,%4,%5,%6,%7,%8,%9,%10,%11,%12,%13,%14,%15,%16,%17,%18,%19,%20,%21,%22,%23,%24,%25,%26,%27,%28,%29,%30,%31,%32,%33,%34,%35,%36,%37,%38,%39,%40,%41,%42,%43,%44,%45,%46,%47,%48,%49,%50,%51,%52,%53,%54,%55,%56,%57,%58,%59,%60,%61,%62,%63,%64,%65,%66,%67,%68,%69,%70,%71,%72,%73,%74,%75,%76,%77,%78,%79}, %80, %81, p, 1, 1, 0, 1;\n}\n"
    : "+f"(d[0]),"+f"(d[1]),"+f"(d[2]),"+f"(d[3]),"+f"(d[4]),"+f"(d[5]),"+f"(d[6]),"+f"(d[7]),"+f"(d[8]),"+f"(d[9]),"+f"(d[10]),"+f"(d[11]),"+f"(d[12]),"+f"(d[13]),"+f"(d[14]),"+f"(d[15]),"+f"(d[16]),"+f"(d[17]),"+f"(d[18]),"+f"(d[19]),"+f"(d[20]),"+f"(d[21]),"+f"(d[22]),"+f"(d[23]),"+f"(d[24]),"+f"(d[25]),"+f"(d[26]),"+f"(d[27]),"+f"(d[28]),"+f"(d[29]),"+f"(d[30]),"+f"(d[31]),"+f"(d[32]),"+f"(d[33]),"+f"(d[34]),"+f"(d[35]),"+f"(d[36]),"+f"(d[37]),"+f"(d[38]),"+f"(d[39]),"+f"(d[40]),"+f"(d[41]),"+f"(d[42]),"+f"(d[43]),"+f"(d[44]),"+f"(d[45]),"+f"(d[46]),"+f"(d[47]),"+f"(d[48]),"+f"(d[49]),"+f"(d[50]),"+f"(d[51]),"+f"(d[52]),"+f"(d[53]),"+f"(d[54]),"+f"(d[55]),"+f"(d[56]),"+f"(d[57]),"+f"(d[58]),"+f"(d[59]),"+f"(d[60]),"+f"(d[61]),"+f"(d[62]),"+f"(d[63]),"+f"(d[64]),"+f"(d[65]),"+f"(d[66]),"+f"(d[67]),"+f"(d[68]),"+f"(d[69]),"+f"(d[70]),"+f"(d[71]),"+f"(d[72]),"+f"(d[73]),"+f"(d[74]),"+f"(d[75]),"+f"(d[76]),"+f"(d[77]),"+f"(d[78]),"+f"(d[79])
    : "l"(da), "l"(db), "r"(sd));
}
__device__ __forceinline__ void wg_ss80t(float (&d)[40], uint64_t da, uint64_t db, int sd) {
  asm volatile("{\n.reg .pred p;\nsetp.ne.b32 p, %42, 0;\n"
    "wgmma.mma_async.sync.aligned.m64n80k16.f32.bf16.bf16 {%0,%1,%2,%3,%4,%5,%6,%7,%8,%9,%10,%11,%12,%13,%14,%15,%16,%17,%18,%19,%20,%21,%22,%23,%24,%25,%26,%27,%28,%29,%30,%31,%32,%33,%34,%35,%36,%37,%38,%39}, %40, %41, p, 1, 1, 0, 1;\n}\n"
    : "+f"(d[0]),"+f"(d[1]),"+f"(d[2]),"+f"(d[3]),"+f"(d[4]),"+f"(d[5]),"+f"(d[6]),"+f"(d[7]),"+f"(d[8]),"+f"(d[9]),"+f"(d[10]),"+f"(d[11]),"+f"(d[12]),"+f"(d[13]),"+f"(d[14]),"+f"(d[15]),"+f"(d[16]),"+f"(d[17]),"+f"(d[18]),"+f"(d[19]),"+f"(d[20]),"+f"(d[21]),"+f"(d[22]),"+f"(d[23]),"+f"(d[24]),"+f"(d[25]),"+f"(d[26]),"+f"(d[27]),"+f"(d[28]),"+f"(d[29]),"+f"(d[30]),"+f"(d[31]),"+f"(d[32]),"+f"(d[33]),"+f"(d[34]),"+f"(d[35]),"+f"(d[36]),"+f"(d[37]),"+f"(d[38]),"+f"(d[39])
    : "l"(da), "l"(db), "r"(sd));
}

struct MapPair { CUtensorMap m[2]; };
struct Params {
  const __nv_bfloat16 *x, *wr, *wg, *wu, *wd, *k, *v;
  Scratch* s;
};

__device__ __forceinline__ void side_cta(const Params& p, int sc, unsigned epoch, float* sm) {
  const int tid = threadIdx.x, lane = tid & 31, warp = tid >> 5;
  int budget = WAIT_BUDGET;
  float* s_x = sm;
  float* s_red = sm + 1280;
  float* s_h = s_red + 6144;
  uint4* s_c = (uint4*)(s_h + 768);
  uint2* s_st = (uint2*)(s_c + 16);
  constexpr int DEPTH = 7, STEP = 4 * 6144;
  const uint32_t ring = smem_u32(s_st + 512) + tid * 16;
  const int cg = tid % 96, ks = tid / 96, cd = tid % 80, kd = tid / 80;
  const __nv_bfloat16* wp = (cg < 48 ? p.wg : p.wu) + (size_t)(ks * 160) * FF + sc * 384 + (cg % 48) * 8;
  int kf = 0, pitch = FF;
  uint32_t slot = ring;
  auto refill = [&]() {
    if (kf == 40) { wp = p.wd + (size_t)(sc * 384 + kd * 96) * DM + cd * 8; pitch = DM; }
    if (kf < (tid < 320 ? 64 : 40)) {
#pragma unroll
      for (int j = 0; j < 4; j++) asm volatile("cp.async.cg.shared.global.L2::cache_hint [%0], [%1], 16, %2;" ::"r"(slot + j * 6144), "l"(wp + j * pitch), "l"(POL_FIRST) : "memory");
    }
    asm volatile("cp.async.commit_group;" ::: "memory");
    wp += 4 * pitch; kf++;
    slot += STEP; if (slot == ring + DEPTH * STEP) slot = ring;
  };
  auto gemv = [&](int n, const float* x0, const float* x1, float* out) {
    float a[2][8] = {};
#pragma unroll 1
    for (int k = 0; k < n; k += 4) {
      refill();
      asm volatile("cp.async.wait_group %0;" ::"n"(DEPTH - 1) : "memory");
      const float4 f0 = *(const float4*)(x0 + k), f1 = *(const float4*)(x1 + k);
      const float y0[4] = {f0.x, f0.y, f0.z, f0.w}, y1[4] = {f1.x, f1.y, f1.z, f1.w};
#pragma unroll
      for (int j = 0; j < 4; j++) {
        const uint4 v = lds128(slot + j * 6144);
        const uint32_t u[4] = {v.x, v.y, v.z, v.w};
#pragma unroll
        for (int i = 0; i < 4; i++) {
          a[0][2 * i] += y0[j] * bf_lo(u[i]); a[0][2 * i + 1] += y0[j] * bf_hi(u[i]);
          a[1][2 * i] += y1[j] * bf_lo(u[i]); a[1][2 * i + 1] += y1[j] * bf_hi(u[i]);
        }
      }
    }
#pragma unroll
    for (int i = 0; i < 16; i++) out[(i >> 3) * 768 + (i & 7)] = a[i >> 3][i & 7];
  };
  auto load_row = [&](const __nv_bfloat16* r, uint32_t (&v)[10]) {
    const uint4 a = __ldg((const uint4*)r + lane), b = __ldg((const uint4*)r + 32 + lane);
    const uint2 c = __ldg((const uint2*)r + 128 + lane);
    v[0] = a.x; v[1] = a.y; v[2] = a.z; v[3] = a.w; v[4] = b.x; v[5] = b.y; v[6] = b.z; v[7] = b.w; v[8] = c.x; v[9] = c.y;
  };
  uint32_t wr[10], xb[3][10];
  load_row(p.wr, wr);
#pragma unroll 1
  for (int i = tid; i < 512; i += 384) {
    uint4 v;
    do v = ld_pkt(p.s->stat + sc * 512 + i); while (v.w != epoch + 1 && --budget >= 0);
    s_st[i] = make_uint2(v.x, v.y);
  }
  __syncthreads();
#pragma unroll
  for (int b = 0; b < 3; b++) load_row(p.x + (size_t)(sc * 512 + warp + 12 * b) * DM, xb[b]);
#pragma unroll 1
  for (int k = 0; k < DEPTH - 1; k++) refill();
  float v0 = -INFINITY, v1 = -INFINITY; int i0 = 0xfff, i1 = 0xfff;
  auto better = [](float a, int ia, float b, int ib) { return a > b || (a == b && ia < ib); };
  auto push = [&](float v, int i) {
    if (better(v, i, v0, i0)) { v1 = v0; i1 = i0; v0 = v; i0 = i; }
    else if (better(v, i, v1, i1)) { v1 = v; i1 = i; }
  };
  auto push2 = [&](uint4 c) { push(__uint_as_float(c.x), c.y & 0xfff); push(__uint_as_float(c.z), c.w & 0xfff); };
#pragma unroll 1
  for (int l3 = warp; l3 < 512; l3 += 36) {
#pragma unroll
    for (int b = 0; b < 3; b++) {
      const int lr = l3 + 12 * b;
      if (lr >= 512) break;
      const uint2 st = s_st[lr];
      uint32_t v[10];
#pragma unroll
      for (int i = 0; i < 10; i++) v[i] = hsub2(xb[b][i], st.x);
      if (lr + 36 < 512) load_row(p.x + (size_t)(sc * 512 + lr + 36) * DM, xb[b]);
      float r0 = 0.f, r1 = 0.f;
#pragma unroll
      for (int i = 0; i < 10; i++) {
        const uint32_t xn = pack_bf16(bf_lo(v[i]) * __uint_as_float(st.y), bf_hi(v[i]) * __uint_as_float(st.y));
        r0 = fmaf(bf_lo(xn), bf_lo(wr[i]), r0); r1 = fmaf(bf_hi(xn), bf_hi(wr[i]), r1);
      }
      r0 += r1;
#pragma unroll
      for (int o = 16; o > 0; o >>= 1) r0 += __shfl_xor_sync(~0u, r0, o);
      push(rbf(r0), sc * 512 + lr);
    }
  }
  if (lane == 0) s_c[warp] = make_uint4(__float_as_uint(v0), i0, __float_as_uint(v1), i1);
  __syncthreads();
#pragma unroll 1
  for (int w = 1; w < 12; w++) push2(s_c[(warp + w) % 12]);
  const uint32_t tag = (epoch + 1) << 12;
  if (tid == 0) st_pkt(p.s->cand + sc, __float_as_uint(v0), i0 | tag, __float_as_uint(v1), i1);
  {
    uint4 c;
    do c = ld_pkt(p.s->cand + (lane & 3)); while (((c.y ^ tag) >> 12) && --budget >= 0);
#pragma unroll 1
    for (int w = 1; w < 4; w++) { const int o = (sc + w) & 3; push2(make_uint4(__shfl_sync(~0u, c.x, o), __shfl_sync(~0u, c.y, o), __shfl_sync(~0u, c.z, o), __shfl_sync(~0u, c.w, o))); }
  }
  if (i0 >= SQ) i0 = 0;
  if (i1 >= SQ) i1 = (i0 == 0) ? 1 : 0;
  if (tid < 320) {
    const int row = tid < 160 ? i0 : i1;
    const uint2 u = __ldg((const uint2*)(p.x + (size_t)row * DM) + tid % 160);
    uint4 st;
    do st = ld_pkt(p.s->stat + row); while (st.w != epoch + 1 && --budget >= 0);
    const uint32_t d0 = hsub2(u.x, st.x), d1 = hsub2(u.y, st.x);
    const float inv = __uint_as_float(st.y);
    ((float4*)s_x)[tid] = make_float4(rbf(bf_lo(d0) * inv), rbf(bf_hi(d0) * inv), rbf(bf_lo(d1) * inv), rbf(bf_hi(d1) * inv));
  }
  __syncthreads();
  gemv(160, s_x + ks * 160, s_x + DM + ks * 160, s_red + ks * 1536 + cg * 8);
  __syncthreads();
#pragma unroll
  for (int t = 0; t < 2; t++) {
    float g = 0.f, u = 0.f;
#pragma unroll
    for (int k = 0; k < 4; k++) { g += s_red[(k * 2 + t) * 768 + tid]; u += s_red[(k * 2 + t) * 768 + 384 + tid]; }
    s_h[t * 384 + tid] = rbf(rbf(silu_f(rbf(g))) * rbf(u));
  }
  __syncthreads();
  if (tid < 320) gemv(96, s_h + kd * 96, s_h + 384 + kd * 96, s_red + kd * 1536 + cd * 8);
  __syncthreads();
  const int o4 = tid + (tid < 160 ? 0 : 32);
  if (tid < 320) {
    const float4 *r = (const float4*)s_red + o4, a = r[0], b = r[384], c = r[768], d = r[1152];
    ((float4*)p.s->ffn)[sc * 320 + tid] = make_float4(a.x + b.x + c.x + d.x, a.y + b.y + c.y + d.y, a.z + b.z + c.z + d.z, a.w + b.w + c.w + d.w);
  }
  __syncthreads();
  if (tid == 0) { __threadfence(); s_c[0].x = (atomicAdd(&p.s->flag[FL_SIDE], 1u) & 3u) == 3u; __threadfence(); }
  __syncthreads();
  if (s_c[0].x) {
    if (tid < 320) {
      const float4 *r = (const float4*)p.s->ffn + tid, a = __ldcg(r), b = __ldcg(r + 320), c = __ldcg(r + 640), d = __ldcg(r + 960), x = ((float4*)s_x)[tid];
      const float rs = rbf(sigmoid_f(tid < 160 ? v0 : v1));
      auto gate = [&](float xn, float y) { return silu_f(rbf(xn + rbf(rbf(y) * rs))); };
      if (tid == 0) { p.s->sel[0] = i0; p.s->sel[1] = i1; }
      ((uint2*)p.s->gsel)[tid] =
          make_uint2(pack_bf16(gate(x.x, a.x + b.x + c.x + d.x), gate(x.y, a.y + b.y + c.y + d.y)), pack_bf16(gate(x.z, a.z + b.z + c.z + d.z), gate(x.w, a.w + b.w + c.w + d.w)));
    }
    __syncthreads();
    if (tid == 0) red_release(&p.s->flag[FL_FFN]);
  }
}

constexpr float SM_C = 0.07216878364870322f * 1.4426950408889634f;

__device__ __forceinline__ void ln_row(const Params& p, uint32_t (&uu)[20], int row, int l16, uint32_t tag) {
  const float x0 = bf_lo(__shfl_sync(~0u, uu[0], 0, 16));
  float s0 = 0.f, s1 = 0.f, q0 = 0.f, q1 = 0.f;
#pragma unroll
  for (int i = 0; i < 20; i++) {
    const float a = bf_lo(uu[i]) - x0, b = bf_hi(uu[i]) - x0;
    s0 += a; s1 += b; q0 = fmaf(a, a, q0); q1 = fmaf(b, b, q1);
  }
  s0 += s1; q0 += q1;
#pragma unroll
  for (int o = 8; o > 0; o >>= 1) { s0 += __shfl_xor_sync(~0u, s0, o); q0 += __shfl_xor_sync(~0u, q0, o); }
  s0 *= 1.f / DM;
  const float mean = x0 + s0, var = rbf(fmaxf(fmaf(q0, 1.f / DM, -s0 * s0), 0.f));
  float sd; asm("sqrt.approx.ftz.f32 %0, %1;" : "=f"(sd) : "f"(rbf(var + 1e-5f)));
  const float inv = rcp(rbf(sd)), invc = inv * SM_C;
  const __nv_bfloat162 mb = __float2bfloat162_rn(mean);
  const uint32_t mean2 = *reinterpret_cast<const uint32_t*>(&mb);
  if (l16 == 0) st_pkt(&p.s->stat[row], mean2, __float_as_uint(inv), 0, tag);
#pragma unroll
  for (int i = 0; i < 20; i++) { const uint32_t d = hsub2(uu[i], mean2); uu[i] = pack_bf16(bf_lo(d) * invc, bf_hi(d) * invc); }
#pragma unroll
  for (int i = 0; i < 5; i++) *((uint4*)(p.s->xn + (size_t)row * DM) + i * 16 + l16) = make_uint4(uu[4 * i], uu[4 * i + 1], uu[4 * i + 2], uu[4 * i + 3]);
}

constexpr float SM_HI = 0x1p64f, SM_LO = 0x1p-64f;
__device__ __forceinline__ void exp_block(float (&s)[32], float& l0, float& l1, int from = 0, int to = 32) {
#pragma unroll
  for (int i = from; i < to; i++) { s[i] = ex2(s[i]); if (i & 2) l1 += s[i]; else l0 += s[i]; }
}
__device__ __forceinline__ float quad_sum(float v) { v += __shfl_xor_sync(~0u, v, 1); return v + __shfl_xor_sync(~0u, v, 2); }
__device__ __forceinline__ float quad_max(float v) { v = fmaxf(v, __shfl_xor_sync(~0u, v, 1)); return fmaxf(v, __shfl_xor_sync(~0u, v, 2)); }
__device__ __noinline__ void safe_head(const uint32_t* kp, const uint32_t* vp, uint4* io) {
  uint32_t fq[48];
#pragma unroll
  for (int i = 0; i < 12; i++) { const uint4 v = io[(i >> 1) * 512 + (i & 1) * 32]; fq[4 * i] = v.x; fq[4 * i + 1] = v.y; fq[4 * i + 2] = v.z; fq[4 * i + 3] = v.w; }
  float m0 = -INFINITY, m1 = -INFINITY;
#pragma unroll 1
  for (int pass = 0; pass < 3; pass++) {
    float o[48] = {}, l0 = 0.f, l1 = 0.f;
#pragma unroll 1
    for (int n = 0; n < 64; n++) {
      const uint32_t *kr = kp + n * (8 * DH / 2), *vr = vp + n * (8 * DH / 2) + (pass - 1) * 48;
      float d[4] = {};
#pragma unroll
      for (int t = 0; t < 12; t++)
        asm volatile("mma.sync.aligned.m16n8k16.row.col.f32.bf16.bf16.f32 {%0,%1,%2,%3}, {%4,%5,%6,%7}, {%8,%9}, {%0,%1,%2,%3};"
                     : "+f"(d[0]), "+f"(d[1]), "+f"(d[2]), "+f"(d[3])
                     : "r"(fq[4 * t]), "r"(fq[4 * t + 1]), "r"(fq[4 * t + 2]), "r"(fq[4 * t + 3]), "r"(__ldg(kr + 8 * t)), "r"(__ldg(kr + 8 * t + 4)));
      if (pass == 0) { m0 = fmaxf(m0, fmaxf(d[0], d[1])); m1 = fmaxf(m1, fmaxf(d[2], d[3])); continue; }
      d[0] = ex2(d[0] - m0); d[1] = ex2(d[1] - m0); d[2] = ex2(d[2] - m1); d[3] = ex2(d[3] - m1);
      l0 += d[0] + d[1]; l1 += d[2] + d[3];
      const uint32_t p0 = pack_bf16(d[0], d[1]), p1 = pack_bf16(d[2], d[3]);
#pragma unroll
      for (int c = 0; c < 12; c++)
        asm volatile("{\n.reg .b32 t;\nmovmatrix.sync.aligned.m8n8.trans.b16 t, %6;\n"
                     "mma.sync.aligned.m16n8k8.row.col.f32.bf16.bf16.f32 {%0,%1,%2,%3}, {%4,%5}, {t}, {%0,%1,%2,%3};\n}\n"
                     : "+f"(o[4 * c]), "+f"(o[4 * c + 1]), "+f"(o[4 * c + 2]), "+f"(o[4 * c + 3]) : "r"(p0), "r"(p1), "r"(__ldg(vr + 4 * c)));
    }
    if (pass == 0) { m0 = quad_max(m0); m1 = quad_max(m1); continue; }
    l0 = rcp(quad_sum(l0)); l1 = rcp(quad_sum(l1));
#pragma unroll
    for (int i = 0; i < 6; i++) {
      const float* v = o + 16 * (i >> 1) + 2 * (i & 1);
      const float r = i & 1 ? l1 : l0;
      io[(3 * (pass - 1) + (i >> 1)) * 512 + (i & 1) * 32] =
          make_uint4(pack_bf16(v[0] * r, v[1] * r), pack_bf16(v[4] * r, v[5] * r), pack_bf16(v[8] * r, v[9] * r), pack_bf16(v[12] * r, v[13] * r));
    }
  }
}

#define CVG 48
#define NE 8
#define PS1 8
#define LQ 6
__device__ __forceinline__ constexpr int end_stage(int n) { return n < 4 ? n : n < LQ ? n - 4 : n == LQ ? 4 : n % 5; }
#define Q2N 1
#define SWN 12
#define SCH 0
__device__ __forceinline__ constexpr int sent(int n) {
  constexpr int t[4][15] = {{0, 2, 4, 5, 5, 6, 7, 8,  9, 10, 11, 12, 13, 14, 15},
                            {0, 2, 4, 5, 5, 6, 7, 8,  9, 10, 12, 13, 14, 15, 15},
                            {0, 2, 4, 5, 5, 7, 8, 9, 10, 10, 12, 14, 15, 15, 15},
                            {0, 2, 4, 5, 5, 7, 8, 9, 10, 10, 13, 15, 15, 15, 15}};
  return n < LQ + 2 ? 0 : LQ == 6 && n == 8 ? 3 : t[SCH][n - 6];
}
template <int N> struct IntC { static constexpr int value = N; };
template <int N, int I = 0, class F> __device__ __forceinline__ void static_for(F&& f) { if constexpr (I < N) { f(IntC<I>{}); static_for<N, I + 1>(f); } }

__global__ void __launch_bounds__(384, 1)
fused_kernel(const Params p, const __grid_constant__ CUtensorMap tm_x, const __grid_constant__ CUtensorMap tm_xn,
             const __grid_constant__ CUtensorMap tm_wq, const __grid_constant__ CUtensorMap tm_k,
             const __grid_constant__ CUtensorMap tm_v, const __grid_constant__ CUtensorMap tm_wo,
             const __grid_constant__ MapPair tm_w2,
             const __grid_constant__ CUtensorMap tm_xg, const __grid_constant__ CUtensorMap tm_xe,
             const __grid_constant__ CUtensorMap tm_out) {
  extern __shared__ __align__(1024) uint8_t smem_raw[];
  const uint32_t sb = smem_u32(smem_raw);
  const CUtensorMap* const tm_w = tm_w2.m;
  const uint32_t bar_a = sb + OFF_M, bar_b = bar_a + 80, bar_o = bar_b + 96;
  const uint32_t bar_x = bar_o + 8, bar_z = bar_o + 16, bar_s = bar_o + 24, bar_d = bar_o + 32, bar_w = bar_o + 40, bar_e = bar_o + 48,
                 bar_u = bar_o + 96;
  const uint32_t s_stat = bar_a + 512;
  const uint32_t s_sel = s_stat + 1024;
  const int wi = __shfl_sync(~0u, threadIdx.x >> 5, 0), wg = wi >> 2;
  const int lane = threadIdx.x & 31;
  const int cl = blockIdx.x >> 1;
  const int rank = blockIdx.x & 1;

  if (cl >= 64) {
    const unsigned epoch = (unsigned)(__ldcg(&p.s->done) >> 7);
    side_cta(p, blockIdx.x - 128, epoch, (float*)smem_raw);
    return;
  }
  const int qt = (cl >> 3) * 2 + rank, hg = cl & 7;
  const int kq = hg >> 1, nh = hg & 1;

  if (elect()) {
    if (wi < 2) asm volatile("prefetch.tensormap [%0];" ::"l"(wi ? &tm_wq : &tm_x) : "memory");
    const uint32_t c = (uint32_t)((wi < 5 ? 0x7777700000ull : wi < 10 ? 0x752107ffffff0ull : 0ull) >> (12 * (wi % 5)));
    for (int i = 0; i < 3; i++) mbar_init(bar_a + 24 * wi + 8 * i, ((c >> (4 * i)) & 15) + 1);
  }
  asm volatile("fence.mbarrier_init.release.cluster;" ::: "memory");
  cluster_arrive();
  uint32_t xw[20];
  unsigned long long done = 0;
  const int lnrow = qt * 128 + hg * 16 + ((int)(threadIdx.x >> 5) - 4) * 2 + (lane >> 4);
  uint32_t cons; asm volatile("{\n.reg .pred q;\nsetp.ne.u32 q, %1, 0;\nselp.u32 %0, 1, 0, q;\n}" : "=r"(cons) : "r"(wg));
  if (cons) {
#pragma unroll
    for (int i = 0; i < 5; i++) {
      const uint4 v = ldg_nc((const uint4*)(p.x + (size_t)lnrow * DM) + i * 16 + (lane & 15));
      xw[4 * i] = v.x; xw[4 * i + 1] = v.y; xw[4 * i + 2] = v.z; xw[4 * i + 3] = v.w;
    }
    asm volatile("ld.relaxed.gpu.global.u64 %0, [%1];" : "=l"(done) : "l"(&p.s->done));
  }
  if (wg > 0) {
    const int w = wg - 1;
    const int cw = wi - 4;
    asm volatile("setmaxnreg.inc.sync.aligned.u32 232;");
    {
      cluster_wait();
      ln_row(p, xw, lnrow, lane & 15, (unsigned)(done >> 7) + 1);
      __syncwarp();
      if (lane == 0) mbar_arrive(bar_o);
    }
    uint32_t rel_addr;
    asm volatile("mapa.shared::cluster.u32 %0, %1, %2;" : "=r"(rel_addr) : "r"(bar_b + 48), "r"(lane & 1));
    auto rel_a = [&](uint32_t o8) { if (lane == 0) mbar_arrive(bar_a + 40 + o8); };
    auto rel_b = [&](uint32_t o8) { if (lane < 2) mbar_arrive_cluster(rel_addr + o8); };
    uint32_t b8 = 0, phb = 0;
    auto next_pair = [&]() { b8 += 16; if (b8 == 48) { b8 = 0; phb ^= 1; } };
    const int g = lane >> 2, q = lane & 3;
    constexpr uint64_t HI_A = desc_hi(16, 1024, 1);
    constexpr uint64_t HI_W = desc_hi(1024, 3072, 1);
    constexpr uint64_t HI_O = desc_hi(2048, 512, 2);
    if (w == 1) asm volatile("bar.arrive 1, 256;" ::: "memory");

    uint32_t zero; asm volatile("mov.u32 %0, %%tid.y;" : "=r"(zero));
    float acc[96];
    uint32_t fr[48];
    uint4* optr = p.s->o + (size_t)(qt * 192 + hg * 24) * 512 + (cw * 16 + g) * 4 + (q ^ ((g >> 1) & 3));
    uint32_t rl[4];
    auto store_o = [&](int pp, bool on) {
#pragma unroll
      for (int i = (12 * pp + 8) / 9; i < (12 * (pp + 1) + 8) / 9; i++) {
#pragma unroll
        for (int k = 4 * i; k < 4 * i + 4; k++)
          asm volatile("{\n.reg .b32 t;\nmul.rn.bf16x2 t, %0, %2;\nfma.rn.bf16x2 %0, %0, %1, t;\n}\n" : "+r"(fr[k]) : "r"(rl[i & 1]), "r"(rl[2 + (i & 1)]));
        fr[4 * i] &= ~1u;
        if (on) optr[(i >> 1) * 512 + (i & 1) * 32] = make_uint4(fr[4 * i], fr[4 * i + 1], fr[4 * i + 2], fr[4 * i + 3]);
      }
      if (pp == 8 && on) { __syncwarp(); if (lane == 0) mbar_arrive(bar_o); optr += 6 * 512; }
    };
    auto fresh = [&]() { uint32_t v = sb; asm volatile("" : "+r"(v)); return v; };
    reg_fence(fr); reg_fence(rl);

#pragma unroll 1
    for (int u = 0; u < 4; u++) {
      const uint32_t sq = fresh();
      const uint64_t dA = mkdesc(sq + w * 8192, HI_A), dB0 = mkdesc(sq + OFF_B, HI_W);
      uint32_t pb8 = 0;
#pragma unroll
      for (int s = 0; s < 10; s++) {
        const uint32_t o8 = b8 + 8 * (s & 1);
        const uint64_t dW = dB0 + o8 * (TB >> 7);
        mbar_wait(bar_a + 8 * (s % 5), s / 5);
        mbar_wait(bar_b + o8, phb);
        if (s == 9) asm volatile("bar.sync %0, 256;" ::"r"(1 + w) : "memory");
        WG_FENCE();
#pragma unroll
        for (int kk = 0; kk < 4; kk++) wg_ss192t(acc, dA + ((s % 5) * (TA >> 4) + kk * 2), dW + kk * 384, kk != 0 || s != 0);
        WG_COMMIT();
        if (s == 9) asm volatile("bar.arrive %0, 256;" ::"r"(2 - w) : "memory");
        if (s < 9) store_o(s, u > 0);
        if (s > 0) { WG_WAIT(1); rel_a(8 * ((s - 1) % 5)); rel_b(pb8); }
        pb8 = o8;
        if (s & 1) next_pair();
      }
      WG_WAIT(0);
      reg_fence(acc);
      rel_b(pb8);
      if (u == 0) {
        mbar_wait(bar_s, 0);
        const uint2 s0 = lds64(s_stat + (cw * 16 + g) * 8), s1 = lds64(s_stat + 64 + (cw * 16 + g) * 8);
        const uint32_t msk = q == 0 ? 0xffffffffu : q == 1 ? 0xffffu : 0u;
        const float c0 = SM_C * __uint_as_float(s0.y), c1 = SM_C * __uint_as_float(s1.y);
        uint32_t am[4] = {(s0.x ^ 0x80008000u) & msk, (s1.x ^ 0x80008000u) & msk, 0, 0};
        reg_fence(am);
        WG_FENCE();
        wg_rs192t(acc, am[0], am[1], am[2], am[3], mkdesc(sb, desc_hi(1024, 0, 1)), 1);
        WG_COMMIT();
        WG_WAIT(0);
        reg_fence(acc);
#pragma unroll
        for (int i = 0; i < 24; i++) { acc[4 * i] *= c0; acc[4 * i + 1] *= c0; acc[4 * i + 2] *= c1; acc[4 * i + 3] *= c1; }
      }
      rel_a(32);
      auto pack_q = [&](int from, int to) {
#pragma unroll
        for (int i = from; i < to; i++) { fr[i] = pack_bf16(acc[2 * i], acc[2 * i + 1]); asm volatile("" : "+r"(fr[i])::"memory"); }
      };
      pack_q(0, CVG);
      float sc[32], l0 = 0.f, l1 = 0.f;
      uint32_t pf[16], k8;
      auto pack_p = [&](const float (&s_)[32], int from = 0, int to = 16) {
#pragma unroll
        for (int i = from; i < to; i++) pf[i] = pack_bf16(s_[2 * i], s_[2 * i + 1]);
      };
      auto scores = [&](int j, int pass = 11) {
        k8 = b8 + 8;
        mbar_wait(bar_b + k8, phb);
        next_pair();
        mbar_wait(bar_b + b8, phb);
        const uint64_t dk = mkdesc(sb + OFF_B, HI_W) + k8 * (TB >> 7);
        asm volatile("bar.sync %0, 256;" ::"r"(1 + w) : "memory");
        WG_FENCE();
#pragma unroll
        for (int t = 0; t < 12; t++) {
          wg_rs64(sc, fr[4 * t], fr[4 * t + 1], fr[4 * t + 2], fr[4 * t + 3], dk + (t >> 2) * 64 + (t & 3) * 2, t != 0);
          if (t == 11) WG_COMMIT();
          if (t == pass) asm volatile("bar.arrive %0, 256;" ::"r"(2 - w) : "memory");
        }
      };
      auto pv = [&](int add) {
        const uint64_t dv = mkdesc(sb + OFF_B, HI_W) + b8 * (TB >> 7);
#pragma unroll
        for (int kk = 0; kk < 4; kk++) wg_rs192t(acc, pf[4 * kk], pf[4 * kk + 1], pf[4 * kk + 2], pf[4 * kk + 3], dv + kk * 384, kk != 0 || add);
        WG_COMMIT();
      };
      auto finish = [&]() {
        WG_WAIT(1);
        reg_fence(sc);
        exp_block(sc, l0, l1);
        rel_b(k8 + (__float_as_uint(l0) & __float_as_uint(l1) & zero));
        WG_WAIT(0);
        reg_fence(acc); reg_fence(pf);
        rel_b(b8);
        pack_p(sc);
      };
      {
        mbar_wait(bar_b + b8, phb);
        const uint64_t dk = mkdesc(sb + OFF_B, HI_W) + b8 * (TB >> 7);
        asm volatile("bar.sync %0, 256;" ::"r"(1 + w) : "memory");
#pragma unroll
        for (int t = 0; t < 12; t++) {
          if (t && (4 * t) % CVG == 0) pack_q(4 * t, 4 * t + CVG);
          if ((4 * t) % CVG == 0) WG_FENCE();
          wg_rs64(sc, fr[4 * t], fr[4 * t + 1], fr[4 * t + 2], fr[4 * t + 3], dk + (t >> 2) * 64 + (t & 3) * 2, t != 0);
          if (t == 7) asm volatile("bar.arrive %0, 256;" ::"r"(2 - w) : "memory");
        }
        WG_COMMIT();
        WG_WAIT(0);
        reg_fence(sc);
        float s0[32];
#pragma unroll
        for (int i = 0; i < 32; i++) s0[i] = i < NE ? sc[i] : __uint_as_float(__float_as_uint(sc[i]) ^ zero);
        exp_block(s0, l0, l1, 0, NE);
        pack_p(s0, 0, NE / 2);
#pragma unroll
        for (int i = NE; i < 32; i++) asm volatile("" : "+f"(s0[i])::"memory");
#pragma unroll
        for (int i = 0; i < NE / 2; i++) asm volatile("" : "+r"(pf[i])::"memory");
        rel_b(b8);
        scores(1, PS1);
        const uint32_t z = lds32(s_stat) & zero;
#pragma unroll
        for (int i = NE; i < 32; i++) {
          asm("{\n.reg .pred p;\nsetp.eq.u32 p, %1, 0;\n@p ex2.approx.ftz.f32 %0, %0;\n}\n" : "+f"(s0[i]) : "r"(z));
          if (i & 2) l1 += s0[i]; else l0 += s0[i];
        }
        pack_p(s0, NE / 2, 16);
        reg_fence(pf);
        WG_FENCE();
        pv(0);
        finish();
      }
#pragma unroll 1
      for (int j = NE < 32 ? 2 : 1; j < 8; j++) { scores(j); pv(j > 1); finish(); }
      const uint32_t v8 = b8 + 8;
      mbar_wait(bar_b + v8, phb);
      next_pair();
      {
        const uint64_t dv = mkdesc(sb + OFF_B, HI_W) + v8 * (TB >> 7);
        asm volatile("bar.sync %0, 256;" ::"r"(1 + w) : "memory");
        WG_FENCE();
#pragma unroll
        for (int kk = 0; kk < 4; kk++) {
          wg_rs192t(acc, pf[4 * kk], pf[4 * kk + 1], pf[4 * kk + 2], pf[4 * kk + 3], dv + kk * 384, 1);
          if (kk == 1 && (u < 3 || w == 0)) asm volatile("bar.arrive %0, 256;" ::"r"(2 - w) : "memory");
        }
        WG_COMMIT();
      }
      l0 = quad_sum(l0); l1 = quad_sum(l1);
      const bool unsafe = __any_sync(~0u, !(l0 >= SM_LO && l1 >= SM_LO && l0 + l1 <= SM_HI));
      l0 = rcp(l0); l1 = rcp(l1);
      rl[0] = pack_bf16(l0, l0); rl[1] = pack_bf16(l1, l1);
      l0 -= bf_lo(rl[0]); l1 -= bf_lo(rl[1]);
      rl[2] = pack_bf16(l0, l0); rl[3] = pack_bf16(l1, l1);
      WG_WAIT(0);
      reg_fence(acc);
      rel_b(v8);
      if (__builtin_expect(unsafe, 0)) {
        int o = hg * 4 + u; asm volatile("" : "+r"(o));
        o = (o * SKC + (SKC - WIN) + g) * (DH / 2) + q;
#pragma unroll
        for (int i = 0; i < 12; i++) optr[(i >> 1) * 512 + (i & 1) * 32] = make_uint4(fr[4 * i], fr[4 * i + 1], fr[4 * i + 2], fr[4 * i + 3]);
        safe_head((const uint32_t*)p.k + o, (const uint32_t*)p.v + o, optr);
#pragma unroll
        for (int i = 0; i < 12; i++) { const uint4 v = optr[(i >> 1) * 512 + (i & 1) * 32]; fr[4 * i] = v.x; fr[4 * i + 1] = v.y; fr[4 * i + 2] = v.z; fr[4 * i + 3] = v.w; }
        rl[0] = rl[1] = 0x3f803f80u; rl[2] = rl[3] = 0;
      } else {
#pragma unroll
        for (int i = 0; i < 24; i++) {
          fr[8 * (i >> 2) + (i & 3)] = pack_bf16(acc[4 * i], acc[4 * i + 1]);
          fr[8 * (i >> 2) + 4 + (i & 3)] = pack_bf16(acc[4 * i + 2], acc[4 * i + 3]);
        }
      }
    }

    float aF[80], aS[80];
    uint32_t pha = 0, a8 = 0, pa8 = 0, pb8 = 0;
#pragma unroll 1
    for (int s = 0; s < 19; s++) {
      const uint64_t d0 = mkdesc(sb, HI_O), dO = d0 + (a8 * (TA >> 7) + w * 256), dB = d0 + ((OFF_B >> 4) + b8 * (TB >> 7));
      mbar_wait(bar_a + a8, pha);
      mbar_wait(bar_b + b8, phb);
      WG_FENCE();
#pragma unroll
      for (int kk = 0; kk < 4; kk++) wg_ss160t(aF, dO + ((kk >> 1) * 512 + (kk & 1) * 2), dB + ((kk >> 1) * 640 + (kk & 1) * 64), kk != 0 || s != 0);
      WG_COMMIT();
      mbar_wait(bar_b + b8 + 8, phb);
      WG_WAIT(1);
      if (s > 0) { rel_a(pa8); rel_b(pb8 + 8); }
      WG_FENCE();
#pragma unroll
      for (int kk = 0; kk < 4; kk++) wg_ss160t(aS, dO + ((kk >> 1) * 512 + (kk & 1) * 2), dB + ((TB >> 4) + (kk >> 1) * 640 + (kk & 1) * 64), kk != 0 || s != 0);
      WG_COMMIT();
      if (s < 9) {
#pragma unroll
        for (int pp = 0; pp < 9; pp++) if (s == pp) store_o(pp, true);
      } else if (s < 15) {
        const int b = 2 * cw + ((lane >> 3) & 1);
        uint32_t ga = sb + OFF_B + TW + ((b * 11) >> 5) * (TB - 3840) + b * 1280 + (lane & 7) * 160 + (lane >> 4) * 16;
        if (s < 14) {
          mbar_wait(bar_x, 0);
          ga += 32 * (s - 9);
          ldsm4(ga, fr);
#pragma unroll
          for (int i = 0; i < 4; i++) {
            const uint2 st = lds64(s_stat + (cw * 16 + g + 8 * (i & 1)) * 8);
            const uint32_t d = hsub2(fr[i], st.x), xn = pack_bf16(bf_lo(d) * __uint_as_float(st.y), bf_hi(d) * __uint_as_float(st.y));
            fr[i] = pack_bf16(silu_f(bf_lo(xn)), silu_f(bf_hi(xn)));
          }
          stsm4(ga, fr);
        } else {
          mbar_wait(bar_u, 0);
          const uint2 sel = lds64(s_sel);
          const uint32_t row = qt * 128 + cw * 16 + (lane & 15);
          if (row == sel.x || row == sel.y) ga = s_sel + 16 + (row == sel.y ? 160 : 0) + (lane >> 4) * 16;
#pragma unroll
          for (int k = 0; k < 5; k++) ldsm4(ga + 32 * k, fr + 4 * k);
        }
      }
      WG_WAIT(1);
      rel_b(b8);
      pa8 = a8; a8 += 8; if (a8 == 40) { a8 = 0; pha ^= 1; }
      pb8 = b8; next_pair();
    }
    const int t128 = threadIdx.x & 127;
    uint4* const xbase = p.s->o + (size_t)(qt * 192 + nh * 24 + 10) * 512 + w * 640 + t128;
    uint4* const dst = xbase + kq * (48 * 512);
    float q1[40], q2[40], oth[40], own[40];
    auto take = [&](float (&x)[40], const float* a) {
#pragma unroll
      for (int k = 0; k < 40; k++) x[k] = __uint_as_float(__float_as_uint(a[k]) ^ zero);
      reg_fence(x);
    };
    reg_fence(aF);
    take(q1, aF);
    auto fa = [&](int i) { return mbar_try(bar_a + 8 * ((4 + i) % 5), i == 0); };
    auto fb = [&](int e) { return mbar_try(bar_b + 8 * (e % 6), (e / 6) & 1); };
    auto send = [&](int m) {
      const float* v = (m < 5 ? q1 : m < 10 ? q2 : oth) + 8 * (m % 5);
      st_pkt(dst + (m / 5) * 1280 + (m % 5) * 128, pack_bf16(v[0], v[1]) | 1, pack_bf16(v[2], v[3]), pack_bf16(v[4], v[5]), pack_bf16(v[6], v[7]));
    };
    static_for<20>([&](auto n_) {
      constexpr int n = n_.value, i = end_stage(n), e = 142 + n / 2, qi = n == 4 ? 1 : n == LQ ? 0 : n / 5;
      float (&acc_)[40] = qi == 0 ? q1 : qi == 1 ? q2 : qi == 2 ? oth : own;
      if (n == 0) while (!(fa(0) & fa(1) & fb(142) & fb(143))) {}
      if (n == 2) while (!(fa(2) & fa(3) & fb(144))) {}
      if (n == LQ) while (!(fa(4) & fb(145) & fb(146) & mbar_try(bar_z, 0))) {}
      if (n == 10) while (!(fb(147) & fb(148) & fb(149))) {}
      const uint64_t d0 = mkdesc(fresh(), HI_O);
      WG_FENCE();
#pragma unroll
      for (int kk = 0; kk < 4; kk++)
        wg_ss80t(acc_, d0 + w * 256 + (((4 + i) % 5) * (TA >> 4) + (kk >> 1) * 512 + (kk & 1) * 2),
                 d0 + ((OFF_B >> 4) + (e % 6) * (TB >> 4) + (n & 1) * 768 + (kk >> 1) * 384 + (kk & 1) * 64), 1);
      WG_COMMIT();
      if ((!(n & 1) && n <= 16) || n == 15 || n == LQ + 1) WG_WAIT(1);
      if (n == 0) rel_a(24);
      if (!(n & 1) && n <= 10) rel_b(8 * ((e - 1) % 6));
      if (n == Q2N) take(q2, aF + 40);
      if (n == 10) cluster_arrive();
      if (n == 12 || n == 14 || n == 16) rel_a(4u * n - 48);
      if (n == LQ + 1) reg_fence(q1);
      if (n == 10) reg_fence(q2);
      if (n == 15) reg_fence(oth);
      if (n == 15) while (!(fb(150) & fb(151))) {}
      static_for<sent(n + 1) - sent(n)>([&](auto k_) { send(sent(n) + k_.value); });
      if (n == 8) {
        reg_fence(aS);
#pragma unroll
        for (int k = 0; k < 40; k++) oth[k] = kq & 1 ? aS[k] : aS[40 + k];
        reg_fence(oth);
      }
      if (n == SWN) {
        reg_fence(aS);
#pragma unroll
        for (int k = 0; k < 40; k++) own[k] = kq & 1 ? aS[40 + k] : aS[k];
        reg_fence(own);
      }
    });
    uint32_t xr[20];
    const uint32_t xs = sb + OFF_B + 2 * TB + cw * 2560, xa = xs + (lane & 15) * 160 + (lane >> 4) * 16;
    mbar_wait(bar_b + 16, 1);
#pragma unroll
    for (int k = 0; k < 5; k++) ldsm4(xa + 32 * k, xr + 4 * k);
    {
      auto fetch = [&](int e, uint4 (&v)[5]) {
        mbar_wait(bar_e + 16 * e + 8 * w, 0);
#pragma unroll
        for (int i = 0; i < 5; i++) v[i] = lds128(sb + OFF_B + (3 + e) * TB + (w * 640 + i * 128 + t128) * 16);
      };
      auto add = [&](int e, uint4 (&v)[5]) {
        while (!(v[0].x & v[1].x & v[2].x & v[3].x & v[4].x & 1)) {
#pragma unroll
          for (int i = 0; i < 5; i++) v[i] = ld_pkt(xbase + (kq ^ ((0x132 >> (4 * e)) & 3)) * (48 * 512) + (e < 2 ? kq & 1 : 2) * 1280 + i * 128);
        }
#pragma unroll
        for (int i = 0; i < 5; i++) {
          float* o = own + 8 * i;
          o[0] += bf_lo(v[i].x); o[1] += bf_hi(v[i].x); o[2] += bf_lo(v[i].y); o[3] += bf_hi(v[i].y);
          o[4] += bf_lo(v[i].z); o[5] += bf_hi(v[i].z); o[6] += bf_lo(v[i].w); o[7] += bf_hi(v[i].w);
        }
      };
      WG_WAIT(0);
      reg_fence(own);
#pragma unroll 1
      for (int e = 0; e < 3; e++) { uint4 v[5]; fetch(e, v); add(e, v); }
      if (lane == 0) mbar_arrive(bar_w);
#pragma unroll
      for (int i = 0; i < 20; i++) xr[i] = hadd2(xr[i], hmul2(pack_bf16(own[2 * i], own[2 * i + 1]), fr[i]));
#pragma unroll
      for (int k = 0; k < 5; k++) stsm4(xa + 32 * k, xr + 4 * k);
      asm volatile("fence.proxy.async.shared::cta;" ::: "memory");
      __syncwarp();
      if (elect()) {
        tma2d_store(&tm_out, xs, nh * 320 + kq * 80, qt * 128 + cw * 16);
        asm volatile("cp.async.bulk.commit_group;\ncp.async.bulk.wait_group.read 0;" ::: "memory");
      }
      __syncwarp();
    }
    cluster_wait();
  } else {
    asm volatile("setmaxnreg.dec.sync.aligned.u32 40;");
    uint32_t tid_; asm volatile("mov.u32 %0, %%tid.x;" : "=r"(tid_));
    const int warp = __shfl_sync(~0u, tid_ >> 5, 0);
    auto is_warp = [&](int k) { uint32_t e; asm volatile("{\n.reg .pred q;\nsetp.eq.u32 q, %1, %2;\nselp.u32 %0, 1, 0, q;\n}" : "=r"(e) : "r"(warp), "r"(k)); return e != 0; };
    auto k_block = [&](int t) {
      const int i = (t * 11) >> 5;
      return ((i < 6 ? 2 * kq + (i & 1) : hg ^ (i & 1)) * 4 + (i >> 1)) * 6 + (t == 3 * i ? 4 : 2 * (t - 3 * i) - 2);
    };
    if (warp > 0) {
      const unsigned epoch = (unsigned)(__ldcg(&p.s->done) >> 7);
      int budget = WAIT_BUDGET;
      cluster_wait();
      const uint32_t tag = epoch + 1;
      mbar_wait(bar_b, 0, budget); mbar_wait(bar_b + 8, 0, budget);
      float cs0 = 0.f, cs1 = 0.f;
      const int n = rank * 96 + (warp - 1) * 32 + (lane & 15) * 2;
#pragma unroll 1
      for (int kg = ((qt >> 1) & 3) * 2 + (lane >> 4) * 5, e = kg + 5; kg < e; kg++) {
        const uint32_t ad = sb + OFF_B + kg * 3072 + (n >> 6) * 1024 + (n & 63) * 2;
#pragma unroll
        for (int k = 0; k < 8; k++) { const uint32_t v = lds32(ad ^ (k * 0x90)); cs0 += bf_lo(v); cs1 += bf_hi(v); }
      }
      cs0 += __shfl_xor_sync(~0u, cs0, 16); cs1 += __shfl_xor_sync(~0u, cs1, 16);
      if (lane < 16) st_pkt(p.s->cs + (hg * 8 + (qt >> 1)) * 96 + (n >> 1), __float_as_uint(cs0), __float_as_uint(cs1), 0, tag);
      mbar_wait(bar_a + 40, 0, budget);
      if (lane < 2) { uint32_t a; asm volatile("mapa.shared::cluster.u32 %0, %1, %2;" : "=r"(a) : "r"(bar_d), "r"(lane)); mbar_arrive_cluster(a); }
      cs0 = cs1 = 0.f;
#pragma unroll 1
      for (int e = is_warp(3) ? 0 : 1; e < 3; e++) {
        const uint4* src = e ? p.s->cs + (hg * 8 + 4 * e - 4) * 96 + (tid_ - 32) : p.s->stat + qt * 128 + lane;
        const int step = e ? 96 : 32;
        uint4 v[4];
        while (true) {
          uint32_t bad = 0;
#pragma unroll
          for (int i = 0; i < 4; i++) v[i] = ld_pkt(src + i * step);
#pragma unroll
          for (int i = 0; i < 4; i++) bad |= v[i].w ^ tag;
          if (!__any_sync(~0u, bad) || --budget < 0) break;
        }
#pragma unroll
        for (int i = 0; i < 4; i++) {
          if (e) { cs0 += __uint_as_float(v[i].x); cs1 += __uint_as_float(v[i].y); }
          else { sts32(s_stat + (i * 32 + lane) * 8, v[i].x); sts32(s_stat + 4 + (i * 32 + lane) * 8, v[i].y); }
        }
      }
      mbar_wait(bar_a + 40, 1, budget);
#pragma unroll 1
      for (int k = 0; k < 8; k++) {
        const uint32_t v = pack_bf16(cs0, cs1);
        sts32((sb + ((tid_ - 32) >> 5) * 1024 + lane * 4) ^ (k * 0x90), k < 3 ? v : 0);
        cs0 -= bf_lo(v); cs1 -= bf_hi(v);
      }
      asm volatile("fence.proxy.async.shared::cta;" ::: "memory");
      __syncwarp();
      if (lane == 0) mbar_arrive(bar_s);
      if (is_warp(1)) {
#pragma unroll 1
        for (int u = 0; u < 5; u++) {
          mbar_wait(bar_o, u & 1);
          if (lane == 0) red_release(&p.s->flag[u ? FL_O + (qt * 8 + hg) * 8 : FL_XN + qt * 32]);
          __syncwarp();
        }
      } else if (is_warp(2)) {
        mbar_wait(bar_x, 0, budget);
        while ((int)(ld_acquire(&p.s->flag[FL_FFN]) - tag) < 0 && --budget >= 0) {}
        if (lane < 21) {
          const uint4 v = __ldcg(lane ? (const uint4*)(p.s->gsel + (lane > 10 ? DM - 80 : 0) + nh * 320 + kq * 80) + lane - 1 : (const uint4*)p.s->sel);
          asm volatile("st.shared.v4.u32 [%0], {%1,%2,%3,%4};" ::"r"(s_sel + 16 * lane), "r"(v.x), "r"(v.y), "r"(v.z), "r"(v.w) : "memory");
        }
        __syncwarp();
        if (lane == 0) { mbar_arrive(bar_u); asm volatile("red.relaxed.gpu.global.add.u64 [%0], 1;" ::"l"(&p.s->done) : "memory"); }
        while ((int)(ld_acquire(&p.s->flag[FL_RD + (qt * 8 + (hg ^ 1)) * 8]) - tag) < 0 && --budget >= 0) __nanosleep(200);
        if (lane == 0) mbar_arrive(bar_z);
        mbar_wait(bar_w, 0, budget);
        if (budget < 0) asm volatile("st.global.u32 [%0], %1;" ::"l"(0ull), "r"(budget) : "memory");
      } else {
        wait_flag(&p.s->flag[FL_XN + qt * 32], (epoch + 1) * 8);
        fence_proxy_async();
        mbar_wait(bar_a + 72, 1);
        uint32_t a8 = 0, pha = 1;
        const int kb = (qt * 192 + k_block(lane)) * 512;
#pragma unroll 1
        for (int n = 0; n < 54; n++) {
          const int t = n - 30, ko = __shfl_sync(~0u, kb, t);
          if (t == 0 || t == 18) {
            wait_flag(&p.s->flag[FL_O + (qt * 8 + (t ? 2 * kq + (lane & 1) : lane & 7)) * 8], epoch * 4 + (t ? 4 : 3));
            fence_proxy_async();
          }
          mbar_wait(bar_a + 40 + a8, pha);
          const uint32_t fb = bar_a + a8, dst = sb + a8 * (TA >> 3);
          if (elect()) {
            if (t >= 0) {
              mbar_expect_tx(fb, TA);
              bulk_load(dst, p.s->o + ko, TA, fb);
              if (t == 8) {
                mbar_expect_tx(bar_x, 6 * 3840);
#pragma unroll 1
                for (int e = 0; e < 6; e++) tma2d(sb + OFF_B + TW + e * TB, &tm_xg, nh * 320 + kq * 80, qt * 128 + e * 24, bar_x);
                asm volatile("prefetch.tensormap [%0];\nprefetch.tensormap [%1];\nprefetch.tensormap [%2];\nprefetch.tensormap [%3];"
                             ::"l"(tm_w), "l"(tm_w + 1), "l"(&tm_xe), "l"(&tm_out) : "memory");
              }
              if (t == 22) asm volatile("red.relaxed.gpu.global.add.u32 [%0], 1;" ::"l"(&p.s->flag[FL_RD + (qt * 8 + hg) * 8]) : "memory");
            } else if (n >= 10 && pha) mbar_arrive(fb);
            else { mbar_expect_tx(fb, TA); tma2d(dst, &tm_xn, 8 * a8 + (pha || (n >= 15 && n < 20) ? 0 : 320), qt * 128, fb); }
          }
          a8 += 8; if (a8 == 40) { a8 = 0; pha ^= 1; }
        }
        if (lane == 0) mbar_arrive(bar_z);
      }
    } else {
      cluster_wait();
      uint32_t fb = bar_b, dst = sb + OFF_B, ph = 1;
      auto next = [&]() { fb += 8; dst += TB; if (fb == bar_b + 48) { fb = bar_b; dst = sb + OFF_B; ph ^= 1; } };
#pragma unroll 1
      for (int u = 0; u < 4; u++) {
        const int h = hg * 4 + u;
        int s = u ? (u == 2 ? 5 : 0) : (5 * (qt >> 1)) >> 2;
#pragma unroll 1
        for (int i = 0; i < 10; i++) {
          if (u == 0) {
            const uint32_t a8 = 8 * (i < 5 ? i : i - 5);
            mbar_wait(bar_a + 40 + a8, i < 5);
            if (elect()) { mbar_expect_tx(bar_a + a8, TA); tma2d(sb + a8 * (TA >> 3), &tm_x, 64 * s, qt * 128, bar_a + a8); }
            if (i == 6) mbar_wait(bar_d, 0);
          }
          mbar_wait(fb + 48, ph);
          if (elect()) { mbar_expect_tx(fb, TB); tma4d_mc(dst + rank * (TB / 2), &tm_wq, 3 * h, 8 * s + 4 * rank, fb); }
          next();
          if (++s == 10) s = 0;
        }
        const int kv0 = (h * SKC + (SKC - WIN)) / 8 + 4 * rank;
#pragma unroll 1
        for (int i = 0; i < 16; i++) {
          const bool isk = (0x2AAB >> i) & 1;
          mbar_wait(fb + 48, ph);
          if (elect()) { mbar_expect_tx(fb, TB); tma4d_mc(dst + rank * (TB / 2), isk ? &tm_k : &tm_v, 0, kv0 + 8 * (isk ? (i + 1) >> 1 : (i - 1) >> 1), fb); }
          next();
        }
      }
      const int cF = 10 * nh + 5 - 5 * (kq >> 1), cS = 10 * nh + 5 * (kq >> 1);
      const int kb = 4 * (k_block(lane) + rank);
#pragma unroll 1
      for (int m = 0; m < 38; m++) {
        const int c2 = __shfl_sync(~0u, kb, m >> 1);
        mbar_wait(fb + 48, ph);
        if (elect()) { mbar_expect_tx(fb, TW); tma5d_mc(dst + rank * (TW / 2), &tm_wo, c2, m & 1 ? cS : cF, fb); }
        next();
      }
      const int odd = (((0x7ff0 ^ 1 << LQ) ^ (kq & 1 ? 0xffc00 : 0)) >> lane) & 1;
      const int tq = __shfl_sync(~0u, kb, 19 + end_stage(lane)) << 16 | odd << 7 | ((lane < 10 ? cF : cS) + 2 * odd);
#pragma unroll 1
      for (int n = 0; n < 20; n += 2) {
        const int t0 = __shfl_sync(~0u, tq, n), t1 = __shfl_sync(~0u, tq, n + 1);
        mbar_wait(fb + 48, ph);
        if (elect()) {
          mbar_expect_tx(fb, TB);
          tma5d_mc(dst + rank * (TB / 4), (const CUtensorMap*)((const char*)tm_w + (t0 & 128)), t0 >> 16, t0 & 31, fb);
          tma5d_mc(dst + TB / 2 + rank * (TB / 4), (const CUtensorMap*)((const char*)tm_w + (t1 & 128)), t1 >> 16, t1 & 31, fb);
        }
        next();
      }
      mbar_wait(fb + 48, ph);
      if (elect()) { mbar_expect_tx(fb, TW); tma2d(dst, &tm_xe, nh * 320 + kq * 80, qt * 128, fb); }
    }
    if (!is_warp(2)) {
      const int e = warp - (warp >> 1), ms = 2 * e + ((lane >> 2) & 1);
      const uint4* src = p.s->o + (size_t)(qt * 192 + nh * 24 + 10 + (kq ^ ((0x132 >> (4 * e)) & 3)) * 48) * 512 + (e < 2 ? kq & 1 : 2) * 1280 + (ms & 1) * 640;
      uint32_t todo = 0xff;
      bool ok = lane >= 8;
      mbar_wait(bar_z, 0);
#pragma unroll 1
      while (todo) {
        if (!ok) ok = ld_pkt(src + 4 * 128 + (lane & 3) * 32 + 31).x & 1;
        const uint32_t got = __ballot_sync(~0u, ok) & todo, go = __ballot_sync(~0u, ((got >> (lane & 28)) & 15) == 15);
        if (go) mbar_wait(bar_a + 40 + 8 * e, 0);
        if ((go & 0x11) >> lane & 1) {
          mbar_expect_tx(bar_e + 8 * ms, TW / 2); bulk_load(sb + OFF_B + (3 + e) * TB + (ms & 1) * (TW / 2), src, TW / 2, bar_e + 8 * ms);
        }
        todo &= ~go;
      }
    }
    cluster_sync();
  }
}

typedef CUresult (*EncodeFn)(CUtensorMap*, CUtensorMapDataType, cuuint32_t, void*, const cuuint64_t*, const cuuint64_t*,
                             const cuuint32_t*, const cuuint32_t*, CUtensorMapInterleave, CUtensorMapSwizzle,
                             CUtensorMapL2promotion, CUtensorMapFloatOOBfill);

void encode(EncodeFn fn, CUtensorMap* tm, void* base, int rank, const cuuint64_t* dims, const cuuint64_t* strides,
            const cuuint32_t* box, CUtensorMapSwizzle sw) {
  const cuuint32_t es[5] = {1, 1, 1, 1, 1};
  fn(tm, CU_TENSOR_MAP_DATA_TYPE_BFLOAT16, rank, base, dims, strides, box, es, CU_TENSOR_MAP_INTERLEAVE_NONE, sw,
     CU_TENSOR_MAP_L2_PROMOTION_L2_128B, CU_TENSOR_MAP_FLOAT_OOB_FILL_NONE);
}

}

extern "C" void kernel_launch(void* const* d_in, const int* in_sizes, int n_in, void* d_out, int out_size) {
  static EncodeFn fn = nullptr;
  static Scratch* scr = nullptr;
  if (!fn) {
    void* f = nullptr;
    cudaDriverEntryPointQueryResult st;
    cudaGetDriverEntryPoint("cuTensorMapEncodeTiled", &f, cudaEnableDefault, &st);
    fn = (EncodeFn)f;
    cudaGetSymbolAddress((void**)&scr, g_scratch);
    cudaFuncSetAttribute(fused_kernel, cudaFuncAttributeMaxDynamicSharedMemorySize, SMEM_BYTES);
  }
  CUtensorMap tm_x, tm_xn, tm_wq, tm_k, tm_v, tm_wo, tm_xg, tm_xe, tm_out;
  MapPair tm_w2;
  { const cuuint64_t d[2] = {DM, SQ}, s[1] = {DM * 2}; const cuuint32_t b[2] = {64, 128};
    encode(fn, &tm_x, d_in[0], 2, d, s, b, CU_TENSOR_MAP_SWIZZLE_128B);
    encode(fn, &tm_xn, scr->xn, 2, d, s, b, CU_TENSOR_MAP_SWIZZLE_128B); }
  { const cuuint64_t d[4] = {64, 8, QD / 64, DM / 8}, s[3] = {QD * 2, 128, 8 * QD * 2}; const cuuint32_t b[4] = {64, 8, 3, 4};
    encode(fn, &tm_wq, d_in[3], 4, d, s, b, CU_TENSOR_MAP_SWIZZLE_128B); }
  { const cuuint64_t d[4] = {64, 8, 3, NH * SKC / 8}, s[3] = {DH * 2, 128, 8 * DH * 2}; const cuuint32_t b[4] = {64, 8, 3, 4};
    encode(fn, &tm_k, d_in[1], 4, d, s, b, CU_TENSOR_MAP_SWIZZLE_128B);
    encode(fn, &tm_v, d_in[2], 4, d, s, b, CU_TENSOR_MAP_SWIZZLE_128B); }
  {
    const cuuint64_t d[5] = {32, 2, QD / 8, 4, DM / 32}, s[4] = {DM * 2, 8 * DM * 2, 2 * DM * 2, 64}; const cuuint32_t b[5] = {32, 2, 4, 4, 5};
    encode(fn, &tm_wo, d_in[4], 5, d, s, b, CU_TENSOR_MAP_SWIZZLE_64B);
    const cuuint32_t b3[5] = {32, 2, 4, 4, 3};
    encode(fn, &tm_w2.m[0], d_in[4], 5, d, s, b3, CU_TENSOR_MAP_SWIZZLE_64B);
    encode(fn, &tm_w2.m[1], (char*)d_in[4] + 32, 5, d, s, b3, CU_TENSOR_MAP_SWIZZLE_64B); }
  { const cuuint64_t d[2] = {DM, SQ}, s[1] = {DM * 2}; const cuuint32_t bg[2] = {80, 24}, bx[2] = {80, 128}, bo[2] = {80, 16};
    encode(fn, &tm_xg, d_in[0], 2, d, s, bg, CU_TENSOR_MAP_SWIZZLE_NONE);
    encode(fn, &tm_xe, d_in[0], 2, d, s, bx, CU_TENSOR_MAP_SWIZZLE_NONE);
    encode(fn, &tm_out, d_out, 2, d, s, bo, CU_TENSOR_MAP_SWIZZLE_NONE); }
  Params p;
  p.x = (const __nv_bfloat16*)d_in[0]; p.wr = (const __nv_bfloat16*)d_in[6]; p.wg = (const __nv_bfloat16*)d_in[7];
  p.wu = (const __nv_bfloat16*)d_in[8]; p.wd = (const __nv_bfloat16*)d_in[9];

  p.k = (const __nv_bfloat16*)d_in[1]; p.v = (const __nv_bfloat16*)d_in[2]; p.s = scr;
  cudaLaunchConfig_t cfg = {};
  cfg.gridDim = dim3(132); cfg.blockDim = dim3(384); cfg.dynamicSmemBytes = SMEM_BYTES; cfg.stream = cudaStreamPerThread;
  cudaLaunchAttribute at[1];
  at[0].id = cudaLaunchAttributeClusterDimension; at[0].val.clusterDim.x = 2; at[0].val.clusterDim.y = 1; at[0].val.clusterDim.z = 1;
  cfg.attrs = at; cfg.numAttrs = 1;
  cudaLaunchKernelEx(&cfg, fused_kernel, p, tm_x, tm_xn, tm_wq, tm_k, tm_v, tm_wo, tm_w2, tm_xg, tm_xe, tm_out);
}
```

```cpp
#include <cuda_runtime.h>
#include <cuda_bf16.h>
#include <cuda.h>
#include <stdint.h>

namespace {

constexpr int SQ = 2048, DM = 640, NH = 32, DH = 192, SKC = 2048, WIN = 512, FF = 1536;
constexpr int QD = NH * DH;
constexpr uint32_t TA = 16384, TB = 24576, TW = 20480, OFF_B = 5 * TA, OFF_M = OFF_B + 6 * TB, SMEM_BYTES = OFF_M + 3072;
constexpr int WAIT_BUDGET = 1 << 20;

constexpr int FL_XN = 0;
constexpr int FL_O = 512;
constexpr int FL_RD = FL_O + 1024;
constexpr int FL_FFN = FL_RD + 1024;
constexpr int FL_SIDE = FL_FFN + 32;
struct __align__(1024) Scratch {
  unsigned long long done, pad0[15];
  unsigned flag[FL_SIDE + 32];
  uint4 cand[8];
  float ffn[4 * 2 * DM];
  int sel[4];
  __nv_bfloat16 gsel[2 * DM];
  uint4 cs[8 * 4 * DH / 2];
  uint4 stat[SQ];
  __align__(1024) __nv_bfloat16 xn[SQ * DM];
  __align__(1024) uint4 o[SQ * QD / 8];
};
__device__ Scratch g_scratch;

__device__ __forceinline__ uint32_t smem_u32(const void* p) { return (uint32_t)__cvta_generic_to_shared(p); }
__device__ __forceinline__ void mbar_init(uint32_t bar, int cnt) { asm volatile("mbarrier.init.shared::cta.b64 [%0], %1;" ::"r"(bar), "r"(cnt)); }
__device__ __forceinline__ void mbar_expect_tx(uint32_t bar, uint32_t bytes) {
  asm volatile("mbarrier.arrive.expect_tx.shared::cta.b64 _, [%0], %1;" ::"r"(bar), "r"(bytes) : "memory");
}
__device__ __forceinline__ void mbar_arrive(uint32_t bar) { asm volatile("mbarrier.arrive.shared::cta.b64 _, [%0];" ::"r"(bar) : "memory"); }
__device__ __forceinline__ void mbar_arrive_cluster(uint32_t addr) { asm volatile("mbarrier.arrive.shared::cluster.b64 _, [%0];" ::"r"(addr) : "memory"); }
__device__ __forceinline__ bool mbar_try(uint32_t bar, uint32_t parity) {
  uint32_t ok;
  asm volatile("{\n.reg .pred p;\nmbarrier.try_wait.parity.shared::cta.b64 p, [%1], %2;\nselp.u32 %0, 1, 0, p;\n}\n" : "=r"(ok) : "r"(bar), "r"(parity) : "memory");
  return ok;
}
__device__ __forceinline__ void mbar_wait(uint32_t bar, uint32_t parity, int& budget) {
#pragma unroll 1
  while (!mbar_try(bar, parity)) { if (--budget < 0) break; }
}
__device__ __forceinline__ void mbar_wait(uint32_t bar, uint32_t parity) {
#pragma unroll 1
  while (!mbar_try(bar, parity)) {}
}
__device__ __forceinline__ unsigned ld_acquire(const unsigned* p) { unsigned v; asm volatile("ld.acquire.gpu.global.u32 %0, [%1];" : "=r"(v) : "l"(p) : "memory"); return v; }
__device__ __forceinline__ void wait_flag(const unsigned* p, unsigned target) {
#pragma unroll 1
  while (__any_sync(~0u, (int)(ld_acquire(p) - target) < 0)) {}
}
__device__ __forceinline__ void red_release(unsigned* p) { asm volatile("red.release.gpu.global.add.u32 [%0], 1;" ::"l"(p) : "memory"); }
__device__ __forceinline__ void fence_proxy_async() { asm volatile("fence.proxy.async.global;" ::: "memory"); }
__device__ __forceinline__ bool elect() {
  uint32_t p;
  asm volatile("{\n.reg .pred P;\nelect.sync _|P, 0xffffffff;\nselp.u32 %0, 1, 0, P;\n}\n" : "=r"(p));
  return p;
}
__device__ __forceinline__ void cluster_arrive() { asm volatile("barrier.cluster.arrive.relaxed.aligned;" ::: "memory"); }
__device__ __forceinline__ void cluster_wait() { asm volatile("barrier.cluster.wait.aligned;" ::: "memory"); }
__device__ __forceinline__ void cluster_sync() { cluster_arrive(); cluster_wait(); }
__device__ __forceinline__ void tma2d(uint32_t dst, const CUtensorMap* tm, int c0, int c1, uint32_t bar) {
  asm volatile("cp.async.bulk.tensor.2d.shared::cluster.global.mbarrier::complete_tx::bytes [%0], [%1, {%3, %4}], [%2];"
               ::"r"(dst), "l"(tm), "r"(bar), "r"(c0), "r"(c1) : "memory");
}
constexpr uint64_t POL_FIRST = 0x12F0000000000000ull;
__device__ __forceinline__ void tma4d_mc(uint32_t dst, const CUtensorMap* tm, int c2, int c3, uint32_t bar) {
  asm volatile("cp.async.bulk.tensor.4d.shared::cluster.global.mbarrier::complete_tx::bytes.multicast::cluster.L2::cache_hint [%0], [%1, {%3, %3, %4, %5}], [%2], %6, %7;"
               ::"r"(dst), "l"(tm), "r"(bar), "r"(0), "r"(c2), "r"(c3), "h"((uint16_t)3), "l"(POL_FIRST) : "memory");
}
__device__ __forceinline__ void tma5d_mc(uint32_t dst, const CUtensorMap* tm, int c2, int c4, uint32_t bar) {
  asm volatile("cp.async.bulk.tensor.5d.shared::cluster.global.mbarrier::complete_tx::bytes.multicast::cluster.L2::cache_hint [%0], [%1, {%3, %3, %4, %3, %5}], [%2], %6, %7;"
               ::"r"(dst), "l"(tm), "r"(bar), "r"(0), "r"(c2), "r"(c4), "h"((uint16_t)3), "l"(POL_FIRST) : "memory");
}
__device__ __forceinline__ void bulk_load(uint32_t dst, const void* src, uint32_t bytes, uint32_t bar) {
  asm volatile("cp.async.bulk.shared::cluster.global.mbarrier::complete_tx::bytes.L2::cache_hint [%0], [%1], %2, [%3], %4;" ::"r"(dst), "l"(src), "r"(bytes), "r"(bar), "l"(POL_FIRST) : "memory");
}
__device__ __forceinline__ void tma2d_store(const CUtensorMap* tm, uint32_t src, int c0, int c1) {
  asm volatile("cp.async.bulk.tensor.2d.global.shared::cta.bulk_group [%0, {%2, %3}], [%1];" ::"l"(tm), "r"(src), "r"(c0), "r"(c1) : "memory");
}
__device__ __forceinline__ uint32_t lds32(uint32_t a) { uint32_t v; asm volatile("ld.shared.u32 %0, [%1];" : "=r"(v) : "r"(a) : "memory"); return v; }
__device__ __forceinline__ uint2 lds64(uint32_t a) { uint2 v; asm volatile("ld.shared.v2.u32 {%0,%1}, [%2];" : "=r"(v.x), "=r"(v.y) : "r"(a) : "memory"); return v; }
__device__ __forceinline__ uint4 lds128(uint32_t a) { uint4 v; asm volatile("ld.shared.v4.u32 {%0,%1,%2,%3}, [%4];" : "=r"(v.x), "=r"(v.y), "=r"(v.z), "=r"(v.w) : "r"(a) : "memory"); return v; }
__device__ __forceinline__ void ldsm4(uint32_t a, uint32_t* v) {
  asm volatile("ldmatrix.sync.aligned.m8n8.x4.shared.b16 {%0,%1,%2,%3}, [%4];" : "=r"(v[0]), "=r"(v[1]), "=r"(v[2]), "=r"(v[3]) : "r"(a) : "memory");
}
__device__ __forceinline__ void stsm4(uint32_t a, const uint32_t* v) {
  asm volatile("stmatrix.sync.aligned.m8n8.x4.shared.b16 [%0], {%1,%2,%3,%4};" ::"r"(a), "r"(v[0]), "r"(v[1]), "r"(v[2]), "r"(v[3]) : "memory");
}
__device__ __forceinline__ void sts32(uint32_t a, uint32_t v) { asm volatile("st.shared.u32 [%0], %1;" ::"r"(a), "r"(v) : "memory"); }
__device__ __forceinline__ void st_pkt(uint4* p, uint32_t a, uint32_t b, uint32_t c, uint32_t d) {
  asm volatile("st.relaxed.gpu.global.v4.b32 [%0], {%1, %2, %3, %4};" ::"l"(p), "r"(a), "r"(b), "r"(c), "r"(d) : "memory");
}
__device__ __forceinline__ uint4 ld_pkt(const uint4* p) {
  uint4 v;
  asm volatile("{\n.reg .b128 v;\nld.relaxed.gpu.global.b128 v, [%4];\nmov.b128 {%0, %1, %2, %3}, v;\n}\n" : "=r"(v.x), "=r"(v.y), "=r"(v.z), "=r"(v.w) : "l"(p) : "memory");
  return v;
}
__device__ __forceinline__ uint4 ldg_nc(const void* p) {
  uint4 v;
  asm volatile("ld.global.nc.v4.u32 {%0,%1,%2,%3}, [%4];" : "=r"(v.x), "=r"(v.y), "=r"(v.z), "=r"(v.w) : "l"(p));
  return v;
}
#define WG_FENCE() asm volatile("wgmma.fence.sync.aligned;" ::: "memory")
#define WG_COMMIT() asm volatile("wgmma.commit_group.sync.aligned;" ::: "memory")
#define WG_WAIT(n) asm volatile("wgmma.wait_group.sync.aligned " #n ";" ::: "memory")
template <int N> __device__ __forceinline__ void reg_fence(float (&d)[N]) {
#pragma unroll
  for (int i = 0; i < N; i++) asm volatile("" : "+f"(d[i])::"memory");
}
template <int N> __device__ __forceinline__ void reg_fence(uint32_t (&d)[N]) {
#pragma unroll
  for (int i = 0; i < N; i++) asm volatile("" : "+r"(d[i])::"memory");
}
__device__ __forceinline__ constexpr uint64_t desc_hi(uint32_t lbo, uint32_t sbo, uint64_t sw) {
  return ((uint64_t)(lbo >> 4) << 16) | ((uint64_t)(sbo >> 4) << 32) | (sw << 62);
}
__device__ __forceinline__ uint64_t mkdesc(uint32_t addr, uint64_t hi) { return hi | (uint64_t)((addr & 0x3FFFF) >> 4); }
__device__ __forceinline__ uint32_t pack_bf16(float lo, float hi) { uint32_t r; asm("cvt.rn.bf16x2.f32 %0, %1, %2;" : "=r"(r) : "f"(hi), "f"(lo)); return r; }
__device__ __forceinline__ float bf_lo(uint32_t v) { return __uint_as_float(v << 16); }
__device__ __forceinline__ float bf_hi(uint32_t v) { return __uint_as_float(v & 0xffff0000u); }
__device__ __forceinline__ uint32_t hadd2(uint32_t a, uint32_t b) { uint32_t r; asm("add.rn.bf16x2 %0, %1, %2;" : "=r"(r) : "r"(a), "r"(b)); return r; }
__device__ __forceinline__ uint32_t hsub2(uint32_t a, uint32_t b) { uint32_t r; asm("sub.rn.bf16x2 %0, %1, %2;" : "=r"(r) : "r"(a), "r"(b)); return r; }
__device__ __forceinline__ uint32_t hmul2(uint32_t a, uint32_t b) { uint32_t r; asm("mul.rn.bf16x2 %0, %1, %2;" : "=r"(r) : "r"(a), "r"(b)); return r; }
__device__ __forceinline__ float rbf(float x) { return __bfloat162float(__float2bfloat16_rn(x)); }
__device__ __forceinline__ float ex2(float x) { float y; asm("ex2.approx.ftz.f32 %0, %1;" : "=f"(y) : "f"(x)); return y; }
__device__ __forceinline__ float rcp(float x) { float y; asm("rcp.approx.ftz.f32 %0, %1;" : "=f"(y) : "f"(x)); return y; }
__device__ __forceinline__ float sigmoid_f(float x) { return rcp(1.f + ex2(x * -1.4426950408889634f)); }
__device__ __forceinline__ float silu_f(float x) { return x * sigmoid_f(x); }

__device__ __forceinline__ void wg_ss192t(float (&d)[96], uint64_t da, uint64_t db, int sd) {
  asm volatile("{\n.reg .pred p;\nsetp.ne.b32 p, %98, 0;\n"
    "wgmma.mma_async.sync.aligned.m64n192k16.f32.bf16.bf16 {%0,%1,%2,%3,%4,%5,%6,%7,%8,%9,%10,%11,%12,%13,%14,%15,%16,%17,%18,%19,%20,%21,%22,%23,%24,%25,%26,%27,%28,%29,%30,%31,%32,%33,%34,%35,%36,%37,%38,%39,%40,%41,%42,%43,%44,%45,%46,%47,%48,%49,%50,%51,%52,%53,%54,%55,%56,%57,%58,%59,%60,%61,%62,%63,%64,%65,%66,%67,%68,%69,%70,%71,%72,%73,%74,%75,%76,%77,%78,%79,%80,%81,%82,%83,%84,%85,%86,%87,%88,%89,%90,%91,%92,%93,%94,%95}, %96, %97, p, 1, 1, 0, 1;\n}\n"
    : "+f"(d[0]),"+f"(d[1]),"+f"(d[2]),"+f"(d[3]),"+f"(d[4]),"+f"(d[5]),"+f"(d[6]),"+f"(d[7]),"+f"(d[8]),"+f"(d[9]),"+f"(d[10]),"+f"(d[11]),"+f"(d[12]),"+f"(d[13]),"+f"(d[14]),"+f"(d[15]),"+f"(d[16]),"+f"(d[17]),"+f"(d[18]),"+f"(d[19]),"+f"(d[20]),"+f"(d[21]),"+f"(d[22]),"+f"(d[23]),"+f"(d[24]),"+f"(d[25]),"+f"(d[26]),"+f"(d[27]),"+f"(d[28]),"+f"(d[29]),"+f"(d[30]),"+f"(d[31]),"+f"(d[32]),"+f"(d[33]),"+f"(d[34]),"+f"(d[35]),"+f"(d[36]),"+f"(d[37]),"+f"(d[38]),"+f"(d[39]),"+f"(d[40]),"+f"(d[41]),"+f"(d[42]),"+f"(d[43]),"+f"(d[44]),"+f"(d[45]),"+f"(d[46]),"+f"(d[47]),"+f"(d[48]),"+f"(d[49]),"+f"(d[50]),"+f"(d[51]),"+f"(d[52]),"+f"(d[53]),"+f"(d[54]),"+f"(d[55]),"+f"(d[56]),"+f"(d[57]),"+f"(d[58]),"+f"(d[59]),"+f"(d[60]),"+f"(d[61]),"+f"(d[62]),"+f"(d[63]),"+f"(d[64]),"+f"(d[65]),"+f"(d[66]),"+f"(d[67]),"+f"(d[68]),"+f"(d[69]),"+f"(d[70]),"+f"(d[71]),"+f"(d[72]),"+f"(d[73]),"+f"(d[74]),"+f"(d[75]),"+f"(d[76]),"+f"(d[77]),"+f"(d[78]),"+f"(d[79]),"+f"(d[80]),"+f"(d[81]),"+f"(d[82]),"+f"(d[83]),"+f"(d[84]),"+f"(d[85]),"+f"(d[86]),"+f"(d[87]),"+f"(d[88]),"+f"(d[89]),"+f"(d[90]),"+f"(d[91]),"+f"(d[92]),"+f"(d[93]),"+f"(d[94]),"+f"(d[95])
    : "l"(da), "l"(db), "r"(sd));
}
__device__ __forceinline__ void wg_rs64(float (&d)[32], uint32_t a0, uint32_t a1, uint32_t a2, uint32_t a3, uint64_t db, int sd) {
  asm volatile("{\n.reg .pred p;\nsetp.ne.b32 p, %37, 0;\n"
    "wgmma.mma_async.sync.aligned.m64n64k16.f32.bf16.bf16 {%0,%1,%2,%3,%4,%5,%6,%7,%8,%9,%10,%11,%12,%13,%14,%15,%16,%17,%18,%19,%20,%21,%22,%23,%24,%25,%26,%27,%28,%29,%30,%31}, {%32,%33,%34,%35}, %36, p, 1, 1, 0;\n}\n"
    : "+f"(d[0]),"+f"(d[1]),"+f"(d[2]),"+f"(d[3]),"+f"(d[4]),"+f"(d[5]),"+f"(d[6]),"+f"(d[7]),"+f"(d[8]),"+f"(d[9]),"+f"(d[10]),"+f"(d[11]),"+f"(d[12]),"+f"(d[13]),"+f"(d[14]),"+f"(d[15]),"+f"(d[16]),"+f"(d[17]),"+f"(d[18]),"+f"(d[19]),"+f"(d[20]),"+f"(d[21]),"+f"(d[22]),"+f"(d[23]),"+f"(d[24]),"+f"(d[25]),"+f"(d[26]),"+f"(d[27]),"+f"(d[28]),"+f"(d[29]),"+f"(d[30]),"+f"(d[31])
    : "r"(a0), "r"(a1), "r"(a2), "r"(a3), "l"(db), "r"(sd));
}
__device__ __forceinline__ void wg_rs192t(float (&d)[96], uint32_t a0, uint32_t a1, uint32_t a2, uint32_t a3, uint64_t db, int sd) {
  asm volatile("{\n.reg .pred p;\nsetp.ne.b32 p, %101, 0;\n"
    "wgmma.mma_async.sync.aligned.m64n192k16.f32.bf16.bf16 {%0,%1,%2,%3,%4,%5,%6,%7,%8,%9,%10,%11,%12,%13,%14,%15,%16,%17,%18,%19,%20,%21,%22,%23,%24,%25,%26,%27,%28,%29,%30,%31,%32,%33,%34,%35,%36,%37,%38,%39,%40,%41,%42,%43,%44,%45,%46,%47,%48,%49,%50,%51,%52,%53,%54,%55,%56,%57,%58,%59,%60,%61,%62,%63,%64,%65,%66,%67,%68,%69,%70,%71,%72,%73,%74,%75,%76,%77,%78,%79,%80,%81,%82,%83,%84,%85,%86,%87,%88,%89,%90,%91,%92,%93,%94,%95}, {%96,%97,%98,%99}, %100, p, 1, 1, 1;\n}\n"
    : "+f"(d[0]),"+f"(d[1]),"+f"(d[2]),"+f"(d[3]),"+f"(d[4]),"+f"(d[5]),"+f"(d[6]),"+f"(d[7]),"+f"(d[8]),"+f"(d[9]),"+f"(d[10]),"+f"(d[11]),"+f"(d[12]),"+f"(d[13]),"+f"(d[14]),"+f"(d[15]),"+f"(d[16]),"+f"(d[17]),"+f"(d[18]),"+f"(d[19]),"+f"(d[20]),"+f"(d[21]),"+f"(d[22]),"+f"(d[23]),"+f"(d[24]),"+f"(d[25]),"+f"(d[26]),"+f"(d[27]),"+f"(d[28]),"+f"(d[29]),"+f"(d[30]),"+f"(d[31]),"+f"(d[32]),"+f"(d[33]),"+f"(d[34]),"+f"(d[35]),"+f"(d[36]),"+f"(d[37]),"+f"(d[38]),"+f"(d[39]),"+f"(d[40]),"+f"(d[41]),"+f"(d[42]),"+f"(d[43]),"+f"(d[44]),"+f"(d[45]),"+f"(d[46]),"+f"(d[47]),"+f"(d[48]),"+f"(d[49]),"+f"(d[50]),"+f"(d[51]),"+f"(d[52]),"+f"(d[53]),"+f"(d[54]),"+f"(d[55]),"+f"(d[56]),"+f"(d[57]),"+f"(d[58]),"+f"(d[59]),"+f"(d[60]),"+f"(d[61]),"+f"(d[62]),"+f"(d[63]),"+f"(d[64]),"+f"(d[65]),"+f"(d[66]),"+f"(d[67]),"+f"(d[68]),"+f"(d[69]),"+f"(d[70]),"+f"(d[71]),"+f"(d[72]),"+f"(d[73]),"+f"(d[74]),"+f"(d[75]),"+f"(d[76]),"+f"(d[77]),"+f"(d[78]),"+f"(d[79]),"+f"(d[80]),"+f"(d[81]),"+f"(d[82]),"+f"(d[83]),"+f"(d[84]),"+f"(d[85]),"+f"(d[86]),"+f"(d[87]),"+f"(d[88]),"+f"(d[89]),"+f"(d[90]),"+f"(d[91]),"+f"(d[92]),"+f"(d[93]),"+f"(d[94]),"+f"(d[95])
    : "r"(a0), "r"(a1), "r"(a2), "r"(a3), "l"(db), "r"(sd));
}
__device__ __forceinline__ void wg_ss160t(float (&d)[80], uint64_t da, uint64_t db, int sd) {
  asm volatile("{\n.reg .pred p;\nsetp.ne.b32 p, %82, 0;\n"
    "wgmma.mma_async.sync.aligned.m64n160k16.f32.bf16.bf16 {%0,%1,%2,%3,%4,%5,%6,%7,%8,%9,%10,%11,%12,%13,%14,%15,%16,%17,%18,%19,%20,%21,%22,%23,%24,%25,%26,%27,%28,%29,%30,%31,%32,%33,%34,%35,%36,%37,%38,%39,%40,%41,%42,%43,%44,%45,%46,%47,%48,%49,%50,%51,%52,%53,%54,%55,%56,%57,%58,%59,%60,%61,%62,%63,%64,%65,%66,%67,%68,%69,%70,%71,%72,%73,%74,%75,%76,%77,%78,%79}, %80, %81, p, 1, 1, 0, 1;\n}\n"
    : "+f"(d[0]),"+f"(d[1]),"+f"(d[2]),"+f"(d[3]),"+f"(d[4]),"+f"(d[5]),"+f"(d[6]),"+f"(d[7]),"+f"(d[8]),"+f"(d[9]),"+f"(d[10]),"+f"(d[11]),"+f"(d[12]),"+f"(d[13]),"+f"(d[14]),"+f"(d[15]),"+f"(d[16]),"+f"(d[17]),"+f"(d[18]),"+f"(d[19]),"+f"(d[20]),"+f"(d[21]),"+f"(d[22]),"+f"(d[23]),"+f"(d[24]),"+f"(d[25]),"+f"(d[26]),"+f"(d[27]),"+f"(d[28]),"+f"(d[29]),"+f"(d[30]),"+f"(d[31]),"+f"(d[32]),"+f"(d[33]),"+f"(d[34]),"+f"(d[35]),"+f"(d[36]),"+f"(d[37]),"+f"(d[38]),"+f"(d[39]),"+f"(d[40]),"+f"(d[41]),"+f"(d[42]),"+f"(d[43]),"+f"(d[44]),"+f"(d[45]),"+f"(d[46]),"+f"(d[47]),"+f"(d[48]),"+f"(d[49]),"+f"(d[50]),"+f"(d[51]),"+f"(d[52]),"+f"(d[53]),"+f"(d[54]),"+f"(d[55]),"+f"(d[56]),"+f"(d[57]),"+f"(d[58]),"+f"(d[59]),"+f"(d[60]),"+f"(d[61]),"+f"(d[62]),"+f"(d[63]),"+f"(d[64]),"+f"(d[65]),"+f"(d[66]),"+f"(d[67]),"+f"(d[68]),"+f"(d[69]),"+f"(d[70]),"+f"(d[71]),"+f"(d[72]),"+f"(d[73]),"+f"(d[74]),"+f"(d[75]),"+f"(d[76]),"+f"(d[77]),"+f"(d[78]),"+f"(d[79])
    : "l"(da), "l"(db), "r"(sd));
}
__device__ __forceinline__ void wg_ss80t(float (&d)[40], uint64_t da, uint64_t db, int sd) {
  asm volatile("{\n.reg .pred p;\nsetp.ne.b32 p, %42, 0;\n"
    "wgmma.mma_async.sync.aligned.m64n80k16.f32.bf16.bf16 {%0,%1,%2,%3,%4,%5,%6,%7,%8,%9,%10,%11,%12,%13,%14,%15,%16,%17,%18,%19,%20,%21,%22,%23,%24,%25,%26,%27,%28,%29,%30,%31,%32,%33,%34,%35,%36,%37,%38,%39}, %40, %41, p, 1, 1, 0, 1;\n}\n"
    : "+f"(d[0]),"+f"(d[1]),"+f"(d[2]),"+f"(d[3]),"+f"(d[4]),"+f"(d[5]),"+f"(d[6]),"+f"(d[7]),"+f"(d[8]),"+f"(d[9]),"+f"(d[10]),"+f"(d[11]),"+f"(d[12]),"+f"(d[13]),"+f"(d[14]),"+f"(d[15]),"+f"(d[16]),"+f"(d[17]),"+f"(d[18]),"+f"(d[19]),"+f"(d[20]),"+f"(d[21]),"+f"(d[22]),"+f"(d[23]),"+f"(d[24]),"+f"(d[25]),"+f"(d[26]),"+f"(d[27]),"+f"(d[28]),"+f"(d[29]),"+f"(d[30]),"+f"(d[31]),"+f"(d[32]),"+f"(d[33]),"+f"(d[34]),"+f"(d[35]),"+f"(d[36]),"+f"(d[37]),"+f"(d[38]),"+f"(d[39])
    : "l"(da), "l"(db), "r"(sd));
}

struct MapPair { CUtensorMap m[2]; };
struct Params {
  const __nv_bfloat16 *x, *wr, *wg, *wu, *wd, *k, *v;
  Scratch* s;
};

__device__ __forceinline__ void side_cta(const Params& p, int sc, unsigned epoch, float* sm) {
  const int tid = threadIdx.x, lane = tid & 31, warp = tid >> 5;
  int budget = WAIT_BUDGET;
  float* s_x = sm;
  float* s_red = sm + 1280;
  float* s_h = s_red + 6144;
  uint4* s_c = (uint4*)(s_h + 768);
  uint2* s_st = (uint2*)(s_c + 16);
  constexpr int DEPTH = 7, STEP = 4 * 6144;
  const uint32_t ring = smem_u32(s_st + 512) + tid * 16;
  const int cg = tid % 96, ks = tid / 96, cd = tid % 80, kd = tid / 80;
  const __nv_bfloat16* wp = (cg < 48 ? p.wg : p.wu) + (size_t)(ks * 160) * FF + sc * 384 + (cg % 48) * 8;
  int kf = 0, pitch = FF;
  uint32_t slot = ring;
  auto refill = [&]() {
    if (kf == 40) { wp = p.wd + (size_t)(sc * 384 + kd * 96) * DM + cd * 8; pitch = DM; }
    if (kf < (tid < 320 ? 64 : 40)) {
#pragma unroll
      for (int j = 0; j < 4; j++) asm volatile("cp.async.cg.shared.global.L2::cache_hint [%0], [%1], 16, %2;" ::"r"(slot + j * 6144), "l"(wp + j * pitch), "l"(POL_FIRST) : "memory");
    }
    asm volatile("cp.async.commit_group;" ::: "memory");
    wp += 4 * pitch; kf++;
    slot += STEP; if (slot == ring + DEPTH * STEP) slot = ring;
  };
  auto gemv = [&](int n, const float* x0, const float* x1, float* out) {
    float a[2][8] = {};
#pragma unroll 1
    for (int k = 0; k < n; k += 4) {
      refill();
      asm volatile("cp.async.wait_group %0;" ::"n"(DEPTH - 1) : "memory");
      const float4 f0 = *(const float4*)(x0 + k), f1 = *(const float4*)(x1 + k);
      const float y0[4] = {f0.x, f0.y, f0.z, f0.w}, y1[4] = {f1.x, f1.y, f1.z, f1.w};
#pragma unroll
      for (int j = 0; j < 4; j++) {
        const uint4 v = lds128(slot + j * 6144);
        const uint32_t u[4] = {v.x, v.y, v.z, v.w};
#pragma unroll
        for (int i = 0; i < 4; i++) {
          a[0][2 * i] += y0[j] * bf_lo(u[i]); a[0][2 * i + 1] += y0[j] * bf_hi(u[i]);
          a[1][2 * i] += y1[j] * bf_lo(u[i]); a[1][2 * i + 1] += y1[j] * bf_hi(u[i]);
        }
      }
    }
#pragma unroll
    for (int i = 0; i < 16; i++) out[(i >> 3) * 768 + (i & 7)] = a[i >> 3][i & 7];
  };
  auto load_row = [&](const __nv_bfloat16* r, uint32_t (&v)[10]) {
    const uint4 a = __ldg((const uint4*)r + lane), b = __ldg((const uint4*)r + 32 + lane);
    const uint2 c = __ldg((const uint2*)r + 128 + lane);
    v[0] = a.x; v[1] = a.y; v[2] = a.z; v[3] = a.w; v[4] = b.x; v[5] = b.y; v[6] = b.z; v[7] = b.w; v[8] = c.x; v[9] = c.y;
  };
  uint32_t wr[10], xb[3][10];
  load_row(p.wr, wr);
#pragma unroll 1
  for (int i = tid; i < 512; i += 384) {
    uint4 v;
    do v = ld_pkt(p.s->stat + sc * 512 + i); while (v.x != epoch + 1 && --budget >= 0);
    s_st[i] = make_uint2(v.w, v.y);
  }
  __syncthreads();
#pragma unroll
  for (int b = 0; b < 3; b++) load_row(p.x + (size_t)(sc * 512 + warp + 12 * b) * DM, xb[b]);
#pragma unroll 1
  for (int k = 0; k < DEPTH - 1; k++) refill();
  float v0 = -INFINITY, v1 = -INFINITY; int i0 = 0xfff, i1 = 0xfff;
  auto better = [](float a, int ia, float b, int ib) { return a > b || (a == b && ia < ib); };
  auto push = [&](float v, int i) {
    if (better(v, i, v0, i0)) { v1 = v0; i1 = i0; v0 = v; i0 = i; }
    else if (better(v, i, v1, i1)) { v1 = v; i1 = i; }
  };
  auto push2 = [&](uint4 c) { push(__uint_as_float(c.x), c.y & 0xfff); push(__uint_as_float(c.z), c.w & 0xfff); };
#pragma unroll 1
  for (int l3 = warp; l3 < 512; l3 += 36) {
#pragma unroll
    for (int b = 0; b < 3; b++) {
      const int lr = l3 + 12 * b;
      if (lr >= 512) break;
      const uint2 st = s_st[lr];
      uint32_t v[10];
#pragma unroll
      for (int i = 0; i < 10; i++) v[i] = hsub2(xb[b][i], st.x);
      if (lr + 36 < 512) load_row(p.x + (size_t)(sc * 512 + lr + 36) * DM, xb[b]);
      float r0 = 0.f, r1 = 0.f;
#pragma unroll
      for (int i = 0; i < 10; i++) {
        const uint32_t xn = pack_bf16(bf_lo(v[i]) * __uint_as_float(st.y), bf_hi(v[i]) * __uint_as_float(st.y));
        r0 = fmaf(bf_lo(xn), bf_lo(wr[i]), r0); r1 = fmaf(bf_hi(xn), bf_hi(wr[i]), r1);
      }
      r0 += r1;
#pragma unroll
      for (int o = 16; o > 0; o >>= 1) r0 += __shfl_xor_sync(~0u, r0, o);
      push(rbf(r0), sc * 512 + lr);
    }
  }
  if (lane == 0) s_c[warp] = make_uint4(__float_as_uint(v0), i0, __float_as_uint(v1), i1);
  __syncthreads();
#pragma unroll 1
  for (int w = 1; w < 12; w++) push2(s_c[(warp + w) % 12]);
  const uint32_t tag = (epoch + 1) << 12;
  if (tid == 0) st_pkt(p.s->cand + sc, __float_as_uint(v0), i0 | tag, __float_as_uint(v1), i1);
  {
    uint4 c;
    do c = ld_pkt(p.s->cand + (lane & 3)); while (((c.y ^ tag) >> 12) && --budget >= 0);
#pragma unroll 1
    for (int w = 1; w < 4; w++) { const int o = (sc + w) & 3; push2(make_uint4(__shfl_sync(~0u, c.x, o), __shfl_sync(~0u, c.y, o), __shfl_sync(~0u, c.z, o), __shfl_sync(~0u, c.w, o))); }
  }
  if (i0 >= SQ) i0 = 0;
  if (i1 >= SQ) i1 = (i0 == 0) ? 1 : 0;
  if (tid < 320) {
    const int row = tid < 160 ? i0 : i1;
    const uint2 u = __ldg((const uint2*)(p.x + (size_t)row * DM) + tid % 160);
    uint4 st;
    do st = ld_pkt(p.s->stat + row); while (st.x != epoch + 1 && --budget >= 0);
    const uint32_t d0 = hsub2(u.x, st.w), d1 = hsub2(u.y, st.w);
    const float inv = __uint_as_float(st.y);
    ((float4*)s_x)[tid] = make_float4(rbf(bf_lo(d0) * inv), rbf(bf_hi(d0) * inv), rbf(bf_lo(d1) * inv), rbf(bf_hi(d1) * inv));
  }
  __syncthreads();
  gemv(160, s_x + ks * 160, s_x + DM + ks * 160, s_red + ks * 1536 + cg * 8);
  __syncthreads();
#pragma unroll
  for (int t = 0; t < 2; t++) {
    float g = 0.f, u = 0.f;
#pragma unroll
    for (int k = 0; k < 4; k++) { g += s_red[(k * 2 + t) * 768 + tid]; u += s_red[(k * 2 + t) * 768 + 384 + tid]; }
    s_h[t * 384 + tid] = rbf(rbf(silu_f(rbf(g))) * rbf(u));
  }
  __syncthreads();
  if (tid < 320) gemv(96, s_h + kd * 96, s_h + 384 + kd * 96, s_red + kd * 1536 + cd * 8);
  __syncthreads();
  const int o4 = tid + (tid < 160 ? 0 : 32);
  if (tid < 320) {
    const float4 *r = (const float4*)s_red + o4, a = r[0], b = r[384], c = r[768], d = r[1152];
    ((float4*)p.s->ffn)[sc * 320 + tid] = make_float4(a.x + b.x + c.x + d.x, a.y + b.y + c.y + d.y, a.z + b.z + c.z + d.z, a.w + b.w + c.w + d.w);
  }
  __syncthreads();
  if (tid == 0) { __threadfence(); s_c[0].x = (atomicAdd(&p.s->flag[FL_SIDE], 1u) & 3u) == 3u; __threadfence(); }
  __syncthreads();
  if (s_c[0].x) {
    if (tid < 320) {
      const float4 *r = (const float4*)p.s->ffn + tid, a = __ldcg(r), b = __ldcg(r + 320), c = __ldcg(r + 640), d = __ldcg(r + 960), x = ((float4*)s_x)[tid];
      const float rs = rbf(sigmoid_f(tid < 160 ? v0 : v1));
      auto gate = [&](float xn, float y) { return silu_f(rbf(xn + rbf(rbf(y) * rs))); };
      if (tid == 0) { p.s->sel[0] = i0; p.s->sel[1] = i1; }
      ((uint2*)p.s->gsel)[tid] =
          make_uint2(pack_bf16(gate(x.x, a.x + b.x + c.x + d.x), gate(x.y, a.y + b.y + c.y + d.y)), pack_bf16(gate(x.z, a.z + b.z + c.z + d.z), gate(x.w, a.w + b.w + c.w + d.w)));
    }
    __syncthreads();
    if (tid == 0) red_release(&p.s->flag[FL_FFN]);
  }
}

constexpr float SM_C = 0.07216878364870322f * 1.4426950408889634f;

#define LD 0
#define LS 3
__device__ __forceinline__ void ln_piece(const Params& p, uint32_t (&r)[48], int k, int row, int l16) {
  auto f = [&](int i) { return __uint_as_float(r[i]); };
  if (k == LD) {
#pragma unroll
    for (int i = 0; i < 5; i++) {
      const uint4 v = ldg_nc((const uint4*)(p.x + (size_t)row * DM) + i * 16 + l16);
      r[4 * i] = v.x; r[4 * i + 1] = v.y; r[4 * i + 2] = v.z; r[4 * i + 3] = v.w;
    }
    asm volatile("ld.relaxed.gpu.global.v2.u32 {%0,%1}, [%2];" : "=r"(r[20]), "=r"(r[21]) : "l"(&p.s->done));
  } else if (k == LS || k == LS + 1) {
    if (k == LS) { r[22] = __shfl_sync(~0u, r[0], 0, 16) << 16; r[23] = r[24] = 0; }
    float s0 = f(23), s1 = 0.f, q0 = f(24), q1 = 0.f;
#pragma unroll
    for (int i = 10 * (k - LS); i < 10 * (k - LS) + 10; i++) {
      const float a = bf_lo(r[i]) - f(22), b = bf_hi(r[i]) - f(22);
      s0 += a; s1 += b; q0 = fmaf(a, a, q0); q1 = fmaf(b, b, q1);
    }
    r[23] = __float_as_uint(s0 + s1); r[24] = __float_as_uint(q0 + q1);
  } else if (k == LS + 2) {
    float s0 = f(23), q0 = f(24);
#pragma unroll
    for (int o = 8; o > 0; o >>= 1) { s0 += __shfl_xor_sync(~0u, s0, o); q0 += __shfl_xor_sync(~0u, q0, o); }
    s0 *= 1.f / DM;
    const float mean = f(22) + s0, var = rbf(fmaxf(fmaf(q0, 1.f / DM, -s0 * s0), 0.f));
    float sd; asm("sqrt.approx.ftz.f32 %0, %1;" : "=f"(sd) : "f"(rbf(var + 1e-5f)));
    const float inv = rcp(rbf(sd));
    r[22] = pack_bf16(mean, mean); r[23] = __float_as_uint(inv * SM_C);
    const uint32_t tag = __funnelshift_r(r[20], r[21], 7) + 1;
    if (l16 == 0) st_pkt(&p.s->stat[row], tag, __float_as_uint(inv), tag, r[22]);
  } else if (k > LS + 2 && k <= LS + 5) {
#pragma unroll
    for (int j = 2 * (k - LS - 3); j < 2 * (k - LS - 3) + 2 && j < 5; j++) {
#pragma unroll
      for (int i = 4 * j; i < 4 * j + 4; i++) { const uint32_t d = hsub2(r[i], r[22]); r[i] = pack_bf16(bf_lo(d) * f(23), bf_hi(d) * f(23)); }
      *((uint4*)(p.s->xn + (size_t)row * DM) + j * 16 + l16) = make_uint4(r[4 * j], r[4 * j + 1], r[4 * j + 2], r[4 * j + 3]);
    }
  }
}

constexpr float SM_HI = 0x1p64f, SM_LO = 0x1p-64f;
__device__ __forceinline__ void exp_block(float (&s)[32], float& l0, float& l1, int from = 0, int to = 32) {
#pragma unroll
  for (int i = from; i < to; i++) { s[i] = ex2(s[i]); if (i & 2) l1 += s[i]; else l0 += s[i]; }
}
__device__ __forceinline__ float quad_sum(float v) { v += __shfl_xor_sync(~0u, v, 1); return v + __shfl_xor_sync(~0u, v, 2); }
__device__ __forceinline__ float quad_max(float v) { v = fmaxf(v, __shfl_xor_sync(~0u, v, 1)); return fmaxf(v, __shfl_xor_sync(~0u, v, 2)); }
__device__ __noinline__ void safe_head(const uint32_t* kp, const uint32_t* vp, uint4* io) {
  uint32_t fq[48];
#pragma unroll
  for (int i = 0; i < 12; i++) { const uint4 v = io[(i >> 1) * 512 + (i & 1) * 32]; fq[4 * i] = v.x; fq[4 * i + 1] = v.y; fq[4 * i + 2] = v.z; fq[4 * i + 3] = v.w; }
  float m0 = -INFINITY, m1 = -INFINITY;
#pragma unroll 1
  for (int pass = 0; pass < 3; pass++) {
    float o[48] = {}, l0 = 0.f, l1 = 0.f;
#pragma unroll 1
    for (int n = 0; n < 64; n++) {
      const uint32_t *kr = kp + n * (8 * DH / 2), *vr = vp + n * (8 * DH / 2) + (pass - 1) * 48;
      float d[4] = {};
#pragma unroll
      for (int t = 0; t < 12; t++)
        asm volatile("mma.sync.aligned.m16n8k16.row.col.f32.bf16.bf16.f32 {%0,%1,%2,%3}, {%4,%5,%6,%7}, {%8,%9}, {%0,%1,%2,%3};"
                     : "+f"(d[0]), "+f"(d[1]), "+f"(d[2]), "+f"(d[3])
                     : "r"(fq[4 * t]), "r"(fq[4 * t + 1]), "r"(fq[4 * t + 2]), "r"(fq[4 * t + 3]), "r"(__ldg(kr + 8 * t)), "r"(__ldg(kr + 8 * t + 4)));
      if (pass == 0) { m0 = fmaxf(m0, fmaxf(d[0], d[1])); m1 = fmaxf(m1, fmaxf(d[2], d[3])); continue; }
      d[0] = ex2(d[0] - m0); d[1] = ex2(d[1] - m0); d[2] = ex2(d[2] - m1); d[3] = ex2(d[3] - m1);
      l0 += d[0] + d[1]; l1 += d[2] + d[3];
      const uint32_t p0 = pack_bf16(d[0], d[1]), p1 = pack_bf16(d[2], d[3]);
#pragma unroll
      for (int c = 0; c < 12; c++)
        asm volatile("{\n.reg .b32 t;\nmovmatrix.sync.aligned.m8n8.trans.b16 t, %6;\n"
                     "mma.sync.aligned.m16n8k8.row.col.f32.bf16.bf16.f32 {%0,%1,%2,%3}, {%4,%5}, {t}, {%0,%1,%2,%3};\n}\n"
                     : "+f"(o[4 * c]), "+f"(o[4 * c + 1]), "+f"(o[4 * c + 2]), "+f"(o[4 * c + 3]) : "r"(p0), "r"(p1), "r"(__ldg(vr + 4 * c)));
    }
    if (pass == 0) { m0 = quad_max(m0); m1 = quad_max(m1); continue; }
    l0 = rcp(quad_sum(l0)); l1 = rcp(quad_sum(l1));
#pragma unroll
    for (int i = 0; i < 6; i++) {
      const float* v = o + 16 * (i >> 1) + 2 * (i & 1);
      const float r = i & 1 ? l1 : l0;
      io[(3 * (pass - 1) + (i >> 1)) * 512 + (i & 1) * 32] =
          make_uint4(pack_bf16(v[0] * r, v[1] * r), pack_bf16(v[4] * r, v[5] * r), pack_bf16(v[8] * r, v[9] * r), pack_bf16(v[12] * r, v[13] * r));
    }
  }
}

#define CVG 48
#define NE 8
#define PS1 8
#define CSW 1400
#define D0 2
#define LQ 6
__device__ __forceinline__ constexpr int end_stage(int n) { return n < 4 ? n : n < LQ ? n - 4 : n == LQ ? 4 : n % 5; }
#define Q2N 1
#define SWN 12
#define SCH 0
__device__ __forceinline__ constexpr int sent(int n) {
  constexpr int t[4][15] = {{0, 2, 4, 5, 5, 6, 7, 8,  9, 10, 11, 12, 13, 14, 15},
                            {0, 2, 4, 5, 5, 6, 7, 8,  9, 10, 12, 13, 14, 15, 15},
                            {0, 2, 4, 5, 5, 7, 8, 9, 10, 10, 12, 14, 15, 15, 15},
                            {0, 2, 4, 5, 5, 7, 8, 9, 10, 10, 13, 15, 15, 15, 15}};
  return n < LQ + 2 ? 0 : LQ == 6 && n == 8 ? 3 : t[SCH][n - 6];
}
template <int N> struct IntC { static constexpr int value = N; };
template <int N, int I = 0, class F> __device__ __forceinline__ void static_for(F&& f) { if constexpr (I < N) { f(IntC<I>{}); static_for<N, I + 1>(f); } }

__global__ void __launch_bounds__(384, 1)
fused_kernel(const Params p, const __grid_constant__ CUtensorMap tm_x, const __grid_constant__ CUtensorMap tm_xn,
             const __grid_constant__ CUtensorMap tm_wq, const __grid_constant__ CUtensorMap tm_k,
             const __grid_constant__ CUtensorMap tm_v, const __grid_constant__ CUtensorMap tm_wo,
             const __grid_constant__ MapPair tm_w2,
             const __grid_constant__ CUtensorMap tm_xg, const __grid_constant__ CUtensorMap tm_xe,
             const __grid_constant__ CUtensorMap tm_out) {
  extern __shared__ __align__(1024) uint8_t smem_raw[];
  const uint32_t sb = smem_u32(smem_raw);
  const CUtensorMap* const tm_w = tm_w2.m;
  const uint32_t bar_a = sb + OFF_M, bar_b = bar_a + 80, bar_o = bar_b + 96;
  const uint32_t bar_x = bar_o + 8, bar_z = bar_o + 16, bar_s = bar_o + 24, bar_d = bar_o + 32, bar_w = bar_o + 40, bar_e = bar_o + 48,
                 bar_u = bar_o + 96;
  const uint32_t s_stat = bar_a + 512;
  const uint32_t s_sel = s_stat + 1024;
  const int wi = __shfl_sync(~0u, threadIdx.x >> 5, 0), wg = wi >> 2;
  const int lane = threadIdx.x & 31;
  const int cl = blockIdx.x >> 1;
  const int rank = blockIdx.x & 1;

  if (cl >= 64) {
    const unsigned epoch = (unsigned)(__ldcg(&p.s->done) >> 7);
    side_cta(p, blockIdx.x - 128, epoch, (float*)smem_raw);
    return;
  }
  const int qt = (cl >> 3) * 2 + rank, hg = cl & 7;
  const int kq = hg >> 1, nh = hg & 1;

  if (elect()) {
    if (wi < 2) asm volatile("prefetch.tensormap [%0];" ::"l"(wi ? &tm_wq : &tm_x) : "memory");
    const uint32_t c = (uint32_t)((wi < 5 ? 0x7777700000ull : wi < 10 ? 0x752107ffffff0ull : 0ull) >> (12 * (wi % 5)));
    for (int i = 0; i < 3; i++) mbar_init(bar_a + 24 * wi + 8 * i, ((c >> (4 * i)) & 15) + 1);
  }
  asm volatile("fence.mbarrier_init.release.cluster;" ::: "memory");
  cluster_arrive();
  if (wg > 0) {
    const int w = wg - 1;
    const int cw = wi - 4;
    asm volatile("setmaxnreg.inc.sync.aligned.u32 232;");
    uint32_t fr[48];
    reg_fence(fr);
    auto ln_row = [&]() { int v = qt * 128 + hg * 16 + cw * 2 + (lane >> 4); asm volatile("" : "+r"(v)); return v; };
    if (LD < 0) ln_piece(p, fr, LD, ln_row(), lane & 15);
    cluster_wait();
    uint32_t rel_addr;
    asm volatile("mapa.shared::cluster.u32 %0, %1, %2;" : "=r"(rel_addr) : "r"(bar_b + 48), "r"(lane & 1));
    auto rel_a = [&](uint32_t o8) { if (lane == 0) mbar_arrive(bar_a + 40 + o8); };
    auto rel_b = [&](uint32_t o8) { if (lane < 2) mbar_arrive_cluster(rel_addr + o8); };
    uint32_t b8 = 0, phb = 0;
    auto next_pair = [&]() { b8 += 16; if (b8 == 48) { b8 = 0; phb ^= 1; } };
    const int g = lane >> 2, q = lane & 3;
    constexpr uint64_t HI_A = desc_hi(16, 1024, 1);
    constexpr uint64_t HI_W = desc_hi(1024, 3072, 1);
    constexpr uint64_t HI_O = desc_hi(2048, 512, 2);
    if (w == 1) asm volatile("bar.arrive 1, 256;" ::: "memory");

    uint32_t zero; asm volatile("mov.u32 %0, %%tid.y;" : "=r"(zero));
    float acc[96];
    uint4* optr = p.s->o + (size_t)(qt * 192 + hg * 24) * 512 + (cw * 16 + g) * 4 + (q ^ ((g >> 1) & 3));
    uint32_t rl[4];
    auto store_o = [&](int pp) {
#pragma unroll
      for (int i = (12 * pp + 8) / 9; i < (12 * (pp + 1) + 8) / 9; i++) {
#pragma unroll
        for (int k = 4 * i; k < 4 * i + 4; k++)
          asm volatile("{\n.reg .b32 t;\nmul.rn.bf16x2 t, %0, %2;\nfma.rn.bf16x2 %0, %0, %1, t;\n}\n" : "+r"(fr[k]) : "r"(rl[i & 1]), "r"(rl[2 + (i & 1)]));
        fr[4 * i] &= ~1u;
        optr[(i >> 1) * 512 + (i & 1) * 32] = make_uint4(fr[4 * i], fr[4 * i + 1], fr[4 * i + 2], fr[4 * i + 3]);
      }
      if (pp == 8) optr += 6 * 512;
    };
    auto fresh = [&]() { uint32_t v = sb; asm volatile("" : "+r"(v)); return v; };
    reg_fence(rl);

#pragma unroll 1
    for (int u = 0; u < 4; u++) {
      const uint32_t sq = fresh();
      const uint64_t dA = mkdesc(sq + w * 8192, HI_A), dB0 = mkdesc(sq + OFF_B, HI_W);
      uint32_t pb8 = 0;
#pragma unroll
      for (int s = 0; s < 10; s++) {
        const uint32_t o8 = b8 + 8 * (s & 1);
        const uint64_t dW = dB0 + o8 * (TB >> 7);
        mbar_wait(bar_a + 8 * (s % 5), s / 5);
        mbar_wait(bar_b + o8, phb);
        if (s == 9) asm volatile("bar.sync %0, 256;" ::"r"(1 + w) : "memory");
        WG_FENCE();
#pragma unroll
        for (int kk = 0; kk < 4; kk++) wg_ss192t(acc, dA + ((s % 5) * (TA >> 4) + kk * 2), dW + kk * 384, kk != 0 || s != 0);
        WG_COMMIT();
        if (s == 9) asm volatile("bar.arrive %0, 256;" ::"r"(2 - w) : "memory");
        if (s > 0) { WG_WAIT(1); rel_a(8 * ((s - 1) % 5)); rel_b(pb8); }
        if (s < 9) { if (u > 0) store_o(s); else ln_piece(p, fr, s, ln_row(), lane & 15); }
        if (s == 8) { __syncwarp(); if (lane == 0) mbar_arrive(bar_o); }
        pb8 = o8;
        if (s & 1) next_pair();
      }
      WG_WAIT(0);
      reg_fence(acc);
      rel_b(pb8);
      if (u == 0) {
        mbar_wait(bar_s, 0);
        const uint2 s0 = lds64(s_stat + (cw * 16 + g) * 8), s1 = lds64(s_stat + 64 + (cw * 16 + g) * 8);
        const uint32_t msk = q == 0 ? 0xffffffffu : q == 1 ? 0xffffu : 0u;
        const float c0 = SM_C * __uint_as_float(s0.y), c1 = SM_C * __uint_as_float(s1.y);
        uint32_t am[4] = {(s0.x ^ 0x80008000u) & msk, (s1.x ^ 0x80008000u) & msk, 0, 0};
        reg_fence(am);
        WG_FENCE();
        wg_rs192t(acc, am[0], am[1], am[2], am[3], mkdesc(sb, desc_hi(1024, 0, 1)), 1);
        WG_COMMIT();
        WG_WAIT(0);
        reg_fence(acc);
#pragma unroll
        for (int i = 0; i < 24; i++) { acc[4 * i] *= c0; acc[4 * i + 1] *= c0; acc[4 * i + 2] *= c1; acc[4 * i + 3] *= c1; }
      }
      rel_a(32);
      auto pack_q = [&](int from, int to) {
#pragma unroll
        for (int i = from; i < to; i++) { fr[i] = pack_bf16(acc[2 * i], acc[2 * i + 1]); asm volatile("" : "+r"(fr[i])::"memory"); }
      };
      pack_q(0, CVG);
      float sc[32], l0 = 0.f, l1 = 0.f;
      uint32_t pf[16], k8;
      auto pack_p = [&](const float (&s_)[32], int from = 0, int to = 16) {
#pragma unroll
        for (int i = from; i < to; i++) pf[i] = pack_bf16(s_[2 * i], s_[2 * i + 1]);
      };
      auto scores = [&](int j, int pass = 11) {
        k8 = b8 + 8;
        mbar_wait(bar_b + k8, phb);
        next_pair();
        mbar_wait(bar_b + b8, phb);
        const uint64_t dk = mkdesc(sb + OFF_B, HI_W) + k8 * (TB >> 7);
        asm volatile("bar.sync %0, 256;" ::"r"(1 + w) : "memory");
        WG_FENCE();
#pragma unroll
        for (int t = 0; t < 12; t++) {
          wg_rs64(sc, fr[4 * t], fr[4 * t + 1], fr[4 * t + 2], fr[4 * t + 3], dk + (t >> 2) * 64 + (t & 3) * 2, t != 0);
          if (t == 11) WG_COMMIT();
          if (t == pass) asm volatile("bar.arrive %0, 256;" ::"r"(2 - w) : "memory");
        }
      };
      auto pv = [&](int add) {
        const uint64_t dv = mkdesc(sb + OFF_B, HI_W) + b8 * (TB >> 7);
#pragma unroll
        for (int kk = 0; kk < 4; kk++) wg_rs192t(acc, pf[4 * kk], pf[4 * kk + 1], pf[4 * kk + 2], pf[4 * kk + 3], dv + kk * 384, kk != 0 || add);
        WG_COMMIT();
      };
      auto finish = [&]() {
        WG_WAIT(1);
        reg_fence(sc);
        exp_block(sc, l0, l1);
        rel_b(k8 + (__float_as_uint(l0) & __float_as_uint(l1) & zero));
        WG_WAIT(0);
        reg_fence(acc); reg_fence(pf);
        rel_b(b8);
        pack_p(sc);
      };
      {
        mbar_wait(bar_b + b8, phb);
        const uint64_t dk = mkdesc(sb + OFF_B, HI_W) + b8 * (TB >> 7);
        asm volatile("bar.sync %0, 256;" ::"r"(1 + w) : "memory");
#pragma unroll
        for (int t = 0; t < 12; t++) {
          if (t && (4 * t) % CVG == 0) pack_q(4 * t, 4 * t + CVG);
          if ((4 * t) % CVG == 0) WG_FENCE();
          wg_rs64(sc, fr[4 * t], fr[4 * t + 1], fr[4 * t + 2], fr[4 * t + 3], dk + (t >> 2) * 64 + (t & 3) * 2, t != 0);
          if (t == 7) asm volatile("bar.arrive %0, 256;" ::"r"(2 - w) : "memory");
        }
        WG_COMMIT();
        WG_WAIT(0);
        reg_fence(sc);
        float s0[32];
#pragma unroll
        for (int i = 0; i < 32; i++) s0[i] = i < NE ? sc[i] : __uint_as_float(__float_as_uint(sc[i]) ^ zero);
        exp_block(s0, l0, l1, 0, NE);
        pack_p(s0, 0, NE / 2);
#pragma unroll
        for (int i = NE; i < 32; i++) asm volatile("" : "+f"(s0[i])::"memory");
#pragma unroll
        for (int i = 0; i < NE / 2; i++) asm volatile("" : "+r"(pf[i])::"memory");
        rel_b(b8);
        scores(1, PS1);
        const uint32_t z = lds32(s_stat) & zero;
#pragma unroll
        for (int i = NE; i < 32; i++) {
          asm("{\n.reg .pred p;\nsetp.eq.u32 p, %1, 0;\n@p ex2.approx.ftz.f32 %0, %0;\n}\n" : "+f"(s0[i]) : "r"(z));
          if (i & 2) l1 += s0[i]; else l0 += s0[i];
        }
        pack_p(s0, NE / 2, 16);
        reg_fence(pf);
        WG_FENCE();
        pv(0);
        finish();
      }
#pragma unroll 1
      for (int j = NE < 32 ? 2 : 1; j < 8; j++) { scores(j); pv(j > 1); finish(); }
      const uint32_t v8 = b8 + 8;
      mbar_wait(bar_b + v8, phb);
      next_pair();
      {
        const uint64_t dv = mkdesc(sb + OFF_B, HI_W) + v8 * (TB >> 7);
        asm volatile("bar.sync %0, 256;" ::"r"(1 + w) : "memory");
        WG_FENCE();
#pragma unroll
        for (int kk = 0; kk < 4; kk++) {
          wg_rs192t(acc, pf[4 * kk], pf[4 * kk + 1], pf[4 * kk + 2], pf[4 * kk + 3], dv + kk * 384, 1);
          if (kk == 1 && (u < 3 || w == 0)) asm volatile("bar.arrive %0, 256;" ::"r"(2 - w) : "memory");
        }
        WG_COMMIT();
      }
      l0 = quad_sum(l0); l1 = quad_sum(l1);
      const bool unsafe = __any_sync(~0u, !(l0 >= SM_LO && l1 >= SM_LO && l0 + l1 <= SM_HI));
      l0 = rcp(l0); l1 = rcp(l1);
      rl[0] = pack_bf16(l0, l0); rl[1] = pack_bf16(l1, l1);
      l0 -= bf_lo(rl[0]); l1 -= bf_lo(rl[1]);
      rl[2] = pack_bf16(l0, l0); rl[3] = pack_bf16(l1, l1);
      WG_WAIT(0);
      reg_fence(acc);
      rel_b(v8);
      if (__builtin_expect(unsafe, 0)) {
        int o = hg * 4 + u; asm volatile("" : "+r"(o));
        o = (o * SKC + (SKC - WIN) + g) * (DH / 2) + q;
#pragma unroll
        for (int i = 0; i < 12; i++) optr[(i >> 1) * 512 + (i & 1) * 32] = make_uint4(fr[4 * i], fr[4 * i + 1], fr[4 * i + 2], fr[4 * i + 3]);
        safe_head((const uint32_t*)p.k + o, (const uint32_t*)p.v + o, optr);
#pragma unroll
        for (int i = 0; i < 12; i++) { const uint4 v = optr[(i >> 1) * 512 + (i & 1) * 32]; fr[4 * i] = v.x; fr[4 * i + 1] = v.y; fr[4 * i + 2] = v.z; fr[4 * i + 3] = v.w; }
        rl[0] = rl[1] = 0x3f803f80u; rl[2] = rl[3] = 0;
      } else {
#pragma unroll
        for (int i = 0; i < 24; i++) {
          fr[8 * (i >> 2) + (i & 3)] = pack_bf16(acc[4 * i], acc[4 * i + 1]);
          fr[8 * (i >> 2) + 4 + (i & 3)] = pack_bf16(acc[4 * i + 2], acc[4 * i + 3]);
        }
      }
    }

    float aF[80], aS[80];
    uint32_t pha = 0, a8 = 0, pa8 = 0, pb8 = 0;
#pragma unroll 1
    for (int s = 0; s < 19; s++) {
      const uint64_t d0 = mkdesc(sb, HI_O), dO = d0 + (a8 * (TA >> 7) + w * 256), dB = d0 + ((OFF_B >> 4) + b8 * (TB >> 7));
      mbar_wait(bar_a + a8, pha);
      mbar_wait(bar_b + b8, phb);
      WG_FENCE();
#pragma unroll
      for (int kk = 0; kk < 4; kk++) wg_ss160t(aF, dO + ((kk >> 1) * 512 + (kk & 1) * 2), dB + ((kk >> 1) * 640 + (kk & 1) * 64), kk != 0 || s != 0);
      WG_COMMIT();
      mbar_wait(bar_b + b8 + 8, phb);
      WG_WAIT(1);
      if (s > 0) { rel_a(pa8); rel_b(pb8 + 8); }
      WG_FENCE();
#pragma unroll
      for (int kk = 0; kk < 4; kk++) wg_ss160t(aS, dO + ((kk >> 1) * 512 + (kk & 1) * 2), dB + ((TB >> 4) + (kk >> 1) * 640 + (kk & 1) * 64), kk != 0 || s != 0);
      WG_COMMIT();
      if (s < 9) {
#pragma unroll
        for (int pp = 0; pp < 9; pp++) if (s == pp) store_o(pp);
        if (s == 8) { __syncwarp(); if (lane == 0) mbar_arrive(bar_o); }
      } else if (s < 15) {
        const int b = 2 * cw + ((lane >> 3) & 1);
        uint32_t ga = sb + OFF_B + TW + ((b * 11) >> 5) * (TB - 3840) + b * 1280 + (lane & 7) * 160 + (lane >> 4) * 16;
        if (s < 14) {
          mbar_wait(bar_x, 0);
          ga += 32 * (s - 9);
          ldsm4(ga, fr);
#pragma unroll
          for (int i = 0; i < 4; i++) {
            const uint2 st = lds64(s_stat + (cw * 16 + g + 8 * (i & 1)) * 8);
            const uint32_t d = hsub2(fr[i], st.x), xn = pack_bf16(bf_lo(d) * __uint_as_float(st.y), bf_hi(d) * __uint_as_float(st.y));
            fr[i] = pack_bf16(silu_f(bf_lo(xn)), silu_f(bf_hi(xn)));
          }
          stsm4(ga, fr);
        } else {
          mbar_wait(bar_u, 0);
          const uint2 sel = lds64(s_sel);
          const uint32_t row = qt * 128 + cw * 16 + (lane & 15);
          if (row == sel.x || row == sel.y) ga = s_sel + 16 + (row == sel.y ? 160 : 0) + (lane >> 4) * 16;
#pragma unroll
          for (int k = 0; k < 5; k++) ldsm4(ga + 32 * k, fr + 4 * k);
        }
      }
      WG_WAIT(1);
      rel_b(b8);
      pa8 = a8; a8 += 8; if (a8 == 40) { a8 = 0; pha ^= 1; }
      pb8 = b8; next_pair();
    }
    const int t128 = threadIdx.x & 127;
    uint4* const xbase = p.s->o + (size_t)(qt * 192 + nh * 24 + 10) * 512 + w * 640 + t128;
    uint4* const dst = xbase + kq * (48 * 512);
    float q1[40], q2[40], oth[40], own[40];
    auto take = [&](float (&x)[40], const float* a) {
#pragma unroll
      for (int k = 0; k < 40; k++) x[k] = __uint_as_float(__float_as_uint(a[k]) ^ zero);
      reg_fence(x);
    };
    reg_fence(aF);
    take(q1, aF);
    auto fa = [&](int i) { return mbar_try(bar_a + 8 * ((4 + i) % 5), i == 0); };
    auto fb = [&](int e) { return mbar_try(bar_b + 8 * (e % 6), (e / 6) & 1); };
    auto send = [&](int m) {
      const float* v = (m < 5 ? q1 : m < 10 ? q2 : oth) + 8 * (m % 5);
      st_pkt(dst + (m / 5) * 1280 + (m % 5) * 128, pack_bf16(v[0], v[1]) | 1, pack_bf16(v[2], v[3]), pack_bf16(v[4], v[5]), pack_bf16(v[6], v[7]));
    };
    static_for<20>([&](auto n_) {
      constexpr int n = n_.value, i = end_stage(n), e = 142 + n / 2, qi = n == 4 ? 1 : n == LQ ? 0 : n / 5;
      float (&acc_)[40] = qi == 0 ? q1 : qi == 1 ? q2 : qi == 2 ? oth : own;
      if (n == 0) while (!(fa(0) & fa(1) & fb(142) & fb(143))) {}
      if (n == 2) while (!(fa(2) & fa(3) & fb(144))) {}
      if (n == LQ) while (!(fa(4) & fb(145) & fb(146) & mbar_try(bar_z, 0))) {}
      if (n == 10) while (!(fb(147) & fb(148) & fb(149))) {}
      const uint64_t d0 = mkdesc(fresh(), HI_O);
      WG_FENCE();
#pragma unroll
      for (int kk = 0; kk < 4; kk++)
        wg_ss80t(acc_, d0 + w * 256 + (((4 + i) % 5) * (TA >> 4) + (kk >> 1) * 512 + (kk & 1) * 2),
                 d0 + ((OFF_B >> 4) + (e % 6) * (TB >> 4) + (n & 1) * 768 + (kk >> 1) * 384 + (kk & 1) * 64), 1);
      WG_COMMIT();
      if ((!(n & 1) && n <= 16) || n == 15 || n == LQ + 1) WG_WAIT(1);
      if (n == 0) rel_a(24);
      if (!(n & 1) && n <= 10) rel_b(8 * ((e - 1) % 6));
      if (n == Q2N) take(q2, aF + 40);
      if (n == 10) cluster_arrive();
      if (n == 12 || n == 14 || n == 16) rel_a(4u * n - 48);
      if (n == LQ + 1) reg_fence(q1);
      if (n == 10) reg_fence(q2);
      if (n == 15) reg_fence(oth);
      if (n == 15) while (!(fb(150) & fb(151))) {}
      static_for<sent(n + 1) - sent(n)>([&](auto k_) { send(sent(n) + k_.value); });
      if (n == 8) {
        reg_fence(aS);
#pragma unroll
        for (int k = 0; k < 40; k++) oth[k] = kq & 1 ? aS[k] : aS[40 + k];
        reg_fence(oth);
      }
      if (n == SWN) {
        reg_fence(aS);
#pragma unroll
        for (int k = 0; k < 40; k++) own[k] = kq & 1 ? aS[40 + k] : aS[k];
        reg_fence(own);
      }
    });
    uint32_t xr[20];
    const uint32_t xs = sb + OFF_B + 2 * TB + cw * 2560, xa = xs + (lane & 15) * 160 + (lane >> 4) * 16;
    mbar_wait(bar_b + 16, 1);
#pragma unroll
    for (int k = 0; k < 5; k++) ldsm4(xa + 32 * k, xr + 4 * k);
    {
      auto fetch = [&](int e, uint4 (&v)[5]) {
        mbar_wait(bar_e + 16 * e + 8 * w, 0);
#pragma unroll
        for (int i = 0; i < 5; i++) v[i] = lds128(sb + OFF_B + (3 + e) * TB + (w * 640 + i * 128 + t128) * 16);
      };
      auto add = [&](int e, uint4 (&v)[5]) {
        while (!(v[0].x & v[1].x & v[2].x & v[3].x & v[4].x & 1)) {
#pragma unroll
          for (int i = 0; i < 5; i++) v[i] = ld_pkt(xbase + (kq ^ ((0x132 >> (4 * e)) & 3)) * (48 * 512) + (e < 2 ? kq & 1 : 2) * 1280 + i * 128);
        }
#pragma unroll
        for (int i = 0; i < 5; i++) {
          float* o = own + 8 * i;
          o[0] += bf_lo(v[i].x); o[1] += bf_hi(v[i].x); o[2] += bf_lo(v[i].y); o[3] += bf_hi(v[i].y);
          o[4] += bf_lo(v[i].z); o[5] += bf_hi(v[i].z); o[6] += bf_lo(v[i].w); o[7] += bf_hi(v[i].w);
        }
      };
      WG_WAIT(0);
      reg_fence(own);
#pragma unroll 1
      for (int e = 0; e < 3; e++) { uint4 v[5]; fetch(e, v); add(e, v); }
      if (lane == 0) mbar_arrive(bar_w);
#pragma unroll
      for (int i = 0; i < 20; i++) xr[i] = hadd2(xr[i], hmul2(pack_bf16(own[2 * i], own[2 * i + 1]), fr[i]));
#pragma unroll
      for (int k = 0; k < 5; k++) stsm4(xa + 32 * k, xr + 4 * k);
      asm volatile("fence.proxy.async.shared::cta;" ::: "memory");
      __syncwarp();
      if (elect()) {
        tma2d_store(&tm_out, xs, nh * 320 + kq * 80, qt * 128 + cw * 16);
        asm volatile("cp.async.bulk.commit_group;\ncp.async.bulk.wait_group.read 0;" ::: "memory");
      }
      __syncwarp();
    }
    cluster_wait();
  } else {
    asm volatile("setmaxnreg.dec.sync.aligned.u32 40;");
    uint32_t tid_; asm volatile("mov.u32 %0, %%tid.x;" : "=r"(tid_));
    const int warp = __shfl_sync(~0u, tid_ >> 5, 0);
    auto is_warp = [&](int k) { uint32_t e; asm volatile("{\n.reg .pred q;\nsetp.eq.u32 q, %1, %2;\nselp.u32 %0, 1, 0, q;\n}" : "=r"(e) : "r"(warp), "r"(k)); return e != 0; };
    auto k_block = [&](int t) {
      const int i = (t * 11) >> 5;
      return ((i < 6 ? 2 * kq + (i & 1) : hg ^ (i & 1)) * 4 + (i >> 1)) * 6 + (t == 3 * i ? 4 : 2 * (t - 3 * i) - 2);
    };
    if (warp > 0) {
      const unsigned epoch = (unsigned)(__ldcg(&p.s->done) >> 7);
      int budget = WAIT_BUDGET;
      cluster_wait();
      const uint32_t tag = epoch + 1;
      mbar_wait(bar_b, 0, budget); mbar_wait(bar_b + 8, 0, budget);
      float cs0 = 0.f, cs1 = 0.f;
      const int n = rank * 96 + (warp - 1) * 32 + (lane & 15) * 2;
#pragma unroll 1
      for (int kg = ((qt >> 1) & 3) * 2 + (lane >> 4) * 5, e = kg + 5; kg < e; kg++) {
        const uint32_t ad = sb + OFF_B + kg * 3072 + (n >> 6) * 1024 + (n & 63) * 2;
#pragma unroll
        for (int k = 0; k < 8; k++) { const uint32_t v = lds32(ad ^ (k * 0x90)); cs0 += bf_lo(v); cs1 += bf_hi(v); }
      }
      cs0 += __shfl_xor_sync(~0u, cs0, 16); cs1 += __shfl_xor_sync(~0u, cs1, 16);
      if (lane < 16)
        asm volatile("{\n.reg .b64 v;\nmov.b64 v, {%1, %2};\nst.relaxed.gpu.global.b64 [%0], v;\n}\n" ::"l"((uint2*)(p.s->cs + (hg * 4 + (qt >> 2)) * 96 + (n >> 1)) + ((qt >> 1) & 1)),
                     "r"((__float_as_uint(cs0) & ~3u) | (tag & 3)), "r"(__float_as_uint(cs1)) : "memory");
      mbar_wait(bar_a + 40, 0, budget);
      if (lane < 2) { uint32_t a; asm volatile("mapa.shared::cluster.u32 %0, %1, %2;" : "=r"(a) : "r"(bar_d), "r"(lane)); mbar_arrive_cluster(a); }
      cs0 = cs1 = 0.f;
      for (const uint32_t c0 = clock(); clock() - c0 < CSW;) {}
#pragma unroll 1
      for (int e = 0; e < 2; e++) {
        if (e) {
          mbar_wait(bar_a + 40, 1, budget);
#pragma unroll 1
          for (int k = 0; k < 8; k++) {
            const uint32_t v = pack_bf16(cs0, cs1);
            sts32((sb + ((tid_ - 32) >> 5) * 1024 + lane * 4) ^ (k * 0x90), k < 3 ? v : 0);
            cs0 -= bf_lo(v); cs1 -= bf_hi(v);
          }
          if (!is_warp(3)) break;
        }
        const uint4* src = e ? p.s->stat + qt * 128 + lane : p.s->cs + hg * 4 * 96 + (tid_ - 32);
        const int step = e ? 32 : 96;
        uint4 v[4];
        while (true) {
          uint32_t bad = 0;
#pragma unroll
          for (int i = 0; i < 4; i++) v[i] = ld_pkt(src + i * step);
#pragma unroll
          for (int i = 0; i < 4; i++) bad |= (v[i].x ^ tag) | (v[i].z ^ tag);
          if (!__any_sync(~0u, bad & 3) || --budget < 0) break;
        }
#pragma unroll
        for (int i = 0; i < 4; i++) {
          cs0 += __uint_as_float(v[i].x & ~3u) + __uint_as_float(v[i].z & ~3u); cs1 += __uint_as_float(v[i].y) + __uint_as_float(v[i].w);
          if (e) asm volatile("st.shared.v2.u32 [%0], {%1,%2};" ::"r"(s_stat + (i * 32 + lane) * 8), "r"(v[i].w), "r"(v[i].y) : "memory");
        }
      }
      asm volatile("fence.proxy.async.shared::cta;" ::: "memory");
      __syncwarp();
      if (lane == 0) mbar_arrive(bar_s);
      if (is_warp(1)) {
#pragma unroll 1
        for (int u = 0; u < 5; u++) {
          mbar_wait(bar_o, u & 1);
          if (lane == 0) red_release(&p.s->flag[u ? FL_O + (qt * 8 + hg) * 8 : FL_XN + qt * 32]);
          __syncwarp();
        }
      } else if (is_warp(2)) {
        mbar_wait(bar_x, 0, budget);
        while ((int)(ld_acquire(&p.s->flag[FL_FFN]) - tag) < 0 && --budget >= 0) {}
        if (lane < 21) {
          const uint4 v = __ldcg(lane ? (const uint4*)(p.s->gsel + (lane > 10 ? DM - 80 : 0) + nh * 320 + kq * 80) + lane - 1 : (const uint4*)p.s->sel);
          asm volatile("st.shared.v4.u32 [%0], {%1,%2,%3,%4};" ::"r"(s_sel + 16 * lane), "r"(v.x), "r"(v.y), "r"(v.z), "r"(v.w) : "memory");
        }
        __syncwarp();
        if (lane == 0) { mbar_arrive(bar_u); asm volatile("red.relaxed.gpu.global.add.u64 [%0], 1;" ::"l"(&p.s->done) : "memory"); }
        while ((int)(ld_acquire(&p.s->flag[FL_RD + (qt * 8 + (hg ^ 1)) * 8]) - tag) < 0 && --budget >= 0) __nanosleep(200);
        if (lane == 0) mbar_arrive(bar_z);
        mbar_wait(bar_w, 0, budget);
        if (budget < 0) asm volatile("st.global.u32 [%0], %1;" ::"l"(0ull), "r"(budget) : "memory");
      } else {
        wait_flag(&p.s->flag[FL_XN + qt * 32], (epoch + 1) * 8);
        fence_proxy_async();
        mbar_wait(bar_a + 72, 1);
        uint32_t a8 = 0, pha = 1;
        const int kb = (qt * 192 + k_block(lane)) * 512;
#pragma unroll 1
        for (int n = 0; n < 54; n++) {
          const int t = n - 30, ko = __shfl_sync(~0u, kb, t);
          if (t == 0 || t == 18) {
            wait_flag(&p.s->flag[FL_O + (qt * 8 + (t ? 2 * kq + (lane & 1) : lane & 7)) * 8], epoch * 4 + (t ? 4 : 3));
            fence_proxy_async();
          }
          mbar_wait(bar_a + 40 + a8, pha);
          const uint32_t fb = bar_a + a8, dst = sb + a8 * (TA >> 3);
          if (elect()) {
            if (t >= 0) {
              mbar_expect_tx(fb, TA);
              bulk_load(dst, p.s->o + ko, TA, fb);
              if (t == 8) {
                mbar_expect_tx(bar_x, 6 * 3840);
#pragma unroll 1
                for (int e = 0; e < 6; e++) tma2d(sb + OFF_B + TW + e * TB, &tm_xg, nh * 320 + kq * 80, qt * 128 + e * 24, bar_x);
                asm volatile("prefetch.tensormap [%0];\nprefetch.tensormap [%1];\nprefetch.tensormap [%2];\nprefetch.tensormap [%3];"
                             ::"l"(tm_w), "l"(tm_w + 1), "l"(&tm_xe), "l"(&tm_out) : "memory");
              }
              if (t == 22) asm volatile("red.relaxed.gpu.global.add.u32 [%0], 1;" ::"l"(&p.s->flag[FL_RD + (qt * 8 + hg) * 8]) : "memory");
            } else if (n >= 10 && pha) mbar_arrive(fb);
            else { mbar_expect_tx(fb, TA); tma2d(dst, &tm_xn, 8 * a8 + (pha || (n >= 15 && n < 20) ? 0 : 320), qt * 128, fb); }
          }
          a8 += 8; if (a8 == 40) { a8 = 0; pha ^= 1; }
        }
        if (lane == 0) mbar_arrive(bar_z);
      }
    } else {
      cluster_wait();
      uint32_t fb = bar_b, dst = sb + OFF_B, ph = 1;
      auto next = [&]() { fb += 8; dst += TB; if (fb == bar_b + 48) { fb = bar_b; dst = sb + OFF_B; ph ^= 1; } };
#pragma unroll 1
      for (int u = 0; u < 4; u++) {
        const int h = hg * 4 + u;
        int s = u ? (u == 2 ? 5 : 0) : (5 * (qt >> 1)) >> 2;
#pragma unroll 1
        for (int i = 0; i < 10; i++) {
          if (u == 0) {
            const uint32_t a8 = 8 * (i < 5 ? i : i - 5);
            if (D0 && i >= D0) { const int j = i - D0; mbar_wait(bar_a + 8 * (j < 5 ? j : j - 5), j >= 5); }
            mbar_wait(bar_a + 40 + a8, i < 5);
            if (elect()) { mbar_expect_tx(bar_a + a8, TA); tma2d(sb + a8 * (TA >> 3), &tm_x, 64 * s, qt * 128, bar_a + a8); }
            if (i == 6) mbar_wait(bar_d, 0);
          }
          mbar_wait(fb + 48, ph);
          if (elect()) { mbar_expect_tx(fb, TB); tma4d_mc(dst + rank * (TB / 2), &tm_wq, 3 * h, 8 * s + 4 * rank, fb); }
          next();
          if (++s == 10) s = 0;
        }
        const int kv0 = (h * SKC + (SKC - WIN)) / 8 + 4 * rank;
#pragma unroll 1
        for (int i = 0; i < 16; i++) {
          const bool isk = (0x2AAB >> i) & 1;
          mbar_wait(fb + 48, ph);
          if (elect()) { mbar_expect_tx(fb, TB); tma4d_mc(dst + rank * (TB / 2), isk ? &tm_k : &tm_v, 0, kv0 + 8 * (isk ? (i + 1) >> 1 : (i - 1) >> 1), fb); }
          next();
        }
      }
      const int cF = 10 * nh + 5 - 5 * (kq >> 1), cS = 10 * nh + 5 * (kq >> 1);
      const int kb = 4 * (k_block(lane) + rank);
#pragma unroll 1
      for (int m = 0; m < 38; m++) {
        const int c2 = __shfl_sync(~0u, kb, m >> 1);
        mbar_wait(fb + 48, ph);
        if (elect()) { mbar_expect_tx(fb, TW); tma5d_mc(dst + rank * (TW / 2), &tm_wo, c2, m & 1 ? cS : cF, fb); }
        next();
      }
      const int odd = (((0x7ff0 ^ 1 << LQ) ^ (kq & 1 ? 0xffc00 : 0)) >> lane) & 1;
      const int tq = __shfl_sync(~0u, kb, 19 + end_stage(lane)) << 16 | odd << 7 | ((lane < 10 ? cF : cS) + 2 * odd);
#pragma unroll 1
      for (int n = 0; n < 20; n += 2) {
        const int t0 = __shfl_sync(~0u, tq, n), t1 = __shfl_sync(~0u, tq, n + 1);
        mbar_wait(fb + 48, ph);
        if (elect()) {
          mbar_expect_tx(fb, TB);
          tma5d_mc(dst + rank * (TB / 4), (const CUtensorMap*)((const char*)tm_w + (t0 & 128)), t0 >> 16, t0 & 31, fb);
          tma5d_mc(dst + TB / 2 + rank * (TB / 4), (const CUtensorMap*)((const char*)tm_w + (t1 & 128)), t1 >> 16, t1 & 31, fb);
        }
        next();
      }
      mbar_wait(fb + 48, ph);
      if (elect()) { mbar_expect_tx(fb, TW); tma2d(dst, &tm_xe, nh * 320 + kq * 80, qt * 128, fb); }
    }
    if (!is_warp(2)) {
      const int e = warp - (warp >> 1), ms = 2 * e + ((lane >> 2) & 1);
      const uint4* src = p.s->o + (size_t)(qt * 192 + nh * 24 + 10 + (kq ^ ((0x132 >> (4 * e)) & 3)) * 48) * 512 + (e < 2 ? kq & 1 : 2) * 1280 + (ms & 1) * 640;
      uint32_t todo = 0xff;
      bool ok = lane >= 8;
      mbar_wait(bar_z, 0);
#pragma unroll 1
      while (todo) {
        if (!ok) ok = ld_pkt(src + 4 * 128 + (lane & 3) * 32 + 31).x & 1;
        const uint32_t got = __ballot_sync(~0u, ok) & todo, go = __ballot_sync(~0u, ((got >> (lane & 28)) & 15) == 15);
        if (go) mbar_wait(bar_a + 40 + 8 * e, 0);
        if ((go & 0x11) >> lane & 1) {
          mbar_expect_tx(bar_e + 8 * ms, TW / 2); bulk_load(sb + OFF_B + (3 + e) * TB + (ms & 1) * (TW / 2), src, TW / 2, bar_e + 8 * ms);
        }
        todo &= ~go;
      }
    }
    cluster_sync();
  }
}

typedef CUresult (*EncodeFn)(CUtensorMap*, CUtensorMapDataType, cuuint32_t, void*, const cuuint64_t*, const cuuint64_t*,
                             const cuuint32_t*, const cuuint32_t*, CUtensorMapInterleave, CUtensorMapSwizzle,
                             CUtensorMapL2promotion, CUtensorMapFloatOOBfill);

void encode(EncodeFn fn, CUtensorMap* tm, void* base, int rank, const cuuint64_t* dims, const cuuint64_t* strides,
            const cuuint32_t* box, CUtensorMapSwizzle sw) {
  const cuuint32_t es[5] = {1, 1, 1, 1, 1};
  fn(tm, CU_TENSOR_MAP_DATA_TYPE_BFLOAT16, rank, base, dims, strides, box, es, CU_TENSOR_MAP_INTERLEAVE_NONE, sw,
     CU_TENSOR_MAP_L2_PROMOTION_L2_128B, CU_TENSOR_MAP_FLOAT_OOB_FILL_NONE);
}

}

extern "C" void kernel_launch(void* const* d_in, const int* in_sizes, int n_in, void* d_out, int out_size) {
  static EncodeFn fn = nullptr;
  static Scratch* scr = nullptr;
  if (!fn) {
    void* f = nullptr;
    cudaDriverEntryPointQueryResult st;
    cudaGetDriverEntryPoint("cuTensorMapEncodeTiled", &f, cudaEnableDefault, &st);
    fn = (EncodeFn)f;
    cudaGetSymbolAddress((void**)&scr, g_scratch);
    cudaFuncSetAttribute(fused_kernel, cudaFuncAttributeMaxDynamicSharedMemorySize, SMEM_BYTES);
  }
  CUtensorMap tm_x, tm_xn, tm_wq, tm_k, tm_v, tm_wo, tm_xg, tm_xe, tm_out;
  MapPair tm_w2;
  { const cuuint64_t d[2] = {DM, SQ}, s[1] = {DM * 2}; const cuuint32_t b[2] = {64, 128};
    encode(fn, &tm_x, d_in[0], 2, d, s, b, CU_TENSOR_MAP_SWIZZLE_128B);
    encode(fn, &tm_xn, scr->xn, 2, d, s, b, CU_TENSOR_MAP_SWIZZLE_128B); }
  { const cuuint64_t d[4] = {64, 8, QD / 64, DM / 8}, s[3] = {QD * 2, 128, 8 * QD * 2}; const cuuint32_t b[4] = {64, 8, 3, 4};
    encode(fn, &tm_wq, d_in[3], 4, d, s, b, CU_TENSOR_MAP_SWIZZLE_128B); }
  { const cuuint64_t d[4] = {64, 8, 3, NH * SKC / 8}, s[3] = {DH * 2, 128, 8 * DH * 2}; const cuuint32_t b[4] = {64, 8, 3, 4};
    encode(fn, &tm_k, d_in[1], 4, d, s, b, CU_TENSOR_MAP_SWIZZLE_128B);
    encode(fn, &tm_v, d_in[2], 4, d, s, b, CU_TENSOR_MAP_SWIZZLE_128B); }
  {
    const cuuint64_t d[5] = {32, 2, QD / 8, 4, DM / 32}, s[4] = {DM * 2, 8 * DM * 2, 2 * DM * 2, 64}; const cuuint32_t b[5] = {32, 2, 4, 4, 5};
    encode(fn, &tm_wo, d_in[4], 5, d, s, b, CU_TENSOR_MAP_SWIZZLE_64B);
    const cuuint32_t b3[5] = {32, 2, 4, 4, 3};
    encode(fn, &tm_w2.m[0], d_in[4], 5, d, s, b3, CU_TENSOR_MAP_SWIZZLE_64B);
    encode(fn, &tm_w2.m[1], (char*)d_in[4] + 32, 5, d, s, b3, CU_TENSOR_MAP_SWIZZLE_64B); }
  { const cuuint64_t d[2] = {DM, SQ}, s[1] = {DM * 2}; const cuuint32_t bg[2] = {80, 24}, bx[2] = {80, 128}, bo[2] = {80, 16};
    encode(fn, &tm_xg, d_in[0], 2, d, s, bg, CU_TENSOR_MAP_SWIZZLE_NONE);
    encode(fn, &tm_xe, d_in[0], 2, d, s, bx, CU_TENSOR_MAP_SWIZZLE_NONE);
    encode(fn, &tm_out, d_out, 2, d, s, bo, CU_TENSOR_MAP_SWIZZLE_NONE); }
  Params p;
  p.x = (const __nv_bfloat16*)d_in[0]; p.wr = (const __nv_bfloat16*)d_in[6]; p.wg = (const __nv_bfloat16*)d_in[7];
  p.wu = (const __nv_bfloat16*)d_in[8]; p.wd = (const __nv_bfloat16*)d_in[9];

  p.k = (const __nv_bfloat16*)d_in[1]; p.v = (const __nv_bfloat16*)d_in[2]; p.s = scr;
  cudaLaunchConfig_t cfg = {};
  cfg.gridDim = dim3(132); cfg.blockDim = dim3(384); cfg.dynamicSmemBytes = SMEM_BYTES; cfg.stream = cudaStreamPerThread;
  cudaLaunchAttribute at[1];
  at[0].id = cudaLaunchAttributeClusterDimension; at[0].val.clusterDim.x = 2; at[0].val.clusterDim.y = 1; at[0].val.clusterDim.z = 1;
  cfg.attrs = at; cfg.numAttrs = 1;
  cudaLaunchKernelEx(&cfg, fused_kernel, p, tm_x, tm_xn, tm_wq, tm_k, tm_v, tm_wo, tm_w2, tm_xg, tm_xe, tm_out);
}
```

```cpp
#include <cuda_runtime.h>
#include <cuda_bf16.h>
#include <cuda.h>
#include <stdint.h>

namespace {

constexpr int SQ = 2048, DM = 640, NH = 32, DH = 192, SKC = 2048, WIN = 512, FF = 1536;
constexpr int QD = NH * DH;
constexpr uint32_t TA = 16384, TB = 24576, TW = 20480, OFF_B = 5 * TA, OFF_M = OFF_B + 6 * TB, SMEM_BYTES = OFF_M + 3072;
constexpr int WAIT_BUDGET = 1 << 20;

constexpr int FL_XN = 0;
constexpr int FL_O = 512;
constexpr int FL_RD = FL_O + 1024;
constexpr int FL_FFN = FL_RD + 1024;
constexpr int FL_SIDE = FL_FFN + 32;
struct __align__(1024) Scratch {
  unsigned long long done, pad0[15];
  unsigned flag[FL_SIDE + 32];
  uint4 cand[8];
  float ffn[4 * 2 * DM];
  int sel[4];
  __nv_bfloat16 gsel[2 * DM];
  uint4 cs[8 * 4 * DH / 2];
  uint4 stat[SQ];
  __align__(1024) __nv_bfloat16 xn[SQ * DM];
  __align__(1024) uint4 o[SQ * QD / 8];
};
__device__ Scratch g_scratch;

__device__ __forceinline__ uint32_t smem_u32(const void* p) { return (uint32_t)__cvta_generic_to_shared(p); }
__device__ __forceinline__ void mbar_init(uint32_t bar, int cnt) { asm volatile("mbarrier.init.shared::cta.b64 [%0], %1;" ::"r"(bar), "r"(cnt)); }
__device__ __forceinline__ void mbar_expect_tx(uint32_t bar, uint32_t bytes) {
  asm volatile("mbarrier.arrive.expect_tx.shared::cta.b64 _, [%0], %1;" ::"r"(bar), "r"(bytes) : "memory");
}
__device__ __forceinline__ void mbar_arrive(uint32_t bar) { asm volatile("mbarrier.arrive.shared::cta.b64 _, [%0];" ::"r"(bar) : "memory"); }
__device__ __forceinline__ void mbar_arrive_cluster(uint32_t addr) { asm volatile("mbarrier.arrive.shared::cluster.b64 _, [%0];" ::"r"(addr) : "memory"); }
__device__ __forceinline__ bool mbar_try(uint32_t bar, uint32_t parity) {
  uint32_t ok;
  asm volatile("{\n.reg .pred p;\nmbarrier.try_wait.parity.shared::cta.b64 p, [%1], %2;\nselp.u32 %0, 1, 0, p;\n}\n" : "=r"(ok) : "r"(bar), "r"(parity) : "memory");
  return ok;
}
__device__ __forceinline__ void mbar_wait(uint32_t bar, uint32_t parity, int& budget) {
#pragma unroll 1
  while (!mbar_try(bar, parity)) { if (--budget < 0) break; }
}
__device__ __forceinline__ void mbar_wait(uint32_t bar, uint32_t parity) {
#pragma unroll 1
  while (!mbar_try(bar, parity)) {}
}
__device__ __forceinline__ unsigned ld_acquire(const unsigned* p) { unsigned v; asm volatile("ld.acquire.gpu.global.u32 %0, [%1];" : "=r"(v) : "l"(p) : "memory"); return v; }
__device__ __forceinline__ void wait_flag(const unsigned* p, unsigned target) {
#pragma unroll 1
  while (__any_sync(~0u, (int)(ld_acquire(p) - target) < 0)) {}
}
__device__ __forceinline__ void red_release(unsigned* p) { asm volatile("red.release.gpu.global.add.u32 [%0], 1;" ::"l"(p) : "memory"); }
__device__ __forceinline__ void fence_proxy_async() { asm volatile("fence.proxy.async.global;" ::: "memory"); }
__device__ __forceinline__ bool elect() {
  uint32_t p;
  asm volatile("{\n.reg .pred P;\nelect.sync _|P, 0xffffffff;\nselp.u32 %0, 1, 0, P;\n}\n" : "=r"(p));
  return p;
}
__device__ __forceinline__ void cluster_arrive() { asm volatile("barrier.cluster.arrive.relaxed.aligned;" ::: "memory"); }
__device__ __forceinline__ void cluster_wait() { asm volatile("barrier.cluster.wait.aligned;" ::: "memory"); }
__device__ __forceinline__ void cluster_sync() { cluster_arrive(); cluster_wait(); }
__device__ __forceinline__ void tma2d(uint32_t dst, const CUtensorMap* tm, int c0, int c1, uint32_t bar) {
  asm volatile("cp.async.bulk.tensor.2d.shared::cluster.global.mbarrier::complete_tx::bytes [%0], [%1, {%3, %4}], [%2];"
               ::"r"(dst), "l"(tm), "r"(bar), "r"(c0), "r"(c1) : "memory");
}
constexpr uint64_t POL_FIRST = 0x12F0000000000000ull;
__device__ __forceinline__ void tma4d_mc(uint32_t dst, const CUtensorMap* tm, int c2, int c3, uint32_t bar) {
  asm volatile("cp.async.bulk.tensor.4d.shared::cluster.global.mbarrier::complete_tx::bytes.multicast::cluster.L2::cache_hint [%0], [%1, {%3, %3, %4, %5}], [%2], %6, %7;"
               ::"r"(dst), "l"(tm), "r"(bar), "r"(0), "r"(c2), "r"(c3), "h"((uint16_t)3), "l"(POL_FIRST) : "memory");
}
__device__ __forceinline__ void tma5d_mc(uint32_t dst, const CUtensorMap* tm, int c2, int c4, uint32_t bar) {
  asm volatile("cp.async.bulk.tensor.5d.shared::cluster.global.mbarrier::complete_tx::bytes.multicast::cluster.L2::cache_hint [%0], [%1, {%3, %3, %4, %3, %5}], [%2], %6, %7;"
               ::"r"(dst), "l"(tm), "r"(bar), "r"(0), "r"(c2), "r"(c4), "h"((uint16_t)3), "l"(POL_FIRST) : "memory");
}
__device__ __forceinline__ void bulk_load(uint32_t dst, const void* src, uint32_t bytes, uint32_t bar) {
  asm volatile("cp.async.bulk.shared::cluster.global.mbarrier::complete_tx::bytes.L2::cache_hint [%0], [%1], %2, [%3], %4;" ::"r"(dst), "l"(src), "r"(bytes), "r"(bar), "l"(POL_FIRST) : "memory");
}
__device__ __forceinline__ void tma2d_store(const CUtensorMap* tm, uint32_t src, int c0, int c1) {
  asm volatile("cp.async.bulk.tensor.2d.global.shared::cta.bulk_group [%0, {%2, %3}], [%1];" ::"l"(tm), "r"(src), "r"(c0), "r"(c1) : "memory");
}
__device__ __forceinline__ uint32_t lds32(uint32_t a) { uint32_t v; asm volatile("ld.shared.u32 %0, [%1];" : "=r"(v) : "r"(a) : "memory"); return v; }
__device__ __forceinline__ uint2 lds64(uint32_t a) { uint2 v; asm volatile("ld.shared.v2.u32 {%0,%1}, [%2];" : "=r"(v.x), "=r"(v.y) : "r"(a) : "memory"); return v; }
__device__ __forceinline__ uint4 lds128(uint32_t a) { uint4 v; asm volatile("ld.shared.v4.u32 {%0,%1,%2,%3}, [%4];" : "=r"(v.x), "=r"(v.y), "=r"(v.z), "=r"(v.w) : "r"(a) : "memory"); return v; }
__device__ __forceinline__ void ldsm4(uint32_t a, uint32_t* v) {
  asm volatile("ldmatrix.sync.aligned.m8n8.x4.shared.b16 {%0,%1,%2,%3}, [%4];" : "=r"(v[0]), "=r"(v[1]), "=r"(v[2]), "=r"(v[3]) : "r"(a) : "memory");
}
__device__ __forceinline__ void stsm4(uint32_t a, const uint32_t* v) {
  asm volatile("stmatrix.sync.aligned.m8n8.x4.shared.b16 [%0], {%1,%2,%3,%4};" ::"r"(a), "r"(v[0]), "r"(v[1]), "r"(v[2]), "r"(v[3]) : "memory");
}
__device__ __forceinline__ void sts32(uint32_t a, uint32_t v) { asm volatile("st.shared.u32 [%0], %1;" ::"r"(a), "r"(v) : "memory"); }
__device__ __forceinline__ void st_pkt(uint4* p, uint32_t a, uint32_t b, uint32_t c, uint32_t d) {
  asm volatile("st.relaxed.gpu.global.v4.b32 [%0], {%1, %2, %3, %4};" ::"l"(p), "r"(a), "r"(b), "r"(c), "r"(d) : "memory");
}
__device__ __forceinline__ uint4 ld_pkt(const uint4* p) {
  uint4 v;
  asm volatile("{\n.reg .b128 v;\nld.relaxed.gpu.global.b128 v, [%4];\nmov.b128 {%0, %1, %2, %3}, v;\n}\n" : "=r"(v.x), "=r"(v.y), "=r"(v.z), "=r"(v.w) : "l"(p) : "memory");
  return v;
}
__device__ __forceinline__ uint4 ldg_nc(const void* p) {
  uint4 v;
  asm volatile("ld.global.nc.v4.u32 {%0,%1,%2,%3}, [%4];" : "=r"(v.x), "=r"(v.y), "=r"(v.z), "=r"(v.w) : "l"(p));
  return v;
}
#define WG_FENCE() asm volatile("wgmma.fence.sync.aligned;" ::: "memory")
#define WG_COMMIT() asm volatile("wgmma.commit_group.sync.aligned;" ::: "memory")
#define WG_WAIT(n) asm volatile("wgmma.wait_group.sync.aligned " #n ";" ::: "memory")
template <int N> __device__ __forceinline__ void reg_fence(float (&d)[N]) {
#pragma unroll
  for (int i = 0; i < N; i++) asm volatile("" : "+f"(d[i])::"memory");
}
template <int N> __device__ __forceinline__ void reg_fence(uint32_t (&d)[N]) {
#pragma unroll
  for (int i = 0; i < N; i++) asm volatile("" : "+r"(d[i])::"memory");
}
__device__ __forceinline__ constexpr uint64_t desc_hi(uint32_t lbo, uint32_t sbo, uint64_t sw) {
  return ((uint64_t)(lbo >> 4) << 16) | ((uint64_t)(sbo >> 4) << 32) | (sw << 62);
}
__device__ __forceinline__ uint64_t mkdesc(uint32_t addr, uint64_t hi) { return hi | (uint64_t)((addr & 0x3FFFF) >> 4); }
__device__ __forceinline__ uint32_t pack_bf16(float lo, float hi) { uint32_t r; asm("cvt.rn.bf16x2.f32 %0, %1, %2;" : "=r"(r) : "f"(hi), "f"(lo)); return r; }
__device__ __forceinline__ float bf_lo(uint32_t v) { return __uint_as_float(v << 16); }
__device__ __forceinline__ float bf_hi(uint32_t v) { return __uint_as_float(v & 0xffff0000u); }
__device__ __forceinline__ uint32_t hadd2(uint32_t a, uint32_t b) { uint32_t r; asm("add.rn.bf16x2 %0, %1, %2;" : "=r"(r) : "r"(a), "r"(b)); return r; }
__device__ __forceinline__ uint32_t hsub2(uint32_t a, uint32_t b) { uint32_t r; asm("sub.rn.bf16x2 %0, %1, %2;" : "=r"(r) : "r"(a), "r"(b)); return r; }
__device__ __forceinline__ uint32_t hmul2(uint32_t a, uint32_t b) { uint32_t r; asm("mul.rn.bf16x2 %0, %1, %2;" : "=r"(r) : "r"(a), "r"(b)); return r; }
__device__ __forceinline__ float rbf(float x) { return __bfloat162float(__float2bfloat16_rn(x)); }
__device__ __forceinline__ float ex2(float x) { float y; asm("ex2.approx.ftz.f32 %0, %1;" : "=f"(y) : "f"(x)); return y; }
__device__ __forceinline__ float rcp(float x) { float y; asm("rcp.approx.ftz.f32 %0, %1;" : "=f"(y) : "f"(x)); return y; }
__device__ __forceinline__ float sigmoid_f(float x) { return rcp(1.f + ex2(x * -1.4426950408889634f)); }
__device__ __forceinline__ float silu_f(float x) { return x * sigmoid_f(x); }

__device__ __forceinline__ void wg_ss192t(float (&d)[96], uint64_t da, uint64_t db, int sd) {
  asm volatile("{\n.reg .pred p;\nsetp.ne.b32 p, %98, 0;\n"
    "wgmma.mma_async.sync.aligned.m64n192k16.f32.bf16.bf16 {%0,%1,%2,%3,%4,%5,%6,%7,%8,%9,%10,%11,%12,%13,%14,%15,%16,%17,%18,%19,%20,%21,%22,%23,%24,%25,%26,%27,%28,%29,%30,%31,%32,%33,%34,%35,%36,%37,%38,%39,%40,%41,%42,%43,%44,%45,%46,%47,%48,%49,%50,%51,%52,%53,%54,%55,%56,%57,%58,%59,%60,%61,%62,%63,%64,%65,%66,%67,%68,%69,%70,%71,%72,%73,%74,%75,%76,%77,%78,%79,%80,%81,%82,%83,%84,%85,%86,%87,%88,%89,%90,%91,%92,%93,%94,%95}, %96, %97, p, 1, 1, 0, 1;\n}\n"
    : "+f"(d[0]),"+f"(d[1]),"+f"(d[2]),"+f"(d[3]),"+f"(d[4]),"+f"(d[5]),"+f"(d[6]),"+f"(d[7]),"+f"(d[8]),"+f"(d[9]),"+f"(d[10]),"+f"(d[11]),"+f"(d[12]),"+f"(d[13]),"+f"(d[14]),"+f"(d[15]),"+f"(d[16]),"+f"(d[17]),"+f"(d[18]),"+f"(d[19]),"+f"(d[20]),"+f"(d[21]),"+f"(d[22]),"+f"(d[23]),"+f"(d[24]),"+f"(d[25]),"+f"(d[26]),"+f"(d[27]),"+f"(d[28]),"+f"(d[29]),"+f"(d[30]),"+f"(d[31]),"+f"(d[32]),"+f"(d[33]),"+f"(d[34]),"+f"(d[35]),"+f"(d[36]),"+f"(d[37]),"+f"(d[38]),"+f"(d[39]),"+f"(d[40]),"+f"(d[41]),"+f"(d[42]),"+f"(d[43]),"+f"(d[44]),"+f"(d[45]),"+f"(d[46]),"+f"(d[47]),"+f"(d[48]),"+f"(d[49]),"+f"(d[50]),"+f"(d[51]),"+f"(d[52]),"+f"(d[53]),"+f"(d[54]),"+f"(d[55]),"+f"(d[56]),"+f"(d[57]),"+f"(d[58]),"+f"(d[59]),"+f"(d[60]),"+f"(d[61]),"+f"(d[62]),"+f"(d[63]),"+f"(d[64]),"+f"(d[65]),"+f"(d[66]),"+f"(d[67]),"+f"(d[68]),"+f"(d[69]),"+f"(d[70]),"+f"(d[71]),"+f"(d[72]),"+f"(d[73]),"+f"(d[74]),"+f"(d[75]),"+f"(d[76]),"+f"(d[77]),"+f"(d[78]),"+f"(d[79]),"+f"(d[80]),"+f"(d[81]),"+f"(d[82]),"+f"(d[83]),"+f"(d[84]),"+f"(d[85]),"+f"(d[86]),"+f"(d[87]),"+f"(d[88]),"+f"(d[89]),"+f"(d[90]),"+f"(d[91]),"+f"(d[92]),"+f"(d[93]),"+f"(d[94]),"+f"(d[95])
    : "l"(da), "l"(db), "r"(sd));
}
__device__ __forceinline__ void wg_rs64(float (&d)[32], uint32_t a0, uint32_t a1, uint32_t a2, uint32_t a3, uint64_t db, int sd) {
  asm volatile("{\n.reg .pred p;\nsetp.ne.b32 p, %37, 0;\n"
    "wgmma.mma_async.sync.aligned.m64n64k16.f32.bf16.bf16 {%0,%1,%2,%3,%4,%5,%6,%7,%8,%9,%10,%11,%12,%13,%14,%15,%16,%17,%18,%19,%20,%21,%22,%23,%24,%25,%26,%27,%28,%29,%30,%31}, {%32,%33,%34,%35}, %36, p, 1, 1, 0;\n}\n"
    : "+f"(d[0]),"+f"(d[1]),"+f"(d[2]),"+f"(d[3]),"+f"(d[4]),"+f"(d[5]),"+f"(d[6]),"+f"(d[7]),"+f"(d[8]),"+f"(d[9]),"+f"(d[10]),"+f"(d[11]),"+f"(d[12]),"+f"(d[13]),"+f"(d[14]),"+f"(d[15]),"+f"(d[16]),"+f"(d[17]),"+f"(d[18]),"+f"(d[19]),"+f"(d[20]),"+f"(d[21]),"+f"(d[22]),"+f"(d[23]),"+f"(d[24]),"+f"(d[25]),"+f"(d[26]),"+f"(d[27]),"+f"(d[28]),"+f"(d[29]),"+f"(d[30]),"+f"(d[31])
    : "r"(a0), "r"(a1), "r"(a2), "r"(a3), "l"(db), "r"(sd));
}
__device__ __forceinline__ void wg_rs192t(float (&d)[96], uint32_t a0, uint32_t a1, uint32_t a2, uint32_t a3, uint64_t db, int sd) {
  asm volatile("{\n.reg .pred p;\nsetp.ne.b32 p, %101, 0;\n"
    "wgmma.mma_async.sync.aligned.m64n192k16.f32.bf16.bf16 {%0,%1,%2,%3,%4,%5,%6,%7,%8,%9,%10,%11,%12,%13,%14,%15,%16,%17,%18,%19,%20,%21,%22,%23,%24,%25,%26,%27,%28,%29,%30,%31,%32,%33,%34,%35,%36,%37,%38,%39,%40,%41,%42,%43,%44,%45,%46,%47,%48,%49,%50,%51,%52,%53,%54,%55,%56,%57,%58,%59,%60,%61,%62,%63,%64,%65,%66,%67,%68,%69,%70,%71,%72,%73,%74,%75,%76,%77,%78,%79,%80,%81,%82,%83,%84,%85,%86,%87,%88,%89,%90,%91,%92,%93,%94,%95}, {%96,%97,%98,%99}, %100, p, 1, 1, 1;\n}\n"
    : "+f"(d[0]),"+f"(d[1]),"+f"(d[2]),"+f"(d[3]),"+f"(d[4]),"+f"(d[5]),"+f"(d[6]),"+f"(d[7]),"+f"(d[8]),"+f"(d[9]),"+f"(d[10]),"+f"(d[11]),"+f"(d[12]),"+f"(d[13]),"+f"(d[14]),"+f"(d[15]),"+f"(d[16]),"+f"(d[17]),"+f"(d[18]),"+f"(d[19]),"+f"(d[20]),"+f"(d[21]),"+f"(d[22]),"+f"(d[23]),"+f"(d[24]),"+f"(d[25]),"+f"(d[26]),"+f"(d[27]),"+f"(d[28]),"+f"(d[29]),"+f"(d[30]),"+f"(d[31]),"+f"(d[32]),"+f"(d[33]),"+f"(d[34]),"+f"(d[35]),"+f"(d[36]),"+f"(d[37]),"+f"(d[38]),"+f"(d[39]),"+f"(d[40]),"+f"(d[41]),"+f"(d[42]),"+f"(d[43]),"+f"(d[44]),"+f"(d[45]),"+f"(d[46]),"+f"(d[47]),"+f"(d[48]),"+f"(d[49]),"+f"(d[50]),"+f"(d[51]),"+f"(d[52]),"+f"(d[53]),"+f"(d[54]),"+f"(d[55]),"+f"(d[56]),"+f"(d[57]),"+f"(d[58]),"+f"(d[59]),"+f"(d[60]),"+f"(d[61]),"+f"(d[62]),"+f"(d[63]),"+f"(d[64]),"+f"(d[65]),"+f"(d[66]),"+f"(d[67]),"+f"(d[68]),"+f"(d[69]),"+f"(d[70]),"+f"(d[71]),"+f"(d[72]),"+f"(d[73]),"+f"(d[74]),"+f"(d[75]),"+f"(d[76]),"+f"(d[77]),"+f"(d[78]),"+f"(d[79]),"+f"(d[80]),"+f"(d[81]),"+f"(d[82]),"+f"(d[83]),"+f"(d[84]),"+f"(d[85]),"+f"(d[86]),"+f"(d[87]),"+f"(d[88]),"+f"(d[89]),"+f"(d[90]),"+f"(d[91]),"+f"(d[92]),"+f"(d[93]),"+f"(d[94]),"+f"(d[95])
    : "r"(a0), "r"(a1), "r"(a2), "r"(a3), "l"(db), "r"(sd));
}
__device__ __forceinline__ void wg_ss160t(float (&d)[80], uint64_t da, uint64_t db, int sd) {
  asm volatile("{\n.reg .pred p;\nsetp.ne.b32 p, %82, 0;\n"
    "wgmma.mma_async.sync.aligned.m64n160k16.f32.bf16.bf16 {%0,%1,%2,%3,%4,%5,%6,%7,%8,%9,%10,%11,%12,%13,%14,%15,%16,%17,%18,%19,%20,%21,%22,%23,%24,%25,%26,%27,%28,%29,%30,%31,%32,%33,%34,%35,%36,%37,%38,%39,%40,%41,%42,%43,%44,%45,%46,%47,%48,%49,%50,%51,%52,%53,%54,%55,%56,%57,%58,%59,%60,%61,%62,%63,%64,%65,%66,%67,%68,%69,%70,%71,%72,%73,%74,%75,%76,%77,%78,%79}, %80, %81, p, 1, 1, 0, 1;\n}\n"
    : "+f"(d[0]),"+f"(d[1]),"+f"(d[2]),"+f"(d[3]),"+f"(d[4]),"+f"(d[5]),"+f"(d[6]),"+f"(d[7]),"+f"(d[8]),"+f"(d[9]),"+f"(d[10]),"+f"(d[11]),"+f"(d[12]),"+f"(d[13]),"+f"(d[14]),"+f"(d[15]),"+f"(d[16]),"+f"(d[17]),"+f"(d[18]),"+f"(d[19]),"+f"(d[20]),"+f"(d[21]),"+f"(d[22]),"+f"(d[23]),"+f"(d[24]),"+f"(d[25]),"+f"(d[26]),"+f"(d[27]),"+f"(d[28]),"+f"(d[29]),"+f"(d[30]),"+f"(d[31]),"+f"(d[32]),"+f"(d[33]),"+f"(d[34]),"+f"(d[35]),"+f"(d[36]),"+f"(d[37]),"+f"(d[38]),"+f"(d[39]),"+f"(d[40]),"+f"(d[41]),"+f"(d[42]),"+f"(d[43]),"+f"(d[44]),"+f"(d[45]),"+f"(d[46]),"+f"(d[47]),"+f"(d[48]),"+f"(d[49]),"+f"(d[50]),"+f"(d[51]),"+f"(d[52]),"+f"(d[53]),"+f"(d[54]),"+f"(d[55]),"+f"(d[56]),"+f"(d[57]),"+f"(d[58]),"+f"(d[59]),"+f"(d[60]),"+f"(d[61]),"+f"(d[62]),"+f"(d[63]),"+f"(d[64]),"+f"(d[65]),"+f"(d[66]),"+f"(d[67]),"+f"(d[68]),"+f"(d[69]),"+f"(d[70]),"+f"(d[71]),"+f"(d[72]),"+f"(d[73]),"+f"(d[74]),"+f"(d[75]),"+f"(d[76]),"+f"(d[77]),"+f"(d[78]),"+f"(d[79])
    : "l"(da), "l"(db), "r"(sd));
}
__device__ __forceinline__ void wg_ss80t(float (&d)[40], uint64_t da, uint64_t db, int sd) {
  asm volatile("{\n.reg .pred p;\nsetp.ne.b32 p, %42, 0;\n"
    "wgmma.mma_async.sync.aligned.m64n80k16.f32.bf16.bf16 {%0,%1,%2,%3,%4,%5,%6,%7,%8,%9,%10,%11,%12,%13,%14,%15,%16,%17,%18,%19,%20,%21,%22,%23,%24,%25,%26,%27,%28,%29,%30,%31,%32,%33,%34,%35,%36,%37,%38,%39}, %40, %41, p, 1, 1, 0, 1;\n}\n"
    : "+f"(d[0]),"+f"(d[1]),"+f"(d[2]),"+f"(d[3]),"+f"(d[4]),"+f"(d[5]),"+f"(d[6]),"+f"(d[7]),"+f"(d[8]),"+f"(d[9]),"+f"(d[10]),"+f"(d[11]),"+f"(d[12]),"+f"(d[13]),"+f"(d[14]),"+f"(d[15]),"+f"(d[16]),"+f"(d[17]),"+f"(d[18]),"+f"(d[19]),"+f"(d[20]),"+f"(d[21]),"+f"(d[22]),"+f"(d[23]),"+f"(d[24]),"+f"(d[25]),"+f"(d[26]),"+f"(d[27]),"+f"(d[28]),"+f"(d[29]),"+f"(d[30]),"+f"(d[31]),"+f"(d[32]),"+f"(d[33]),"+f"(d[34]),"+f"(d[35]),"+f"(d[36]),"+f"(d[37]),"+f"(d[38]),"+f"(d[39])
    : "l"(da), "l"(db), "r"(sd));
}

struct MapPair { CUtensorMap m[2]; };
struct Params {
  const __nv_bfloat16 *x, *wr, *wg, *wu, *wd, *k, *v;
  Scratch* s;
};

__device__ __forceinline__ void side_cta(const Params& p, int sc, unsigned epoch, float* sm) {
  const int tid = threadIdx.x, lane = tid & 31, warp = tid >> 5;
  int budget = WAIT_BUDGET;
  float* s_x = sm;
  float* s_red = sm + 1280;
  float* s_h = s_red + 6144;
  uint4* s_c = (uint4*)(s_h + 768);
  uint2* s_st = (uint2*)(s_c + 16);
  constexpr int DEPTH = 7, STEP = 4 * 6144;
  const uint32_t ring = smem_u32(s_st + 512) + tid * 16;
  const int cg = tid % 96, ks = tid / 96, cd = tid % 80, kd = tid / 80;
  const __nv_bfloat16* wp = (cg < 48 ? p.wg : p.wu) + (size_t)(ks * 160) * FF + sc * 384 + (cg % 48) * 8;
  int kf = 0, pitch = FF;
  uint32_t slot = ring;
  auto refill = [&]() {
    if (kf == 40) { wp = p.wd + (size_t)(sc * 384 + kd * 96) * DM + cd * 8; pitch = DM; }
    if (kf < (tid < 320 ? 64 : 40)) {
#pragma unroll
      for (int j = 0; j < 4; j++) asm volatile("cp.async.cg.shared.global.L2::cache_hint [%0], [%1], 16, %2;" ::"r"(slot + j * 6144), "l"(wp + j * pitch), "l"(POL_FIRST) : "memory");
    }
    asm volatile("cp.async.commit_group;" ::: "memory");
    wp += 4 * pitch; kf++;
    slot += STEP; if (slot == ring + DEPTH * STEP) slot = ring;
  };
  auto gemv = [&](int n, const float* x0, const float* x1, float* out) {
    float a[2][8] = {};
#pragma unroll 1
    for (int k = 0; k < n; k += 4) {
      refill();
      asm volatile("cp.async.wait_group %0;" ::"n"(DEPTH - 1) : "memory");
      const float4 f0 = *(const float4*)(x0 + k), f1 = *(const float4*)(x1 + k);
      const float y0[4] = {f0.x, f0.y, f0.z, f0.w}, y1[4] = {f1.x, f1.y, f1.z, f1.w};
#pragma unroll
      for (int j = 0; j < 4; j++) {
        const uint4 v = lds128(slot + j * 6144);
        const uint32_t u[4] = {v.x, v.y, v.z, v.w};
#pragma unroll
        for (int i = 0; i < 4; i++) {
          a[0][2 * i] += y0[j] * bf_lo(u[i]); a[0][2 * i + 1] += y0[j] * bf_hi(u[i]);
          a[1][2 * i] += y1[j] * bf_lo(u[i]); a[1][2 * i + 1] += y1[j] * bf_hi(u[i]);
        }
      }
    }
#pragma unroll
    for (int i = 0; i < 16; i++) out[(i >> 3) * 768 + (i & 7)] = a[i >> 3][i & 7];
  };
  auto load_row = [&](const __nv_bfloat16* r, uint32_t (&v)[10]) {
    const uint4 a = __ldg((const uint4*)r + lane), b = __ldg((const uint4*)r + 32 + lane);
    const uint2 c = __ldg((const uint2*)r + 128 + lane);
    v[0] = a.x; v[1] = a.y; v[2] = a.z; v[3] = a.w; v[4] = b.x; v[5] = b.y; v[6] = b.z; v[7] = b.w; v[8] = c.x; v[9] = c.y;
  };
  uint32_t wr[10], xb[3][10];
  load_row(p.wr, wr);
#pragma unroll 1
  for (int i = tid; i < 512; i += 384) {
    uint4 v;
    do v = ld_pkt(p.s->stat + sc * 512 + i); while (v.x != epoch + 1 && --budget >= 0);
    s_st[i] = make_uint2(v.w, v.y);
  }
  __syncthreads();
#pragma unroll
  for (int b = 0; b < 3; b++) load_row(p.x + (size_t)(sc * 512 + warp + 12 * b) * DM, xb[b]);
#pragma unroll 1
  for (int k = 0; k < DEPTH - 1; k++) refill();
  float v0 = -INFINITY, v1 = -INFINITY; int i0 = 0xfff, i1 = 0xfff;
  auto better = [](float a, int ia, float b, int ib) { return a > b || (a == b && ia < ib); };
  auto push = [&](float v, int i) {
    if (better(v, i, v0, i0)) { v1 = v0; i1 = i0; v0 = v; i0 = i; }
    else if (better(v, i, v1, i1)) { v1 = v; i1 = i; }
  };
  auto push2 = [&](uint4 c) { push(__uint_as_float(c.x), c.y & 0xfff); push(__uint_as_float(c.z), c.w & 0xfff); };
#pragma unroll 1
  for (int l3 = warp; l3 < 512; l3 += 36) {
#pragma unroll
    for (int b = 0; b < 3; b++) {
      const int lr = l3 + 12 * b;
      if (lr >= 512) break;
      const uint2 st = s_st[lr];
      uint32_t v[10];
#pragma unroll
      for (int i = 0; i < 10; i++) v[i] = hsub2(xb[b][i], st.x);
      if (lr + 36 < 512) load_row(p.x + (size_t)(sc * 512 + lr + 36) * DM, xb[b]);
      float r0 = 0.f, r1 = 0.f;
#pragma unroll
      for (int i = 0; i < 10; i++) {
        const uint32_t xn = pack_bf16(bf_lo(v[i]) * __uint_as_float(st.y), bf_hi(v[i]) * __uint_as_float(st.y));
        r0 = fmaf(bf_lo(xn), bf_lo(wr[i]), r0); r1 = fmaf(bf_hi(xn), bf_hi(wr[i]), r1);
      }
      r0 += r1;
#pragma unroll
      for (int o = 16; o > 0; o >>= 1) r0 += __shfl_xor_sync(~0u, r0, o);
      push(rbf(r0), sc * 512 + lr);
    }
  }
  if (lane == 0) s_c[warp] = make_uint4(__float_as_uint(v0), i0, __float_as_uint(v1), i1);
  __syncthreads();
#pragma unroll 1
  for (int w = 1; w < 12; w++) push2(s_c[(warp + w) % 12]);
  const uint32_t tag = (epoch + 1) << 12;
  if (tid == 0) st_pkt(p.s->cand + sc, __float_as_uint(v0), i0 | tag, __float_as_uint(v1), i1);
  {
    uint4 c;
    do c = ld_pkt(p.s->cand + (lane & 3)); while (((c.y ^ tag) >> 12) && --budget >= 0);
#pragma unroll 1
    for (int w = 1; w < 4; w++) { const int o = (sc + w) & 3; push2(make_uint4(__shfl_sync(~0u, c.x, o), __shfl_sync(~0u, c.y, o), __shfl_sync(~0u, c.z, o), __shfl_sync(~0u, c.w, o))); }
  }
  if (i0 >= SQ) i0 = 0;
  if (i1 >= SQ) i1 = (i0 == 0) ? 1 : 0;
  if (tid < 320) {
    const int row = tid < 160 ? i0 : i1;
    const uint2 u = __ldg((const uint2*)(p.x + (size_t)row * DM) + tid % 160);
    uint4 st;
    do st = ld_pkt(p.s->stat + row); while (st.x != epoch + 1 && --budget >= 0);
    const uint32_t d0 = hsub2(u.x, st.w), d1 = hsub2(u.y, st.w);
    const float inv = __uint_as_float(st.y);
    ((float4*)s_x)[tid] = make_float4(rbf(bf_lo(d0) * inv), rbf(bf_hi(d0) * inv), rbf(bf_lo(d1) * inv), rbf(bf_hi(d1) * inv));
  }
  __syncthreads();
  gemv(160, s_x + ks * 160, s_x + DM + ks * 160, s_red + ks * 1536 + cg * 8);
  __syncthreads();
#pragma unroll
  for (int t = 0; t < 2; t++) {
    float g = 0.f, u = 0.f;
#pragma unroll
    for (int k = 0; k < 4; k++) { g += s_red[(k * 2 + t) * 768 + tid]; u += s_red[(k * 2 + t) * 768 + 384 + tid]; }
    s_h[t * 384 + tid] = rbf(rbf(silu_f(rbf(g))) * rbf(u));
  }
  __syncthreads();
  if (tid < 320) gemv(96, s_h + kd * 96, s_h + 384 + kd * 96, s_red + kd * 1536 + cd * 8);
  __syncthreads();
  const int o4 = tid + (tid < 160 ? 0 : 32);
  if (tid < 320) {
    const float4 *r = (const float4*)s_red + o4, a = r[0], b = r[384], c = r[768], d = r[1152];
    ((float4*)p.s->ffn)[sc * 320 + tid] = make_float4(a.x + b.x + c.x + d.x, a.y + b.y + c.y + d.y, a.z + b.z + c.z + d.z, a.w + b.w + c.w + d.w);
  }
  __syncthreads();
  if (tid == 0) { __threadfence(); s_c[0].x = (atomicAdd(&p.s->flag[FL_SIDE], 1u) & 3u) == 3u; __threadfence(); }
  __syncthreads();
  if (s_c[0].x) {
    if (tid < 320) {
      const float4 *r = (const float4*)p.s->ffn + tid, a = __ldcg(r), b = __ldcg(r + 320), c = __ldcg(r + 640), d = __ldcg(r + 960), x = ((float4*)s_x)[tid];
      const float rs = rbf(sigmoid_f(tid < 160 ? v0 : v1));
      auto gate = [&](float xn, float y) { return silu_f(rbf(xn + rbf(rbf(y) * rs))); };
      if (tid == 0) { p.s->sel[0] = i0; p.s->sel[1] = i1; }
      ((uint2*)p.s->gsel)[tid] =
          make_uint2(pack_bf16(gate(x.x, a.x + b.x + c.x + d.x), gate(x.y, a.y + b.y + c.y + d.y)), pack_bf16(gate(x.z, a.z + b.z + c.z + d.z), gate(x.w, a.w + b.w + c.w + d.w)));
    }
    __syncthreads();
    if (tid == 0) red_release(&p.s->flag[FL_FFN]);
  }
}

constexpr float SM_C = 0.07216878364870322f * 1.4426950408889634f;

#define LD 0
#define LS 3
__device__ __forceinline__ void ln_piece(const Params& p, uint32_t (&r)[48], int k, int row, int l16) {
  auto f = [&](int i) { return __uint_as_float(r[i]); };
  if (k == LD) {
#pragma unroll
    for (int i = 0; i < 5; i++) {
      const uint4 v = ldg_nc((const uint4*)(p.x + (size_t)row * DM) + i * 16 + l16);
      r[4 * i] = v.x; r[4 * i + 1] = v.y; r[4 * i + 2] = v.z; r[4 * i + 3] = v.w;
    }
    asm volatile("ld.relaxed.gpu.global.v2.u32 {%0,%1}, [%2];" : "=r"(r[20]), "=r"(r[21]) : "l"(&p.s->done));
  } else if (k == LS || k == LS + 1) {
    if (k == LS) { r[22] = __shfl_sync(~0u, r[0], 0, 16) << 16; r[23] = r[24] = 0; }
    float s0 = f(23), s1 = 0.f, q0 = f(24), q1 = 0.f;
#pragma unroll
    for (int i = 10 * (k - LS); i < 10 * (k - LS) + 10; i++) {
      const float a = bf_lo(r[i]) - f(22), b = bf_hi(r[i]) - f(22);
      s0 += a; s1 += b; q0 = fmaf(a, a, q0); q1 = fmaf(b, b, q1);
    }
    r[23] = __float_as_uint(s0 + s1); r[24] = __float_as_uint(q0 + q1);
  } else if (k == LS + 2) {
    float s0 = f(23), q0 = f(24);
#pragma unroll
    for (int o = 8; o > 0; o >>= 1) { s0 += __shfl_xor_sync(~0u, s0, o); q0 += __shfl_xor_sync(~0u, q0, o); }
    s0 *= 1.f / DM;
    const float mean = f(22) + s0, var = rbf(fmaxf(fmaf(q0, 1.f / DM, -s0 * s0), 0.f));
    float sd; asm("sqrt.approx.ftz.f32 %0, %1;" : "=f"(sd) : "f"(rbf(var + 1e-5f)));
    const float inv = rcp(rbf(sd));
    r[22] = pack_bf16(mean, mean); r[23] = __float_as_uint(inv * SM_C);
    const uint32_t tag = __funnelshift_r(r[20], r[21], 7) + 1;
    if (l16 == 0) st_pkt(&p.s->stat[row], tag, __float_as_uint(inv), tag, r[22]);
  } else if (k > LS + 2 && k <= LS + 5) {
#pragma unroll
    for (int j = 2 * (k - LS - 3); j < 2 * (k - LS - 3) + 2 && j < 5; j++) {
#pragma unroll
      for (int i = 4 * j; i < 4 * j + 4; i++) { const uint32_t d = hsub2(r[i], r[22]); r[i] = pack_bf16(bf_lo(d) * f(23), bf_hi(d) * f(23)); }
      *((uint4*)(p.s->xn + (size_t)row * DM) + j * 16 + l16) = make_uint4(r[4 * j], r[4 * j + 1], r[4 * j + 2], r[4 * j + 3]);
    }
  }
}

constexpr float SM_HI = 0x1p64f, SM_LO = 0x1p-64f;
__device__ __forceinline__ void exp_block(float (&s)[32], float& l0, float& l1, int from = 0, int to = 32) {
#pragma unroll
  for (int i = from; i < to; i++) { s[i] = ex2(s[i]); if (i & 2) l1 += s[i]; else l0 += s[i]; }
}
__device__ __forceinline__ float quad_sum(float v) { v += __shfl_xor_sync(~0u, v, 1); return v + __shfl_xor_sync(~0u, v, 2); }
__device__ __forceinline__ float quad_max(float v) { v = fmaxf(v, __shfl_xor_sync(~0u, v, 1)); return fmaxf(v, __shfl_xor_sync(~0u, v, 2)); }
__device__ __noinline__ void safe_head(const uint32_t* kp, const uint32_t* vp, uint4* io) {
  uint32_t fq[48];
#pragma unroll
  for (int i = 0; i < 12; i++) { const uint4 v = io[(i >> 1) * 512 + (i & 1) * 32]; fq[4 * i] = v.x; fq[4 * i + 1] = v.y; fq[4 * i + 2] = v.z; fq[4 * i + 3] = v.w; }
  float m0 = -INFINITY, m1 = -INFINITY;
#pragma unroll 1
  for (int pass = 0; pass < 3; pass++) {
    float o[48] = {}, l0 = 0.f, l1 = 0.f;
#pragma unroll 1
    for (int n = 0; n < 64; n++) {
      const uint32_t *kr = kp + n * (8 * DH / 2), *vr = vp + n * (8 * DH / 2) + (pass - 1) * 48;
      float d[4] = {};
#pragma unroll
      for (int t = 0; t < 12; t++)
        asm volatile("mma.sync.aligned.m16n8k16.row.col.f32.bf16.bf16.f32 {%0,%1,%2,%3}, {%4,%5,%6,%7}, {%8,%9}, {%0,%1,%2,%3};"
                     : "+f"(d[0]), "+f"(d[1]), "+f"(d[2]), "+f"(d[3])
                     : "r"(fq[4 * t]), "r"(fq[4 * t + 1]), "r"(fq[4 * t + 2]), "r"(fq[4 * t + 3]), "r"(__ldg(kr + 8 * t)), "r"(__ldg(kr + 8 * t + 4)));
      if (pass == 0) { m0 = fmaxf(m0, fmaxf(d[0], d[1])); m1 = fmaxf(m1, fmaxf(d[2], d[3])); continue; }
      d[0] = ex2(d[0] - m0); d[1] = ex2(d[1] - m0); d[2] = ex2(d[2] - m1); d[3] = ex2(d[3] - m1);
      l0 += d[0] + d[1]; l1 += d[2] + d[3];
      const uint32_t p0 = pack_bf16(d[0], d[1]), p1 = pack_bf16(d[2], d[3]);
#pragma unroll
      for (int c = 0; c < 12; c++)
        asm volatile("{\n.reg .b32 t;\nmovmatrix.sync.aligned.m8n8.trans.b16 t, %6;\n"
                     "mma.sync.aligned.m16n8k8.row.col.f32.bf16.bf16.f32 {%0,%1,%2,%3}, {%4,%5}, {t}, {%0,%1,%2,%3};\n}\n"
                     : "+f"(o[4 * c]), "+f"(o[4 * c + 1]), "+f"(o[4 * c + 2]), "+f"(o[4 * c + 3]) : "r"(p0), "r"(p1), "r"(__ldg(vr + 4 * c)));
    }
    if (pass == 0) { m0 = quad_max(m0); m1 = quad_max(m1); continue; }
    l0 = rcp(quad_sum(l0)); l1 = rcp(quad_sum(l1));
#pragma unroll
    for (int i = 0; i < 6; i++) {
      const float* v = o + 16 * (i >> 1) + 2 * (i & 1);
      const float r = i & 1 ? l1 : l0;
      io[(3 * (pass - 1) + (i >> 1)) * 512 + (i & 1) * 32] =
          make_uint4(pack_bf16(v[0] * r, v[1] * r), pack_bf16(v[4] * r, v[5] * r), pack_bf16(v[8] * r, v[9] * r), pack_bf16(v[12] * r, v[13] * r));
    }
  }
}

#define CVG 48
#define NE 8
#define PS1 8
#define CSW 1400
#define D0 2
#define LQ 6
__device__ __forceinline__ constexpr int end_stage(int n) { return n < 4 ? n : n < LQ ? n - 4 : n == LQ ? 4 : n % 5; }
#define Q2N 1
#define SWN 12
#define SCH 0
__device__ __forceinline__ constexpr int sent(int n) {
  constexpr int t[4][15] = {{0, 2, 4, 5, 5, 6, 7, 8,  9, 10, 11, 12, 13, 14, 15},
                            {0, 2, 4, 5, 5, 6, 7, 8,  9, 10, 12, 13, 14, 15, 15},
                            {0, 2, 4, 5, 5, 7, 8, 9, 10, 10, 12, 14, 15, 15, 15},
                            {0, 2, 4, 5, 5, 7, 8, 9, 10, 10, 13, 15, 15, 15, 15}};
  return n < LQ + 2 ? 0 : LQ == 6 && n == 8 ? 3 : t[SCH][n - 6];
}
template <int N> struct IntC { static constexpr int value = N; };
template <int N, int I = 0, class F> __device__ __forceinline__ void static_for(F&& f) { if constexpr (I < N) { f(IntC<I>{}); static_for<N, I + 1>(f); } }

__global__ void __launch_bounds__(384, 1) __cluster_dims__(2, 1, 1)
fused_kernel(const Params p, const __grid_constant__ CUtensorMap tm_x, const __grid_constant__ CUtensorMap tm_xn,
             const __grid_constant__ CUtensorMap tm_wq, const __grid_constant__ CUtensorMap tm_k,
             const __grid_constant__ CUtensorMap tm_v, const __grid_constant__ CUtensorMap tm_wo,
             const __grid_constant__ MapPair tm_w2,
             const __grid_constant__ CUtensorMap tm_xg, const __grid_constant__ CUtensorMap tm_xe,
             const __grid_constant__ CUtensorMap tm_out) {
  extern __shared__ __align__(1024) uint8_t smem_raw[];
  const uint32_t sb = smem_u32(smem_raw);
  const CUtensorMap* const tm_w = tm_w2.m;
  constexpr uint32_t EA = 160, EB = 184;
  const uint32_t bar_a = sb + OFF_M, bar_b = bar_a + 40, bar_x = bar_a + 88, bar_u = bar_a + 96, bar_e = bar_a + 104,
                 bar_o = bar_a + 200, bar_w = bar_a + 208, bar_z = bar_a + 288, bar_s = bar_a + 296, bar_d = bar_a + 304;
  const uint32_t s_stat = bar_a + 512;
  const uint32_t s_sel = s_stat + 1024;
  const int wi = __shfl_sync(~0u, threadIdx.x >> 5, 0), wg = wi >> 2;
  const int lane = threadIdx.x & 31;
  const int cl = blockIdx.x >> 1;
  const int rank = blockIdx.x & 1;

  if (cl >= 64) {
    const unsigned epoch = (unsigned)(__ldcg(&p.s->done) >> 7);
    side_cta(p, blockIdx.x - 128, epoch, (float*)smem_raw);
    return;
  }
  const int qt = (cl >> 3) * 2 + rank, hg = cl & 7;
  const int kq = hg >> 1, nh = hg & 1;

  const int s0 = (5 * (qt >> 1)) >> 2;
  if (elect()) {
    const int c = (int)(0x5ff7700000ull >> (4 * wi) & 15) + 1;
    for (int i = 0; i < 4; i++) mbar_init(bar_a + 32 * wi + 8 * i, c);
    asm volatile("fence.mbarrier_init.release.cluster;" ::: "memory");
  }
  __syncwarp();
  cluster_arrive();
  if (wi < 2 && elect()) {
    if (wi) { asm volatile("prefetch.tensormap [%0];" ::"l"(&tm_wq) : "memory"); mbar_expect_tx(bar_b, TB); mbar_expect_tx(bar_b + 8, TB); }
    else for (int i = 0; i < 2; i++) { mbar_expect_tx(bar_a + 8 * i, TA); tma2d(sb + i * TA, &tm_x, 64 * (s0 + i), qt * 128, bar_a + 8 * i); }
  }
  __syncwarp();
  cluster_wait();
  if (wi == 1 && elect())
    for (int i = 0; i < 2; i++) tma4d_mc(sb + OFF_B + i * TB + rank * (TB / 2), &tm_wq, 12 * hg, 8 * (s0 + i) + 4 * rank, bar_b + 8 * i);
  if (wg > 0) {
    const int w = wg - 1;
    const int cw = wi - 4;
    asm volatile("setmaxnreg.inc.sync.aligned.u32 232;");
    uint32_t fr[48];
    reg_fence(fr);
    auto ln_row = [&]() { int v = qt * 128 + hg * 16 + cw * 2 + (lane >> 4); asm volatile("" : "+r"(v)); return v; };
    uint32_t rel_addr;
    asm volatile("mapa.shared::cluster.u32 %0, %1, %2;" : "=r"(rel_addr) : "r"(bar_b + EB), "r"(lane & 1));
    auto rel_a = [&](uint32_t o8) { if (lane == 0) mbar_arrive(bar_a + EA + o8); };
    auto rel_b = [&](uint32_t o8) { if (lane < 2) mbar_arrive_cluster(rel_addr + o8); };
    uint32_t b8 = 0, phb = 0;
    auto next_pair = [&]() { b8 += 16; if (b8 == 48) { b8 = 0; phb ^= 1; } };
    const int g = lane >> 2, q = lane & 3;
    constexpr uint64_t HI_A = desc_hi(16, 1024, 1);
    constexpr uint64_t HI_W = desc_hi(1024, 3072, 1);
    constexpr uint64_t HI_O = desc_hi(2048, 512, 2);
    if (w == 1) asm volatile("bar.arrive 1, 256;" ::: "memory");

    uint32_t zero; asm volatile("mov.u32 %0, %%tid.y;" : "=r"(zero));
    float acc[96];
    uint4* optr = p.s->o + (size_t)(qt * 192 + hg * 24) * 512 + (cw * 16 + g) * 4 + (q ^ ((g >> 1) & 3));
    uint32_t rl[4];
    auto store_o = [&](int pp) {
#pragma unroll
      for (int i = (12 * pp + 8) / 9; i < (12 * (pp + 1) + 8) / 9; i++) {
#pragma unroll
        for (int k = 4 * i; k < 4 * i + 4; k++)
          asm volatile("{\n.reg .b32 t;\nmul.rn.bf16x2 t, %0, %2;\nfma.rn.bf16x2 %0, %0, %1, t;\n}\n" : "+r"(fr[k]) : "r"(rl[i & 1]), "r"(rl[2 + (i & 1)]));
        fr[4 * i] &= ~1u;
        optr[(i >> 1) * 512 + (i & 1) * 32] = make_uint4(fr[4 * i], fr[4 * i + 1], fr[4 * i + 2], fr[4 * i + 3]);
      }
      if (pp == 8) optr += 6 * 512;
    };
    auto fresh = [&]() { uint32_t v = sb; asm volatile("" : "+r"(v)); return v; };
    reg_fence(rl);

#pragma unroll 1
    for (int u = 0; u < 4; u++) {
      const uint32_t sq = fresh();
      const uint64_t dA = mkdesc(sq + w * 8192, HI_A), dB0 = mkdesc(sq + OFF_B, HI_W);
      uint32_t pb8 = 0;
#pragma unroll
      for (int s = 0; s < 10; s++) {
        const uint32_t o8 = b8 + 8 * (s & 1);
        const uint64_t dW = dB0 + o8 * (TB >> 7);
        mbar_wait(bar_a + 8 * (s % 5), s / 5);
        mbar_wait(bar_b + o8, phb);
        if (s == 9) asm volatile("bar.sync %0, 256;" ::"r"(1 + w) : "memory");
        WG_FENCE();
#pragma unroll
        for (int kk = 0; kk < 4; kk++) wg_ss192t(acc, dA + ((s % 5) * (TA >> 4) + kk * 2), dW + kk * 384, kk != 0 || s != 0);
        WG_COMMIT();
        if (s == 9) asm volatile("bar.arrive %0, 256;" ::"r"(2 - w) : "memory");
        if (s > 0) { WG_WAIT(1); rel_a(8 * ((s - 1) % 5)); rel_b(pb8); }
        if (s < 9) { if (u > 0) store_o(s); else ln_piece(p, fr, s, ln_row(), lane & 15); }
        if (s == 8) { __syncwarp(); if (lane == 0) mbar_arrive(bar_o); }
        pb8 = o8;
        if (s & 1) next_pair();
      }
      WG_WAIT(0);
      reg_fence(acc);
      rel_b(pb8);
      if (u == 0) {
        mbar_wait(bar_s, 0);
        const uint2 s0 = lds64(s_stat + (cw * 16 + g) * 8), s1 = lds64(s_stat + 64 + (cw * 16 + g) * 8);
        const uint32_t msk = q == 0 ? 0xffffffffu : q == 1 ? 0xffffu : 0u;
        const float c0 = SM_C * __uint_as_float(s0.y), c1 = SM_C * __uint_as_float(s1.y);
        uint32_t am[4] = {(s0.x ^ 0x80008000u) & msk, (s1.x ^ 0x80008000u) & msk, 0, 0};
        reg_fence(am);
        WG_FENCE();
        wg_rs192t(acc, am[0], am[1], am[2], am[3], mkdesc(sb, desc_hi(1024, 0, 1)), 1);
        WG_COMMIT();
        WG_WAIT(0);
        reg_fence(acc);
#pragma unroll
        for (int i = 0; i < 24; i++) { acc[4 * i] *= c0; acc[4 * i + 1] *= c0; acc[4 * i + 2] *= c1; acc[4 * i + 3] *= c1; }
      }
      rel_a(32);
      auto pack_q = [&](int from, int to) {
#pragma unroll
        for (int i = from; i < to; i++) { fr[i] = pack_bf16(acc[2 * i], acc[2 * i + 1]); asm volatile("" : "+r"(fr[i])::"memory"); }
      };
      pack_q(0, CVG);
      float sc[32], l0 = 0.f, l1 = 0.f;
      uint32_t pf[16], k8;
      auto pack_p = [&](const float (&s_)[32], int from = 0, int to = 16) {
#pragma unroll
        for (int i = from; i < to; i++) pf[i] = pack_bf16(s_[2 * i], s_[2 * i + 1]);
      };
      auto scores = [&](int j, int pass = 11) {
        k8 = b8 + 8;
        mbar_wait(bar_b + k8, phb);
        next_pair();
        mbar_wait(bar_b + b8, phb);
        const uint64_t dk = mkdesc(sb + OFF_B, HI_W) + k8 * (TB >> 7);
        asm volatile("bar.sync %0, 256;" ::"r"(1 + w) : "memory");
        WG_FENCE();
#pragma unroll
        for (int t = 0; t < 12; t++) {
          wg_rs64(sc, fr[4 * t], fr[4 * t + 1], fr[4 * t + 2], fr[4 * t + 3], dk + (t >> 2) * 64 + (t & 3) * 2, t != 0);
          if (t == 11) WG_COMMIT();
          if (t == pass) asm volatile("bar.arrive %0, 256;" ::"r"(2 - w) : "memory");
        }
      };
      auto pv = [&](int add) {
        const uint64_t dv = mkdesc(sb + OFF_B, HI_W) + b8 * (TB >> 7);
#pragma unroll
        for (int kk = 0; kk < 4; kk++) wg_rs192t(acc, pf[4 * kk], pf[4 * kk + 1], pf[4 * kk + 2], pf[4 * kk + 3], dv + kk * 384, kk != 0 || add);
        WG_COMMIT();
      };
      auto finish = [&]() {
        WG_WAIT(1);
        reg_fence(sc);
        exp_block(sc, l0, l1);
        rel_b(k8 + (__float_as_uint(l0) & __float_as_uint(l1) & zero));
        WG_WAIT(0);
        reg_fence(acc); reg_fence(pf);
        rel_b(b8);
        pack_p(sc);
      };
      {
        mbar_wait(bar_b + b8, phb);
        const uint64_t dk = mkdesc(sb + OFF_B, HI_W) + b8 * (TB >> 7);
        asm volatile("bar.sync %0, 256;" ::"r"(1 + w) : "memory");
#pragma unroll
        for (int t = 0; t < 12; t++) {
          if (t && (4 * t) % CVG == 0) pack_q(4 * t, 4 * t + CVG);
          if ((4 * t) % CVG == 0) WG_FENCE();
          wg_rs64(sc, fr[4 * t], fr[4 * t + 1], fr[4 * t + 2], fr[4 * t + 3], dk + (t >> 2) * 64 + (t & 3) * 2, t != 0);
          if (t == 7) asm volatile("bar.arrive %0, 256;" ::"r"(2 - w) : "memory");
        }
        WG_COMMIT();
        WG_WAIT(0);
        reg_fence(sc);
        float s0[32];
#pragma unroll
        for (int i = 0; i < 32; i++) s0[i] = i < NE ? sc[i] : __uint_as_float(__float_as_uint(sc[i]) ^ zero);
        exp_block(s0, l0, l1, 0, NE);
        pack_p(s0, 0, NE / 2);
#pragma unroll
        for (int i = NE; i < 32; i++) asm volatile("" : "+f"(s0[i])::"memory");
#pragma unroll
        for (int i = 0; i < NE / 2; i++) asm volatile("" : "+r"(pf[i])::"memory");
        rel_b(b8);
        scores(1, PS1);
        const uint32_t z = lds32(s_stat) & zero;
#pragma unroll
        for (int i = NE; i < 32; i++) {
          asm("{\n.reg .pred p;\nsetp.eq.u32 p, %1, 0;\n@p ex2.approx.ftz.f32 %0, %0;\n}\n" : "+f"(s0[i]) : "r"(z));
          if (i & 2) l1 += s0[i]; else l0 += s0[i];
        }
        pack_p(s0, NE / 2, 16);
        reg_fence(pf);
        WG_FENCE();
        pv(0);
        finish();
      }
#pragma unroll 1
      for (int j = NE < 32 ? 2 : 1; j < 8; j++) { scores(j); pv(j > 1); finish(); }
      const uint32_t v8 = b8 + 8;
      mbar_wait(bar_b + v8, phb);
      next_pair();
      {
        const uint64_t dv = mkdesc(sb + OFF_B, HI_W) + v8 * (TB >> 7);
        asm volatile("bar.sync %0, 256;" ::"r"(1 + w) : "memory");
        WG_FENCE();
#pragma unroll
        for (int kk = 0; kk < 4; kk++) {
          wg_rs192t(acc, pf[4 * kk], pf[4 * kk + 1], pf[4 * kk + 2], pf[4 * kk + 3], dv + kk * 384, 1);
          if (kk == 1 && (u < 3 || w == 0)) asm volatile("bar.arrive %0, 256;" ::"r"(2 - w) : "memory");
        }
        WG_COMMIT();
      }
      l0 = quad_sum(l0); l1 = quad_sum(l1);
      const bool unsafe = __any_sync(~0u, !(l0 >= SM_LO && l1 >= SM_LO && l0 + l1 <= SM_HI));
      l0 = rcp(l0); l1 = rcp(l1);
      rl[0] = pack_bf16(l0, l0); rl[1] = pack_bf16(l1, l1);
      l0 -= bf_lo(rl[0]); l1 -= bf_lo(rl[1]);
      rl[2] = pack_bf16(l0, l0); rl[3] = pack_bf16(l1, l1);
      WG_WAIT(0);
      reg_fence(acc);
      rel_b(v8);
      if (__builtin_expect(unsafe, 0)) {
        int o = hg * 4 + u; asm volatile("" : "+r"(o));
        o = (o * SKC + (SKC - WIN) + g) * (DH / 2) + q;
#pragma unroll
        for (int i = 0; i < 12; i++) optr[(i >> 1) * 512 + (i & 1) * 32] = make_uint4(fr[4 * i], fr[4 * i + 1], fr[4 * i + 2], fr[4 * i + 3]);
        safe_head((const uint32_t*)p.k + o, (const uint32_t*)p.v + o, optr);
#pragma unroll
        for (int i = 0; i < 12; i++) { const uint4 v = optr[(i >> 1) * 512 + (i & 1) * 32]; fr[4 * i] = v.x; fr[4 * i + 1] = v.y; fr[4 * i + 2] = v.z; fr[4 * i + 3] = v.w; }
        rl[0] = rl[1] = 0x3f803f80u; rl[2] = rl[3] = 0;
      } else {
#pragma unroll
        for (int i = 0; i < 24; i++) {
          fr[8 * (i >> 2) + (i & 3)] = pack_bf16(acc[4 * i], acc[4 * i + 1]);
          fr[8 * (i >> 2) + 4 + (i & 3)] = pack_bf16(acc[4 * i + 2], acc[4 * i + 3]);
        }
      }
    }

    float aF[80], aS[80];
    uint32_t pha = 0, a8 = 0, pa8 = 0, pb8 = 0;
#pragma unroll 1
    for (int s = 0; s < 19; s++) {
      const uint64_t d0 = mkdesc(sb, HI_O), dO = d0 + (a8 * (TA >> 7) + w * 256), dB = d0 + ((OFF_B >> 4) + b8 * (TB >> 7));
      mbar_wait(bar_a + a8, pha);
      mbar_wait(bar_b + b8, phb);
      WG_FENCE();
#pragma unroll
      for (int kk = 0; kk < 4; kk++) wg_ss160t(aF, dO + ((kk >> 1) * 512 + (kk & 1) * 2), dB + ((kk >> 1) * 640 + (kk & 1) * 64), kk != 0 || s != 0);
      WG_COMMIT();
      mbar_wait(bar_b + b8 + 8, phb);
      WG_WAIT(1);
      if (s > 0) { rel_a(pa8); rel_b(pb8 + 8); }
      WG_FENCE();
#pragma unroll
      for (int kk = 0; kk < 4; kk++) wg_ss160t(aS, dO + ((kk >> 1) * 512 + (kk & 1) * 2), dB + ((TB >> 4) + (kk >> 1) * 640 + (kk & 1) * 64), kk != 0 || s != 0);
      WG_COMMIT();
      if (s < 9) {
#pragma unroll
        for (int pp = 0; pp < 9; pp++) if (s == pp) store_o(pp);
        if (s == 8) { __syncwarp(); if (lane == 0) mbar_arrive(bar_o); }
      } else if (s < 15) {
        const int b = 2 * cw + ((lane >> 3) & 1);
        uint32_t ga = sb + OFF_B + TW + ((b * 11) >> 5) * (TB - 3840) + b * 1280 + (lane & 7) * 160 + (lane >> 4) * 16;
        if (s < 14) {
          mbar_wait(bar_x, 0);
          ga += 32 * (s - 9);
          ldsm4(ga, fr);
#pragma unroll
          for (int i = 0; i < 4; i++) {
            const uint2 st = lds64(s_stat + (cw * 16 + g + 8 * (i & 1)) * 8);
            const uint32_t d = hsub2(fr[i], st.x), xn = pack_bf16(bf_lo(d) * __uint_as_float(st.y), bf_hi(d) * __uint_as_float(st.y));
            fr[i] = pack_bf16(silu_f(bf_lo(xn)), silu_f(bf_hi(xn)));
          }
          stsm4(ga, fr);
        } else {
          mbar_wait(bar_u, 0);
          const uint2 sel = lds64(s_sel);
          const uint32_t row = qt * 128 + cw * 16 + (lane & 15);
          if (row == sel.x || row == sel.y) ga = s_sel + 16 + (row == sel.y ? 160 : 0) + (lane >> 4) * 16;
#pragma unroll
          for (int k = 0; k < 5; k++) ldsm4(ga + 32 * k, fr + 4 * k);
        }
      }
      WG_WAIT(1);
      rel_b(b8);
      pa8 = a8; a8 += 8; if (a8 == 40) { a8 = 0; pha ^= 1; }
      pb8 = b8; next_pair();
    }
    const int t128 = threadIdx.x & 127;
    uint4* const xbase = p.s->o + (size_t)(qt * 192 + nh * 24 + 10) * 512 + w * 640 + t128;
    uint4* const dst = xbase + kq * (48 * 512);
    float q1[40], q2[40], oth[40], own[40];
    auto take = [&](float (&x)[40], const float* a) {
#pragma unroll
      for (int k = 0; k < 40; k++) x[k] = __uint_as_float(__float_as_uint(a[k]) ^ zero);
      reg_fence(x);
    };
    reg_fence(aF);
    take(q1, aF);
    auto fa = [&](int i) { return mbar_try(bar_a + 8 * ((4 + i) % 5), i == 0); };
    auto fb = [&](int e) { return mbar_try(bar_b + 8 * (e % 6), (e / 6) & 1); };
    auto send = [&](int m) {
      const float* v = (m < 5 ? q1 : m < 10 ? q2 : oth) + 8 * (m % 5);
      st_pkt(dst + (m / 5) * 1280 + (m % 5) * 128, pack_bf16(v[0], v[1]) | 1, pack_bf16(v[2], v[3]), pack_bf16(v[4], v[5]), pack_bf16(v[6], v[7]));
    };
    static_for<20>([&](auto n_) {
      constexpr int n = n_.value, i = end_stage(n), e = 142 + n / 2, qi = n == 4 ? 1 : n == LQ ? 0 : n / 5;
      float (&acc_)[40] = qi == 0 ? q1 : qi == 1 ? q2 : qi == 2 ? oth : own;
      if (n == 0) while (!(fa(0) & fa(1) & fb(142) & fb(143))) {}
      if (n == 2) while (!(fa(2) & fa(3) & fb(144))) {}
      if (n == LQ) while (!(fa(4) & fb(145) & fb(146) & mbar_try(bar_z, 0))) {}
      if (n == 10) while (!(fb(147) & fb(148) & fb(149))) {}
      const uint64_t d0 = mkdesc(fresh(), HI_O);
      WG_FENCE();
#pragma unroll
      for (int kk = 0; kk < 4; kk++)
        wg_ss80t(acc_, d0 + w * 256 + (((4 + i) % 5) * (TA >> 4) + (kk >> 1) * 512 + (kk & 1) * 2),
                 d0 + ((OFF_B >> 4) + (e % 6) * (TB >> 4) + (n & 1) * 768 + (kk >> 1) * 384 + (kk & 1) * 64), 1);
      WG_COMMIT();
      if ((!(n & 1) && n <= 16) || n == 15 || n == LQ + 1) WG_WAIT(1);
      if (n == 0) rel_a(24);
      if (!(n & 1) && n <= 10) rel_b(8 * ((e - 1) % 6));
      if (n == Q2N) take(q2, aF + 40);
      if (n == 10) cluster_arrive();
      if (n == 12 || n == 14 || n == 16) rel_a(4u * n - 48);
      if (n == LQ + 1) reg_fence(q1);
      if (n == 10) reg_fence(q2);
      if (n == 15) reg_fence(oth);
      if (n == 15) while (!(fb(150) & fb(151))) {}
      static_for<sent(n + 1) - sent(n)>([&](auto k_) { send(sent(n) + k_.value); });
      if (n == 8) {
        reg_fence(aS);
#pragma unroll
        for (int k = 0; k < 40; k++) oth[k] = kq & 1 ? aS[k] : aS[40 + k];
        reg_fence(oth);
      }
      if (n == SWN) {
        reg_fence(aS);
#pragma unroll
        for (int k = 0; k < 40; k++) own[k] = kq & 1 ? aS[40 + k] : aS[k];
        reg_fence(own);
      }
    });
    uint32_t xr[20];
    const uint32_t xs = sb + OFF_B + 2 * TB + cw * 2560, xa = xs + (lane & 15) * 160 + (lane >> 4) * 16;
    mbar_wait(bar_b + 16, 1);
#pragma unroll
    for (int k = 0; k < 5; k++) ldsm4(xa + 32 * k, xr + 4 * k);
    {
      auto fetch = [&](int e, uint4 (&v)[5]) {
        mbar_wait(bar_e + 16 * e + 8 * w, 0);
#pragma unroll
        for (int i = 0; i < 5; i++) v[i] = lds128(sb + OFF_B + (3 + e) * TB + (w * 640 + i * 128 + t128) * 16);
      };
      auto add = [&](int e, uint4 (&v)[5]) {
        while (!(v[0].x & v[1].x & v[2].x & v[3].x & v[4].x & 1)) {
#pragma unroll
          for (int i = 0; i < 5; i++) v[i] = ld_pkt(xbase + (kq ^ ((0x132 >> (4 * e)) & 3)) * (48 * 512) + (e < 2 ? kq & 1 : 2) * 1280 + i * 128);
        }
#pragma unroll
        for (int i = 0; i < 5; i++) {
          float* o = own + 8 * i;
          o[0] += bf_lo(v[i].x); o[1] += bf_hi(v[i].x); o[2] += bf_lo(v[i].y); o[3] += bf_hi(v[i].y);
          o[4] += bf_lo(v[i].z); o[5] += bf_hi(v[i].z); o[6] += bf_lo(v[i].w); o[7] += bf_hi(v[i].w);
        }
      };
      WG_WAIT(0);
      reg_fence(own);
#pragma unroll 1
      for (int e = 0; e < 3; e++) { uint4 v[5]; fetch(e, v); add(e, v); }
      if (lane == 0) mbar_arrive(bar_w);
#pragma unroll
      for (int i = 0; i < 20; i++) xr[i] = hadd2(xr[i], hmul2(pack_bf16(own[2 * i], own[2 * i + 1]), fr[i]));
#pragma unroll
      for (int k = 0; k < 5; k++) stsm4(xa + 32 * k, xr + 4 * k);
      asm volatile("fence.proxy.async.shared::cta;" ::: "memory");
      __syncwarp();
      if (elect()) {
        tma2d_store(&tm_out, xs, nh * 320 + kq * 80, qt * 128 + cw * 16);
        asm volatile("cp.async.bulk.commit_group;\ncp.async.bulk.wait_group.read 0;" ::: "memory");
      }
      __syncwarp();
    }
    cluster_wait();
  } else {
    asm volatile("setmaxnreg.dec.sync.aligned.u32 40;");
    uint32_t tid_; asm volatile("mov.u32 %0, %%tid.x;" : "=r"(tid_));
    const int warp = __shfl_sync(~0u, tid_ >> 5, 0);
    auto is_warp = [&](int k) { uint32_t e; asm volatile("{\n.reg .pred q;\nsetp.eq.u32 q, %1, %2;\nselp.u32 %0, 1, 0, q;\n}" : "=r"(e) : "r"(warp), "r"(k)); return e != 0; };
    auto k_block = [&](int t) {
      const int i = (t * 11) >> 5;
      return ((i < 6 ? 2 * kq + (i & 1) : hg ^ (i & 1)) * 4 + (i >> 1)) * 6 + (t == 3 * i ? 4 : 2 * (t - 3 * i) - 2);
    };
    if (warp > 0) {
      const unsigned epoch = (unsigned)(__ldcg(&p.s->done) >> 7);
      int budget = WAIT_BUDGET;
      const uint32_t tag = epoch + 1;
      mbar_wait(bar_b, 0, budget); mbar_wait(bar_b + 8, 0, budget);
      float cs0 = 0.f, cs1 = 0.f;
      const int n = rank * 96 + (warp - 1) * 32 + (lane & 15) * 2;
#pragma unroll 1
      for (int kg = ((qt >> 1) & 3) * 2 + (lane >> 4) * 5, e = kg + 5; kg < e; kg++) {
        const uint32_t ad = sb + OFF_B + kg * 3072 + (n >> 6) * 1024 + (n & 63) * 2;
#pragma unroll
        for (int k = 0; k < 8; k++) { const uint32_t v = lds32(ad ^ (k * 0x90)); cs0 += bf_lo(v); cs1 += bf_hi(v); }
      }
      cs0 += __shfl_xor_sync(~0u, cs0, 16); cs1 += __shfl_xor_sync(~0u, cs1, 16);
      if (lane < 16)
        asm volatile("{\n.reg .b64 v;\nmov.b64 v, {%1, %2};\nst.relaxed.gpu.global.b64 [%0], v;\n}\n" ::"l"((uint2*)(p.s->cs + (hg * 4 + (qt >> 2)) * 96 + (n >> 1)) + ((qt >> 1) & 1)),
                     "r"((__float_as_uint(cs0) & ~3u) | (tag & 3)), "r"(__float_as_uint(cs1)) : "memory");
      mbar_wait(bar_a + EA, 0, budget);
      if (lane < 2) { uint32_t a; asm volatile("mapa.shared::cluster.u32 %0, %1, %2;" : "=r"(a) : "r"(bar_d), "r"(lane)); mbar_arrive_cluster(a); }
      cs0 = cs1 = 0.f;
      for (const uint32_t c0 = clock(); clock() - c0 < CSW;) {}
#pragma unroll 1
      for (int e = 0; e < 2; e++) {
        if (e) {
          mbar_wait(bar_a + EA, 1, budget);
#pragma unroll 1
          for (int k = 0; k < 8; k++) {
            const uint32_t v = pack_bf16(cs0, cs1);
            sts32((sb + ((tid_ - 32) >> 5) * 1024 + lane * 4) ^ (k * 0x90), k < 3 ? v : 0);
            cs0 -= bf_lo(v); cs1 -= bf_hi(v);
          }
          if (!is_warp(3)) break;
        }
        const uint4* src = e ? p.s->stat + qt * 128 + lane : p.s->cs + hg * 4 * 96 + (tid_ - 32);
        const int step = e ? 32 : 96;
        uint4 v[4];
        while (true) {
          uint32_t bad = 0;
#pragma unroll
          for (int i = 0; i < 4; i++) v[i] = ld_pkt(src + i * step);
#pragma unroll
          for (int i = 0; i < 4; i++) bad |= (v[i].x ^ tag) | (v[i].z ^ tag);
          if (!__any_sync(~0u, bad & 3) || --budget < 0) break;
        }
#pragma unroll
        for (int i = 0; i < 4; i++) {
          cs0 += __uint_as_float(v[i].x & ~3u) + __uint_as_float(v[i].z & ~3u); cs1 += __uint_as_float(v[i].y) + __uint_as_float(v[i].w);
          if (e) asm volatile("st.shared.v2.u32 [%0], {%1,%2};" ::"r"(s_stat + (i * 32 + lane) * 8), "r"(v[i].w), "r"(v[i].y) : "memory");
        }
      }
      asm volatile("fence.proxy.async.shared::cta;" ::: "memory");
      __syncwarp();
      if (lane < 2) mbar_arrive(bar_s);
      if (is_warp(1)) {
#pragma unroll 1
        for (int u = 0; u < 5; u++) {
          mbar_wait(bar_o, u & 1);
          if (lane == 0) red_release(&p.s->flag[u ? FL_O + (qt * 8 + hg) * 8 : FL_XN + qt * 32]);
          __syncwarp();
        }
      } else if (is_warp(2)) {
        mbar_wait(bar_x, 0, budget);
        while ((int)(ld_acquire(&p.s->flag[FL_FFN]) - tag) < 0 && --budget >= 0) {}
        if (lane < 21) {
          const uint4 v = __ldcg(lane ? (const uint4*)(p.s->gsel + (lane > 10 ? DM - 80 : 0) + nh * 320 + kq * 80) + lane - 1 : (const uint4*)p.s->sel);
          asm volatile("st.shared.v4.u32 [%0], {%1,%2,%3,%4};" ::"r"(s_sel + 16 * lane), "r"(v.x), "r"(v.y), "r"(v.z), "r"(v.w) : "memory");
        }
        __syncwarp();
        if (lane == 0) { mbar_arrive(bar_u); asm volatile("red.relaxed.gpu.global.add.u64 [%0], 1;" ::"l"(&p.s->done) : "memory"); }
        while ((int)(ld_acquire(&p.s->flag[FL_RD + (qt * 8 + (hg ^ 1)) * 8]) - tag) < 0 && --budget >= 0) __nanosleep(200);
        if (lane < 3) mbar_arrive(bar_z);
        mbar_wait(bar_w, 0, budget);
        if (budget < 0) asm volatile("st.global.u32 [%0], %1;" ::"l"(0ull), "r"(budget) : "memory");
      } else {
        wait_flag(&p.s->flag[FL_XN + qt * 32], (epoch + 1) * 8);
        fence_proxy_async();
        mbar_wait(bar_a + EA + 32, 1);
        uint32_t a8 = 0, pha = 1;
        const int kb = (qt * 192 + k_block(lane)) * 512;
#pragma unroll 1
        for (int n = 0; n < 54; n++) {
          const int t = n - 30, ko = __shfl_sync(~0u, kb, t);
          if (t == 0 || t == 18) {
            wait_flag(&p.s->flag[FL_O + (qt * 8 + (t ? 2 * kq + (lane & 1) : lane & 7)) * 8], epoch * 4 + (t ? 4 : 3));
            fence_proxy_async();
          }
          mbar_wait(bar_a + EA + a8, pha);
          const uint32_t fb = bar_a + a8, dst = sb + a8 * (TA >> 3);
          if (elect()) {
            if (t >= 0) {
              mbar_expect_tx(fb, TA);
              bulk_load(dst, p.s->o + ko, TA, fb);
              if (t == 8) {
                mbar_expect_tx(bar_x, 6 * 3840);
#pragma unroll 1
                for (int e = 0; e < 6; e++) tma2d(sb + OFF_B + TW + e * TB, &tm_xg, nh * 320 + kq * 80, qt * 128 + e * 24, bar_x);
                asm volatile("prefetch.tensormap [%0];\nprefetch.tensormap [%1];\nprefetch.tensormap [%2];\nprefetch.tensormap [%3];"
                             ::"l"(tm_w), "l"(tm_w + 1), "l"(&tm_xe), "l"(&tm_out) : "memory");
              }
              if (t == 22) asm volatile("red.relaxed.gpu.global.add.u32 [%0], 1;" ::"l"(&p.s->flag[FL_RD + (qt * 8 + hg) * 8]) : "memory");
            } else if (n >= 10 && pha) mbar_arrive(fb);
            else { mbar_expect_tx(fb, TA); tma2d(dst, &tm_xn, 8 * a8 + (pha || (n >= 15 && n < 20) ? 0 : 320), qt * 128, fb); }
          }
          a8 += 8; if (a8 == 40) { a8 = 0; pha ^= 1; }
        }
        if (lane < 3) mbar_arrive(bar_z);
      }
    } else {
      uint32_t fb = bar_b + 16, dst = sb + OFF_B + 2 * TB, ph = 1;
      auto next = [&]() { fb += 8; dst += TB; if (fb == bar_b + 48) { fb = bar_b; dst = sb + OFF_B; ph ^= 1; } };
#pragma unroll 1
      for (int u = 0; u < 4; u++) {
        const int h = hg * 4 + u;
        int s = u ? (u == 2 ? 5 : 0) : (s0 + 2) % 10;
#pragma unroll 1
        for (int i = u ? 0 : 2; i < 10; i++) {
          if (u == 0) {
            const uint32_t a8 = 8 * (i < 5 ? i : i - 5);
            if (D0 && i >= D0) { const int j = i - D0; mbar_wait(bar_a + 8 * (j < 5 ? j : j - 5), j >= 5); }
            mbar_wait(bar_a + EA + a8, i < 5);
            if (elect()) { mbar_expect_tx(bar_a + a8, TA); tma2d(sb + a8 * (TA >> 3), &tm_x, 64 * s, qt * 128, bar_a + a8); }
            if (i == 6) mbar_wait(bar_d, 0);
          }
          mbar_wait(fb + EB, ph);
          if (elect()) { mbar_expect_tx(fb, TB); tma4d_mc(dst + rank * (TB / 2), &tm_wq, 3 * h, 8 * s + 4 * rank, fb); }
          next();
          if (++s == 10) s = 0;
        }
        const int kv0 = (h * SKC + (SKC - WIN)) / 8 + 4 * rank;
#pragma unroll 1
        for (int i = 0; i < 16; i++) {
          const bool isk = (0x2AAB >> i) & 1;
          mbar_wait(fb + EB, ph);
          if (elect()) { mbar_expect_tx(fb, TB); tma4d_mc(dst + rank * (TB / 2), isk ? &tm_k : &tm_v, 0, kv0 + 8 * (isk ? (i + 1) >> 1 : (i - 1) >> 1), fb); }
          next();
        }
      }
      const int cF = 10 * nh + 5 - 5 * (kq >> 1), cS = 10 * nh + 5 * (kq >> 1);
      const int kb = 4 * (k_block(lane) + rank);
#pragma unroll 1
      for (int m = 0; m < 38; m++) {
        const int c2 = __shfl_sync(~0u, kb, m >> 1);
        mbar_wait(fb + EB, ph);
        if (elect()) { mbar_expect_tx(fb, TW); tma5d_mc(dst + rank * (TW / 2), &tm_wo, c2, m & 1 ? cS : cF, fb); }
        next();
      }
      const int odd = (((0x7ff0 ^ 1 << LQ) ^ (kq & 1 ? 0xffc00 : 0)) >> lane) & 1;
      const int tq = __shfl_sync(~0u, kb, 19 + end_stage(lane)) << 16 | odd << 7 | ((lane < 10 ? cF : cS) + 2 * odd);
#pragma unroll 1
      for (int n = 0; n < 20; n += 2) {
        const int t0 = __shfl_sync(~0u, tq, n), t1 = __shfl_sync(~0u, tq, n + 1);
        mbar_wait(fb + EB, ph);
        if (elect()) {
          mbar_expect_tx(fb, TB);
          tma5d_mc(dst + rank * (TB / 4), (const CUtensorMap*)((const char*)tm_w + (t0 & 128)), t0 >> 16, t0 & 31, fb);
          tma5d_mc(dst + TB / 2 + rank * (TB / 4), (const CUtensorMap*)((const char*)tm_w + (t1 & 128)), t1 >> 16, t1 & 31, fb);
        }
        next();
      }
      mbar_wait(fb + EB, ph);
      if (elect()) { mbar_expect_tx(fb, TW); tma2d(dst, &tm_xe, nh * 320 + kq * 80, qt * 128, fb); }
    }
    if (!is_warp(2)) {
      const int e = warp - (warp >> 1), ms = 2 * e + ((lane >> 2) & 1);
      const uint4* src = p.s->o + (size_t)(qt * 192 + nh * 24 + 10 + (kq ^ ((0x132 >> (4 * e)) & 3)) * 48) * 512 + (e < 2 ? kq & 1 : 2) * 1280 + (ms & 1) * 640;
      uint32_t todo = 0xff;
      bool ok = lane >= 8;
      mbar_wait(bar_z, 0);
#pragma unroll 1
      while (todo) {
        if (!ok) ok = ld_pkt(src + 4 * 128 + (lane & 3) * 32 + 31).x & 1;
        const uint32_t got = __ballot_sync(~0u, ok) & todo, go = __ballot_sync(~0u, ((got >> (lane & 28)) & 15) == 15);
        if (go) mbar_wait(bar_a + EA + 8 * e, 0);
        if ((go & 0x11) >> lane & 1) {
          mbar_expect_tx(bar_e + 8 * ms, TW / 2); bulk_load(sb + OFF_B + (3 + e) * TB + (ms & 1) * (TW / 2), src, TW / 2, bar_e + 8 * ms);
        }
        todo &= ~go;
      }
    }
    cluster_sync();
  }
}

typedef CUresult (*EncodeFn)(CUtensorMap*, CUtensorMapDataType, cuuint32_t, void*, const cuuint64_t*, const cuuint64_t*,
                             const cuuint32_t*, const cuuint32_t*, CUtensorMapInterleave, CUtensorMapSwizzle,
                             CUtensorMapL2promotion, CUtensorMapFloatOOBfill);

void encode(EncodeFn fn, CUtensorMap* tm, void* base, int rank, const cuuint64_t* dims, const cuuint64_t* strides,
            const cuuint32_t* box, CUtensorMapSwizzle sw) {
  const cuuint32_t es[5] = {1, 1, 1, 1, 1};
  fn(tm, CU_TENSOR_MAP_DATA_TYPE_BFLOAT16, rank, base, dims, strides, box, es, CU_TENSOR_MAP_INTERLEAVE_NONE, sw,
     CU_TENSOR_MAP_L2_PROMOTION_L2_128B, CU_TENSOR_MAP_FLOAT_OOB_FILL_NONE);
}

}

extern "C" void kernel_launch(void* const* d_in, const int* in_sizes, int n_in, void* d_out, int out_size) {
  static EncodeFn fn = nullptr;
  static Scratch* scr = nullptr;
  if (!fn) {
    void* f = nullptr;
    cudaDriverEntryPointQueryResult st;
    cudaGetDriverEntryPoint("cuTensorMapEncodeTiled", &f, cudaEnableDefault, &st);
    fn = (EncodeFn)f;
    cudaGetSymbolAddress((void**)&scr, g_scratch);
    cudaFuncSetAttribute(fused_kernel, cudaFuncAttributeMaxDynamicSharedMemorySize, SMEM_BYTES);
  }
  CUtensorMap tm_x, tm_xn, tm_wq, tm_k, tm_v, tm_wo, tm_xg, tm_xe, tm_out;
  MapPair tm_w2;
  { const cuuint64_t d[2] = {DM, SQ}, s[1] = {DM * 2}; const cuuint32_t b[2] = {64, 128};
    encode(fn, &tm_x, d_in[0], 2, d, s, b, CU_TENSOR_MAP_SWIZZLE_128B);
    encode(fn, &tm_xn, scr->xn, 2, d, s, b, CU_TENSOR_MAP_SWIZZLE_128B); }
  { const cuuint64_t d[4] = {64, 8, QD / 64, DM / 8}, s[3] = {QD * 2, 128, 8 * QD * 2}; const cuuint32_t b[4] = {64, 8, 3, 4};
    encode(fn, &tm_wq, d_in[3], 4, d, s, b, CU_TENSOR_MAP_SWIZZLE_128B); }
  { const cuuint64_t d[4] = {64, 8, 3, NH * SKC / 8}, s[3] = {DH * 2, 128, 8 * DH * 2}; const cuuint32_t b[4] = {64, 8, 3, 4};
    encode(fn, &tm_k, d_in[1], 4, d, s, b, CU_TENSOR_MAP_SWIZZLE_128B);
    encode(fn, &tm_v, d_in[2], 4, d, s, b, CU_TENSOR_MAP_SWIZZLE_128B); }
  {
    const cuuint64_t d[5] = {32, 2, QD / 8, 4, DM / 32}, s[4] = {DM * 2, 8 * DM * 2, 2 * DM * 2, 64}; const cuuint32_t b[5] = {32, 2, 4, 4, 5};
    encode(fn, &tm_wo, d_in[4], 5, d, s, b, CU_TENSOR_MAP_SWIZZLE_64B);
    const cuuint32_t b3[5] = {32, 2, 4, 4, 3};
    encode(fn, &tm_w2.m[0], d_in[4], 5, d, s, b3, CU_TENSOR_MAP_SWIZZLE_64B);
    encode(fn, &tm_w2.m[1], (char*)d_in[4] + 32, 5, d, s, b3, CU_TENSOR_MAP_SWIZZLE_64B); }
  { const cuuint64_t d[2] = {DM, SQ}, s[1] = {DM * 2}; const cuuint32_t bg[2] = {80, 24}, bx[2] = {80, 128}, bo[2] = {80, 16};
    encode(fn, &tm_xg, d_in[0], 2, d, s, bg, CU_TENSOR_MAP_SWIZZLE_NONE);
    encode(fn, &tm_xe, d_in[0], 2, d, s, bx, CU_TENSOR_MAP_SWIZZLE_NONE);
    encode(fn, &tm_out, d_out, 2, d, s, bo, CU_TENSOR_MAP_SWIZZLE_NONE); }
  Params p;
  p.x = (const __nv_bfloat16*)d_in[0]; p.wr = (const __nv_bfloat16*)d_in[6]; p.wg = (const __nv_bfloat16*)d_in[7];
  p.wu = (const __nv_bfloat16*)d_in[8]; p.wd = (const __nv_bfloat16*)d_in[9];

  p.k = (const __nv_bfloat16*)d_in[1]; p.v = (const __nv_bfloat16*)d_in[2]; p.s = scr;
  cudaLaunchConfig_t cfg = {};
  cfg.gridDim = dim3(132); cfg.blockDim = dim3(384); cfg.dynamicSmemBytes = SMEM_BYTES; cfg.stream = cudaStreamPerThread;
  cudaLaunchKernelEx(&cfg, fused_kernel, p, tm_x, tm_xn, tm_wq, tm_k, tm_v, tm_wo, tm_w2, tm_xg, tm_xe, tm_out);
}
```

```cpp
#include <cuda_runtime.h>
#include <cuda_bf16.h>
#include <cuda.h>
#include <stdint.h>

namespace {

constexpr int SQ = 2048, DM = 640, NH = 32, DH = 192, SKC = 2048, WIN = 512, FF = 1536;
constexpr int QD = NH * DH;
constexpr uint32_t TA = 16384, TB = 24576, TW = 20480, OFF_B = 5 * TA, OFF_M = OFF_B + 6 * TB, SMEM_BYTES = OFF_M + 3072;
constexpr int WAIT_BUDGET = 1 << 20;

constexpr int FL_XN = 0;
constexpr int FL_O = 512;
constexpr int FL_RD = FL_O + 1024;
constexpr int FL_FFN = FL_RD + 1024;
constexpr int FL_SIDE = FL_FFN + 32;
struct __align__(1024) Scratch {
  unsigned long long done, pad0[15];
  unsigned flag[FL_SIDE + 32];
  uint4 cand[8];
  float ffn[4 * 2 * DM];
  int sel[4];
  __nv_bfloat16 gsel[2 * DM];
  uint4 cs[8 * 4 * DH / 2];
  uint4 stat[SQ];
  __align__(1024) __nv_bfloat16 xn[SQ * DM];
  __align__(1024) uint4 o[SQ * QD / 8];
};
__device__ Scratch g_scratch;

__device__ __forceinline__ uint32_t smem_u32(const void* p) { return (uint32_t)__cvta_generic_to_shared(p); }
__device__ __forceinline__ void mbar_init(uint32_t bar, int cnt) { asm volatile("mbarrier.init.shared::cta.b64 [%0], %1;" ::"r"(bar), "r"(cnt)); }
__device__ __forceinline__ void mbar_expect_tx(uint32_t bar, uint32_t bytes) {
  asm volatile("mbarrier.arrive.expect_tx.shared::cta.b64 _, [%0], %1;" ::"r"(bar), "r"(bytes) : "memory");
}
__device__ __forceinline__ void mbar_arrive(uint32_t bar) { asm volatile("mbarrier.arrive.shared::cta.b64 _, [%0];" ::"r"(bar) : "memory"); }
__device__ __forceinline__ void mbar_arrive_cluster(uint32_t addr) { asm volatile("mbarrier.arrive.shared::cluster.b64 _, [%0];" ::"r"(addr) : "memory"); }
__device__ __forceinline__ bool mbar_try(uint32_t bar, uint32_t parity) {
  uint32_t ok;
  asm volatile("{\n.reg .pred p;\nmbarrier.try_wait.parity.shared::cta.b64 p, [%1], %2;\nselp.u32 %0, 1, 0, p;\n}\n" : "=r"(ok) : "r"(bar), "r"(parity) : "memory");
  return ok;
}
__device__ __forceinline__ void mbar_wait(uint32_t bar, uint32_t parity, int& budget) {
#pragma unroll 1
  while (!mbar_try(bar, parity)) { if (--budget < 0) break; }
}
__device__ __forceinline__ void mbar_wait(uint32_t bar, uint32_t parity) {
#pragma unroll 1
  while (!mbar_try(bar, parity)) {}
}
__device__ __forceinline__ unsigned ld_acquire(const unsigned* p) { unsigned v; asm volatile("ld.acquire.gpu.global.u32 %0, [%1];" : "=r"(v) : "l"(p) : "memory"); return v; }
__device__ __forceinline__ void wait_flag(const unsigned* p, unsigned target) {
#pragma unroll 1
  while (__any_sync(~0u, (int)(ld_acquire(p) - target) < 0)) {}
}
__device__ __forceinline__ void red_release(unsigned* p) { asm volatile("red.release.gpu.global.add.u32 [%0], 1;" ::"l"(p) : "memory"); }
__device__ __forceinline__ void fence_proxy_async() { asm volatile("fence.proxy.async.global;" ::: "memory"); }
__device__ __forceinline__ bool elect() {
  uint32_t p;
  asm volatile("{\n.reg .pred P;\nelect.sync _|P, 0xffffffff;\nselp.u32 %0, 1, 0, P;\n}\n" : "=r"(p));
  return p;
}
__device__ __forceinline__ void cluster_arrive() { asm volatile("barrier.cluster.arrive.relaxed.aligned;" ::: "memory"); }
__device__ __forceinline__ void cluster_wait() { asm volatile("barrier.cluster.wait.aligned;" ::: "memory"); }
__device__ __forceinline__ void cluster_sync() { cluster_arrive(); cluster_wait(); }
__device__ __forceinline__ void tma2d(uint32_t dst, const CUtensorMap* tm, int c0, int c1, uint32_t bar) {
  asm volatile("cp.async.bulk.tensor.2d.shared::cluster.global.mbarrier::complete_tx::bytes [%0], [%1, {%3, %4}], [%2];"
               ::"r"(dst), "l"(tm), "r"(bar), "r"(c0), "r"(c1) : "memory");
}
constexpr uint64_t POL_FIRST = 0x12F0000000000000ull;
__device__ __forceinline__ void tma4d_mc(uint32_t dst, const CUtensorMap* tm, int c2, int c3, uint32_t bar) {
  asm volatile("cp.async.bulk.tensor.4d.shared::cluster.global.mbarrier::complete_tx::bytes.multicast::cluster.L2::cache_hint [%0], [%1, {%3, %3, %4, %5}], [%2], %6, %7;"
               ::"r"(dst), "l"(tm), "r"(bar), "r"(0), "r"(c2), "r"(c3), "h"((uint16_t)3), "l"(POL_FIRST) : "memory");
}
__device__ __forceinline__ void tma5d_mc(uint32_t dst, const CUtensorMap* tm, int c2, int c4, uint32_t bar) {
  asm volatile("cp.async.bulk.tensor.5d.shared::cluster.global.mbarrier::complete_tx::bytes.multicast::cluster.L2::cache_hint [%0], [%1, {%3, %3, %4, %3, %5}], [%2], %6, %7;"
               ::"r"(dst), "l"(tm), "r"(bar), "r"(0), "r"(c2), "r"(c4), "h"((uint16_t)3), "l"(POL_FIRST) : "memory");
}
__device__ __forceinline__ void bulk_load(uint32_t dst, const void* src, uint32_t bytes, uint32_t bar) {
  asm volatile("cp.async.bulk.shared::cluster.global.mbarrier::complete_tx::bytes.L2::cache_hint [%0], [%1], %2, [%3], %4;" ::"r"(dst), "l"(src), "r"(bytes), "r"(bar), "l"(POL_FIRST) : "memory");
}
__device__ __forceinline__ void tma2d_store(const CUtensorMap* tm, uint32_t src, int c0, int c1) {
  asm volatile("cp.async.bulk.tensor.2d.global.shared::cta.bulk_group [%0, {%2, %3}], [%1];" ::"l"(tm), "r"(src), "r"(c0), "r"(c1) : "memory");
}
__device__ __forceinline__ uint32_t lds32(uint32_t a) { uint32_t v; asm volatile("ld.shared.u32 %0, [%1];" : "=r"(v) : "r"(a) : "memory"); return v; }
__device__ __forceinline__ uint2 lds64(uint32_t a) { uint2 v; asm volatile("ld.shared.v2.u32 {%0,%1}, [%2];" : "=r"(v.x), "=r"(v.y) : "r"(a) : "memory"); return v; }
__device__ __forceinline__ uint4 lds128(uint32_t a) { uint4 v; asm volatile("ld.shared.v4.u32 {%0,%1,%2,%3}, [%4];" : "=r"(v.x), "=r"(v.y), "=r"(v.z), "=r"(v.w) : "r"(a) : "memory"); return v; }
__device__ __forceinline__ void ldsm4(uint32_t a, uint32_t* v) {
  asm volatile("ldmatrix.sync.aligned.m8n8.x4.shared.b16 {%0,%1,%2,%3}, [%4];" : "=r"(v[0]), "=r"(v[1]), "=r"(v[2]), "=r"(v[3]) : "r"(a) : "memory");
}
__device__ __forceinline__ void stsm4(uint32_t a, const uint32_t* v) {
  asm volatile("stmatrix.sync.aligned.m8n8.x4.shared.b16 [%0], {%1,%2,%3,%4};" ::"r"(a), "r"(v[0]), "r"(v[1]), "r"(v[2]), "r"(v[3]) : "memory");
}
__device__ __forceinline__ void sts32(uint32_t a, uint32_t v) { asm volatile("st.shared.u32 [%0], %1;" ::"r"(a), "r"(v) : "memory"); }
__device__ __forceinline__ void st_pkt(uint4* p, uint32_t a, uint32_t b, uint32_t c, uint32_t d) {
  asm volatile("st.relaxed.gpu.global.v4.b32 [%0], {%1, %2, %3, %4};" ::"l"(p), "r"(a), "r"(b), "r"(c), "r"(d) : "memory");
}
__device__ __forceinline__ uint4 ld_pkt(const uint4* p) {
  uint4 v;
  asm volatile("{\n.reg .b128 v;\nld.relaxed.gpu.global.b128 v, [%4];\nmov.b128 {%0, %1, %2, %3}, v;\n}\n" : "=r"(v.x), "=r"(v.y), "=r"(v.z), "=r"(v.w) : "l"(p) : "memory");
  return v;
}
__device__ __forceinline__ uint4 ldg_nc(const void* p) {
  uint4 v;
  asm volatile("ld.global.nc.v4.u32 {%0,%1,%2,%3}, [%4];" : "=r"(v.x), "=r"(v.y), "=r"(v.z), "=r"(v.w) : "l"(p));
  return v;
}
#define WG_FENCE() asm volatile("wgmma.fence.sync.aligned;" ::: "memory")
#define WG_COMMIT() asm volatile("wgmma.commit_group.sync.aligned;" ::: "memory")
#define WG_WAIT(n) asm volatile("wgmma.wait_group.sync.aligned " #n ";" ::: "memory")
template <int N> __device__ __forceinline__ void reg_fence(float (&d)[N]) {
#pragma unroll
  for (int i = 0; i < N; i++) asm volatile("" : "+f"(d[i])::"memory");
}
template <int N> __device__ __forceinline__ void reg_fence(uint32_t (&d)[N]) {
#pragma unroll
  for (int i = 0; i < N; i++) asm volatile("" : "+r"(d[i])::"memory");
}
__device__ __forceinline__ constexpr uint64_t desc_hi(uint32_t lbo, uint32_t sbo, uint64_t sw) {
  return ((uint64_t)(lbo >> 4) << 16) | ((uint64_t)(sbo >> 4) << 32) | (sw << 62);
}
__device__ __forceinline__ uint64_t mkdesc(uint32_t addr, uint64_t hi) { return hi | (uint64_t)((addr & 0x3FFFF) >> 4); }
__device__ __forceinline__ uint32_t pack_bf16(float lo, float hi) { uint32_t r; asm("cvt.rn.bf16x2.f32 %0, %1, %2;" : "=r"(r) : "f"(hi), "f"(lo)); return r; }
__device__ __forceinline__ float bf_lo(uint32_t v) { return __uint_as_float(v << 16); }
__device__ __forceinline__ float bf_hi(uint32_t v) { return __uint_as_float(v & 0xffff0000u); }
__device__ __forceinline__ uint32_t hadd2(uint32_t a, uint32_t b) { uint32_t r; asm("add.rn.bf16x2 %0, %1, %2;" : "=r"(r) : "r"(a), "r"(b)); return r; }
__device__ __forceinline__ uint32_t hsub2(uint32_t a, uint32_t b) { uint32_t r; asm("sub.rn.bf16x2 %0, %1, %2;" : "=r"(r) : "r"(a), "r"(b)); return r; }
__device__ __forceinline__ uint32_t hmul2(uint32_t a, uint32_t b) { uint32_t r; asm("mul.rn.bf16x2 %0, %1, %2;" : "=r"(r) : "r"(a), "r"(b)); return r; }
__device__ __forceinline__ float rbf(float x) { return __bfloat162float(__float2bfloat16_rn(x)); }
__device__ __forceinline__ float ex2(float x) { float y; asm("ex2.approx.ftz.f32 %0, %1;" : "=f"(y) : "f"(x)); return y; }
__device__ __forceinline__ float rcp(float x) { float y; asm("rcp.approx.ftz.f32 %0, %1;" : "=f"(y) : "f"(x)); return y; }
__device__ __forceinline__ float sigmoid_f(float x) { return rcp(1.f + ex2(x * -1.4426950408889634f)); }
__device__ __forceinline__ float silu_f(float x) { return x * sigmoid_f(x); }

__device__ __forceinline__ void wg_ss192t(float (&d)[96], uint64_t da, uint64_t db, int sd) {
  asm volatile("{\n.reg .pred p;\nsetp.ne.b32 p, %98, 0;\n"
    "wgmma.mma_async.sync.aligned.m64n192k16.f32.bf16.bf16 {%0,%1,%2,%3,%4,%5,%6,%7,%8,%9,%10,%11,%12,%13,%14,%15,%16,%17,%18,%19,%20,%21,%22,%23,%24,%25,%26,%27,%28,%29,%30,%31,%32,%33,%34,%35,%36,%37,%38,%39,%40,%41,%42,%43,%44,%45,%46,%47,%48,%49,%50,%51,%52,%53,%54,%55,%56,%57,%58,%59,%60,%61,%62,%63,%64,%65,%66,%67,%68,%69,%70,%71,%72,%73,%74,%75,%76,%77,%78,%79,%80,%81,%82,%83,%84,%85,%86,%87,%88,%89,%90,%91,%92,%93,%94,%95}, %96, %97, p, 1, 1, 0, 1;\n}\n"
    : "+f"(d[0]),"+f"(d[1]),"+f"(d[2]),"+f"(d[3]),"+f"(d[4]),"+f"(d[5]),"+f"(d[6]),"+f"(d[7]),"+f"(d[8]),"+f"(d[9]),"+f"(d[10]),"+f"(d[11]),"+f"(d[12]),"+f"(d[13]),"+f"(d[14]),"+f"(d[15]),"+f"(d[16]),"+f"(d[17]),"+f"(d[18]),"+f"(d[19]),"+f"(d[20]),"+f"(d[21]),"+f"(d[22]),"+f"(d[23]),"+f"(d[24]),"+f"(d[25]),"+f"(d[26]),"+f"(d[27]),"+f"(d[28]),"+f"(d[29]),"+f"(d[30]),"+f"(d[31]),"+f"(d[32]),"+f"(d[33]),"+f"(d[34]),"+f"(d[35]),"+f"(d[36]),"+f"(d[37]),"+f"(d[38]),"+f"(d[39]),"+f"(d[40]),"+f"(d[41]),"+f"(d[42]),"+f"(d[43]),"+f"(d[44]),"+f"(d[45]),"+f"(d[46]),"+f"(d[47]),"+f"(d[48]),"+f"(d[49]),"+f"(d[50]),"+f"(d[51]),"+f"(d[52]),"+f"(d[53]),"+f"(d[54]),"+f"(d[55]),"+f"(d[56]),"+f"(d[57]),"+f"(d[58]),"+f"(d[59]),"+f"(d[60]),"+f"(d[61]),"+f"(d[62]),"+f"(d[63]),"+f"(d[64]),"+f"(d[65]),"+f"(d[66]),"+f"(d[67]),"+f"(d[68]),"+f"(d[69]),"+f"(d[70]),"+f"(d[71]),"+f"(d[72]),"+f"(d[73]),"+f"(d[74]),"+f"(d[75]),"+f"(d[76]),"+f"(d[77]),"+f"(d[78]),"+f"(d[79]),"+f"(d[80]),"+f"(d[81]),"+f"(d[82]),"+f"(d[83]),"+f"(d[84]),"+f"(d[85]),"+f"(d[86]),"+f"(d[87]),"+f"(d[88]),"+f"(d[89]),"+f"(d[90]),"+f"(d[91]),"+f"(d[92]),"+f"(d[93]),"+f"(d[94]),"+f"(d[95])
    : "l"(da), "l"(db), "r"(sd));
}
__device__ __forceinline__ void wg_rs64(float (&d)[32], uint32_t a0, uint32_t a1, uint32_t a2, uint32_t a3, uint64_t db, int sd) {
  asm volatile("{\n.reg .pred p;\nsetp.ne.b32 p, %37, 0;\n"
    "wgmma.mma_async.sync.aligned.m64n64k16.f32.bf16.bf16 {%0,%1,%2,%3,%4,%5,%6,%7,%8,%9,%10,%11,%12,%13,%14,%15,%16,%17,%18,%19,%20,%21,%22,%23,%24,%25,%26,%27,%28,%29,%30,%31}, {%32,%33,%34,%35}, %36, p, 1, 1, 0;\n}\n"
    : "+f"(d[0]),"+f"(d[1]),"+f"(d[2]),"+f"(d[3]),"+f"(d[4]),"+f"(d[5]),"+f"(d[6]),"+f"(d[7]),"+f"(d[8]),"+f"(d[9]),"+f"(d[10]),"+f"(d[11]),"+f"(d[12]),"+f"(d[13]),"+f"(d[14]),"+f"(d[15]),"+f"(d[16]),"+f"(d[17]),"+f"(d[18]),"+f"(d[19]),"+f"(d[20]),"+f"(d[21]),"+f"(d[22]),"+f"(d[23]),"+f"(d[24]),"+f"(d[25]),"+f"(d[26]),"+f"(d[27]),"+f"(d[28]),"+f"(d[29]),"+f"(d[30]),"+f"(d[31])
    : "r"(a0), "r"(a1), "r"(a2), "r"(a3), "l"(db), "r"(sd));
}
__device__ __forceinline__ void wg_rs192t(float (&d)[96], uint32_t a0, uint32_t a1, uint32_t a2, uint32_t a3, uint64_t db, int sd) {
  asm volatile("{\n.reg .pred p;\nsetp.ne.b32 p, %101, 0;\n"
    "wgmma.mma_async.sync.aligned.m64n192k16.f32.bf16.bf16 {%0,%1,%2,%3,%4,%5,%6,%7,%8,%9,%10,%11,%12,%13,%14,%15,%16,%17,%18,%19,%20,%21,%22,%23,%24,%25,%26,%27,%28,%29,%30,%31,%32,%33,%34,%35,%36,%37,%38,%39,%40,%41,%42,%43,%44,%45,%46,%47,%48,%49,%50,%51,%52,%53,%54,%55,%56,%57,%58,%59,%60,%61,%62,%63,%64,%65,%66,%67,%68,%69,%70,%71,%72,%73,%74,%75,%76,%77,%78,%79,%80,%81,%82,%83,%84,%85,%86,%87,%88,%89,%90,%91,%92,%93,%94,%95}, {%96,%97,%98,%99}, %100, p, 1, 1, 1;\n}\n"
    : "+f"(d[0]),"+f"(d[1]),"+f"(d[2]),"+f"(d[3]),"+f"(d[4]),"+f"(d[5]),"+f"(d[6]),"+f"(d[7]),"+f"(d[8]),"+f"(d[9]),"+f"(d[10]),"+f"(d[11]),"+f"(d[12]),"+f"(d[13]),"+f"(d[14]),"+f"(d[15]),"+f"(d[16]),"+f"(d[17]),"+f"(d[18]),"+f"(d[19]),"+f"(d[20]),"+f"(d[21]),"+f"(d[22]),"+f"(d[23]),"+f"(d[24]),"+f"(d[25]),"+f"(d[26]),"+f"(d[27]),"+f"(d[28]),"+f"(d[29]),"+f"(d[30]),"+f"(d[31]),"+f"(d[32]),"+f"(d[33]),"+f"(d[34]),"+f"(d[35]),"+f"(d[36]),"+f"(d[37]),"+f"(d[38]),"+f"(d[39]),"+f"(d[40]),"+f"(d[41]),"+f"(d[42]),"+f"(d[43]),"+f"(d[44]),"+f"(d[45]),"+f"(d[46]),"+f"(d[47]),"+f"(d[48]),"+f"(d[49]),"+f"(d[50]),"+f"(d[51]),"+f"(d[52]),"+f"(d[53]),"+f"(d[54]),"+f"(d[55]),"+f"(d[56]),"+f"(d[57]),"+f"(d[58]),"+f"(d[59]),"+f"(d[60]),"+f"(d[61]),"+f"(d[62]),"+f"(d[63]),"+f"(d[64]),"+f"(d[65]),"+f"(d[66]),"+f"(d[67]),"+f"(d[68]),"+f"(d[69]),"+f"(d[70]),"+f"(d[71]),"+f"(d[72]),"+f"(d[73]),"+f"(d[74]),"+f"(d[75]),"+f"(d[76]),"+f"(d[77]),"+f"(d[78]),"+f"(d[79]),"+f"(d[80]),"+f"(d[81]),"+f"(d[82]),"+f"(d[83]),"+f"(d[84]),"+f"(d[85]),"+f"(d[86]),"+f"(d[87]),"+f"(d[88]),"+f"(d[89]),"+f"(d[90]),"+f"(d[91]),"+f"(d[92]),"+f"(d[93]),"+f"(d[94]),"+f"(d[95])
    : "r"(a0), "r"(a1), "r"(a2), "r"(a3), "l"(db), "r"(sd));
}
__device__ __forceinline__ void wg_ss160t(float (&d)[80], uint64_t da, uint64_t db, int sd) {
  asm volatile("{\n.reg .pred p;\nsetp.ne.b32 p, %82, 0;\n"
    "wgmma.mma_async.sync.aligned.m64n160k16.f32.bf16.bf16 {%0,%1,%2,%3,%4,%5,%6,%7,%8,%9,%10,%11,%12,%13,%14,%15,%16,%17,%18,%19,%20,%21,%22,%23,%24,%25,%26,%27,%28,%29,%30,%31,%32,%33,%34,%35,%36,%37,%38,%39,%40,%41,%42,%43,%44,%45,%46,%47,%48,%49,%50,%51,%52,%53,%54,%55,%56,%57,%58,%59,%60,%61,%62,%63,%64,%65,%66,%67,%68,%69,%70,%71,%72,%73,%74,%75,%76,%77,%78,%79}, %80, %81, p, 1, 1, 0, 1;\n}\n"
    : "+f"(d[0]),"+f"(d[1]),"+f"(d[2]),"+f"(d[3]),"+f"(d[4]),"+f"(d[5]),"+f"(d[6]),"+f"(d[7]),"+f"(d[8]),"+f"(d[9]),"+f"(d[10]),"+f"(d[11]),"+f"(d[12]),"+f"(d[13]),"+f"(d[14]),"+f"(d[15]),"+f"(d[16]),"+f"(d[17]),"+f"(d[18]),"+f"(d[19]),"+f"(d[20]),"+f"(d[21]),"+f"(d[22]),"+f"(d[23]),"+f"(d[24]),"+f"(d[25]),"+f"(d[26]),"+f"(d[27]),"+f"(d[28]),"+f"(d[29]),"+f"(d[30]),"+f"(d[31]),"+f"(d[32]),"+f"(d[33]),"+f"(d[34]),"+f"(d[35]),"+f"(d[36]),"+f"(d[37]),"+f"(d[38]),"+f"(d[39]),"+f"(d[40]),"+f"(d[41]),"+f"(d[42]),"+f"(d[43]),"+f"(d[44]),"+f"(d[45]),"+f"(d[46]),"+f"(d[47]),"+f"(d[48]),"+f"(d[49]),"+f"(d[50]),"+f"(d[51]),"+f"(d[52]),"+f"(d[53]),"+f"(d[54]),"+f"(d[55]),"+f"(d[56]),"+f"(d[57]),"+f"(d[58]),"+f"(d[59]),"+f"(d[60]),"+f"(d[61]),"+f"(d[62]),"+f"(d[63]),"+f"(d[64]),"+f"(d[65]),"+f"(d[66]),"+f"(d[67]),"+f"(d[68]),"+f"(d[69]),"+f"(d[70]),"+f"(d[71]),"+f"(d[72]),"+f"(d[73]),"+f"(d[74]),"+f"(d[75]),"+f"(d[76]),"+f"(d[77]),"+f"(d[78]),"+f"(d[79])
    : "l"(da), "l"(db), "r"(sd));
}
__device__ __forceinline__ void wg_ss80t(float (&d)[40], uint64_t da, uint64_t db, int sd) {
  asm volatile("{\n.reg .pred p;\nsetp.ne.b32 p, %42, 0;\n"
    "wgmma.mma_async.sync.aligned.m64n80k16.f32.bf16.bf16 {%0,%1,%2,%3,%4,%5,%6,%7,%8,%9,%10,%11,%12,%13,%14,%15,%16,%17,%18,%19,%20,%21,%22,%23,%24,%25,%26,%27,%28,%29,%30,%31,%32,%33,%34,%35,%36,%37,%38,%39}, %40, %41, p, 1, 1, 0, 1;\n}\n"
    : "+f"(d[0]),"+f"(d[1]),"+f"(d[2]),"+f"(d[3]),"+f"(d[4]),"+f"(d[5]),"+f"(d[6]),"+f"(d[7]),"+f"(d[8]),"+f"(d[9]),"+f"(d[10]),"+f"(d[11]),"+f"(d[12]),"+f"(d[13]),"+f"(d[14]),"+f"(d[15]),"+f"(d[16]),"+f"(d[17]),"+f"(d[18]),"+f"(d[19]),"+f"(d[20]),"+f"(d[21]),"+f"(d[22]),"+f"(d[23]),"+f"(d[24]),"+f"(d[25]),"+f"(d[26]),"+f"(d[27]),"+f"(d[28]),"+f"(d[29]),"+f"(d[30]),"+f"(d[31]),"+f"(d[32]),"+f"(d[33]),"+f"(d[34]),"+f"(d[35]),"+f"(d[36]),"+f"(d[37]),"+f"(d[38]),"+f"(d[39])
    : "l"(da), "l"(db), "r"(sd));
}

struct Maps { CUtensorMap x, xn, wq, k, v, wo, w3[2], xg, xe, out; };
struct Params {
  const __nv_bfloat16 *x, *wr, *wg, *wu, *wd, *k, *v;
  Scratch* s;
};

__device__ __forceinline__ void side_cta(const Params& p, int sc, unsigned epoch, float* sm) {
  const int tid = threadIdx.x, lane = tid & 31, warp = tid >> 5;
  int budget = WAIT_BUDGET;
  float* s_x = sm;
  float* s_red = sm + 1280;
  float* s_h = s_red + 6144;
  uint4* s_c = (uint4*)(s_h + 768);
  uint2* s_st = (uint2*)(s_c + 16);
  constexpr int DEPTH = 7, STEP = 4 * 6144;
  const uint32_t ring = smem_u32(s_st + 512) + tid * 16;
  const int cg = tid % 96, ks = tid / 96, cd = tid % 80, kd = tid / 80;
  const __nv_bfloat16* wp = (cg < 48 ? p.wg : p.wu) + (size_t)(ks * 160) * FF + sc * 384 + (cg % 48) * 8;
  int kf = 0, pitch = FF;
  uint32_t slot = ring;
  auto refill = [&]() {
    if (kf == 40) { wp = p.wd + (size_t)(sc * 384 + kd * 96) * DM + cd * 8; pitch = DM; }
    if (kf < (tid < 320 ? 64 : 40)) {
#pragma unroll
      for (int j = 0; j < 4; j++) asm volatile("cp.async.cg.shared.global.L2::cache_hint [%0], [%1], 16, %2;" ::"r"(slot + j * 6144), "l"(wp + j * pitch), "l"(POL_FIRST) : "memory");
    }
    asm volatile("cp.async.commit_group;" ::: "memory");
    wp += 4 * pitch; kf++;
    slot += STEP; if (slot == ring + DEPTH * STEP) slot = ring;
  };
  auto gemv = [&](int n, const float* x0, const float* x1, float* out) {
    float a[2][8] = {};
#pragma unroll 1
    for (int k = 0; k < n; k += 4) {
      refill();
      asm volatile("cp.async.wait_group %0;" ::"n"(DEPTH - 1) : "memory");
      const float4 f0 = *(const float4*)(x0 + k), f1 = *(const float4*)(x1 + k);
      const float y0[4] = {f0.x, f0.y, f0.z, f0.w}, y1[4] = {f1.x, f1.y, f1.z, f1.w};
#pragma unroll
      for (int j = 0; j < 4; j++) {
        const uint4 v = lds128(slot + j * 6144);
        const uint32_t u[4] = {v.x, v.y, v.z, v.w};
#pragma unroll
        for (int i = 0; i < 4; i++) {
          a[0][2 * i] += y0[j] * bf_lo(u[i]); a[0][2 * i + 1] += y0[j] * bf_hi(u[i]);
          a[1][2 * i] += y1[j] * bf_lo(u[i]); a[1][2 * i + 1] += y1[j] * bf_hi(u[i]);
        }
      }
    }
#pragma unroll
    for (int i = 0; i < 16; i++) out[(i >> 3) * 768 + (i & 7)] = a[i >> 3][i & 7];
  };
  auto load_row = [&](const __nv_bfloat16* r, uint32_t (&v)[10]) {
    const uint4 a = __ldg((const uint4*)r + lane), b = __ldg((const uint4*)r + 32 + lane);
    const uint2 c = __ldg((const uint2*)r + 128 + lane);
    v[0] = a.x; v[1] = a.y; v[2] = a.z; v[3] = a.w; v[4] = b.x; v[5] = b.y; v[6] = b.z; v[7] = b.w; v[8] = c.x; v[9] = c.y;
  };
  uint32_t wr[10], xb[3][10];
  load_row(p.wr, wr);
#pragma unroll 1
  for (int i = tid; i < 512; i += 384) {
    uint4 v;
    do v = ld_pkt(p.s->stat + sc * 512 + i); while (v.x != epoch + 1 && --budget >= 0);
    s_st[i] = make_uint2(v.w, v.y);
  }
  __syncthreads();
#pragma unroll
  for (int b = 0; b < 3; b++) load_row(p.x + (size_t)(sc * 512 + warp + 12 * b) * DM, xb[b]);
#pragma unroll 1
  for (int k = 0; k < DEPTH - 1; k++) refill();
  float v0 = -INFINITY, v1 = -INFINITY; int i0 = 0xfff, i1 = 0xfff;
  auto better = [](float a, int ia, float b, int ib) { return a > b || (a == b && ia < ib); };
  auto push = [&](float v, int i) {
    if (better(v, i, v0, i0)) { v1 = v0; i1 = i0; v0 = v; i0 = i; }
    else if (better(v, i, v1, i1)) { v1 = v; i1 = i; }
  };
  auto push2 = [&](uint4 c) { push(__uint_as_float(c.x), c.y & 0xfff); push(__uint_as_float(c.z), c.w & 0xfff); };
#pragma unroll 1
  for (int l3 = warp; l3 < 512; l3 += 36) {
#pragma unroll
    for (int b = 0; b < 3; b++) {
      const int lr = l3 + 12 * b;
      if (lr >= 512) break;
      const uint2 st = s_st[lr];
      uint32_t v[10];
#pragma unroll
      for (int i = 0; i < 10; i++) v[i] = hsub2(xb[b][i], st.x);
      if (lr + 36 < 512) load_row(p.x + (size_t)(sc * 512 + lr + 36) * DM, xb[b]);
      float r0 = 0.f, r1 = 0.f;
#pragma unroll
      for (int i = 0; i < 10; i++) {
        const uint32_t xn = pack_bf16(bf_lo(v[i]) * __uint_as_float(st.y), bf_hi(v[i]) * __uint_as_float(st.y));
        r0 = fmaf(bf_lo(xn), bf_lo(wr[i]), r0); r1 = fmaf(bf_hi(xn), bf_hi(wr[i]), r1);
      }
      r0 += r1;
#pragma unroll
      for (int o = 16; o > 0; o >>= 1) r0 += __shfl_xor_sync(~0u, r0, o);
      push(rbf(r0), sc * 512 + lr);
    }
  }
  if (lane == 0) s_c[warp] = make_uint4(__float_as_uint(v0), i0, __float_as_uint(v1), i1);
  __syncthreads();
#pragma unroll 1
  for (int w = 1; w < 12; w++) push2(s_c[(warp + w) % 12]);
  const uint32_t tag = (epoch + 1) << 12;
  if (tid == 0) st_pkt(p.s->cand + sc, __float_as_uint(v0), i0 | tag, __float_as_uint(v1), i1);
  {
    uint4 c;
    do c = ld_pkt(p.s->cand + (lane & 3)); while (((c.y ^ tag) >> 12) && --budget >= 0);
#pragma unroll 1
    for (int w = 1; w < 4; w++) { const int o = (sc + w) & 3; push2(make_uint4(__shfl_sync(~0u, c.x, o), __shfl_sync(~0u, c.y, o), __shfl_sync(~0u, c.z, o), __shfl_sync(~0u, c.w, o))); }
  }
  if (i0 >= SQ) i0 = 0;
  if (i1 >= SQ) i1 = (i0 == 0) ? 1 : 0;
  if (tid < 320) {
    const int row = tid < 160 ? i0 : i1;
    const uint2 u = __ldg((const uint2*)(p.x + (size_t)row * DM) + tid % 160);
    uint4 st;
    do st = ld_pkt(p.s->stat + row); while (st.x != epoch + 1 && --budget >= 0);
    const uint32_t d0 = hsub2(u.x, st.w), d1 = hsub2(u.y, st.w);
    const float inv = __uint_as_float(st.y);
    ((float4*)s_x)[tid] = make_float4(rbf(bf_lo(d0) * inv), rbf(bf_hi(d0) * inv), rbf(bf_lo(d1) * inv), rbf(bf_hi(d1) * inv));
  }
  __syncthreads();
  gemv(160, s_x + ks * 160, s_x + DM + ks * 160, s_red + ks * 1536 + cg * 8);
  __syncthreads();
#pragma unroll
  for (int t = 0; t < 2; t++) {
    float g = 0.f, u = 0.f;
#pragma unroll
    for (int k = 0; k < 4; k++) { g += s_red[(k * 2 + t) * 768 + tid]; u += s_red[(k * 2 + t) * 768 + 384 + tid]; }
    s_h[t * 384 + tid] = rbf(rbf(silu_f(rbf(g))) * rbf(u));
  }
  __syncthreads();
  if (tid < 320) gemv(96, s_h + kd * 96, s_h + 384 + kd * 96, s_red + kd * 1536 + cd * 8);
  __syncthreads();
  const int o4 = tid + (tid < 160 ? 0 : 32);
  if (tid < 320) {
    const float4 *r = (const float4*)s_red + o4, a = r[0], b = r[384], c = r[768], d = r[1152];
    ((float4*)p.s->ffn)[sc * 320 + tid] = make_float4(a.x + b.x + c.x + d.x, a.y + b.y + c.y + d.y, a.z + b.z + c.z + d.z, a.w + b.w + c.w + d.w);
  }
  __syncthreads();
  if (tid == 0) { __threadfence(); s_c[0].x = (atomicAdd(&p.s->flag[FL_SIDE], 1u) & 3u) == 3u; __threadfence(); }
  __syncthreads();
  if (s_c[0].x) {
    if (tid < 320) {
      const float4 *r = (const float4*)p.s->ffn + tid, a = __ldcg(r), b = __ldcg(r + 320), c = __ldcg(r + 640), d = __ldcg(r + 960), x = ((float4*)s_x)[tid];
      const float rs = rbf(sigmoid_f(tid < 160 ? v0 : v1));
      auto gate = [&](float xn, float y) { return silu_f(rbf(xn + rbf(rbf(y) * rs))); };
      if (tid == 0) { p.s->sel[0] = i0; p.s->sel[1] = i1; }
      ((uint2*)p.s->gsel)[tid] =
          make_uint2(pack_bf16(gate(x.x, a.x + b.x + c.x + d.x), gate(x.y, a.y + b.y + c.y + d.y)), pack_bf16(gate(x.z, a.z + b.z + c.z + d.z), gate(x.w, a.w + b.w + c.w + d.w)));
    }
    __syncthreads();
    if (tid == 0) red_release(&p.s->flag[FL_FFN]);
  }
}

constexpr float SM_C = 0.07216878364870322f * 1.4426950408889634f;

#define LD 0
#define LS 3
__device__ __forceinline__ void ln_piece(const Params& p, uint32_t (&r)[48], int k, int row, int l16) {
  auto f = [&](int i) { return __uint_as_float(r[i]); };
  if (k == LD) {
#pragma unroll
    for (int i = 0; i < 5; i++) {
      const uint4 v = ldg_nc((const uint4*)(p.x + (size_t)row * DM) + i * 16 + l16);
      r[4 * i] = v.x; r[4 * i + 1] = v.y; r[4 * i + 2] = v.z; r[4 * i + 3] = v.w;
    }
    asm volatile("ld.relaxed.gpu.global.v2.u32 {%0,%1}, [%2];" : "=r"(r[20]), "=r"(r[21]) : "l"(&p.s->done));
  } else if (k == LS || k == LS + 1) {
    if (k == LS) { r[22] = __shfl_sync(~0u, r[0], 0, 16) << 16; r[23] = r[24] = 0; }
    float s0 = f(23), s1 = 0.f, q0 = f(24), q1 = 0.f;
#pragma unroll
    for (int i = 10 * (k - LS); i < 10 * (k - LS) + 10; i++) {
      const float a = bf_lo(r[i]) - f(22), b = bf_hi(r[i]) - f(22);
      s0 += a; s1 += b; q0 = fmaf(a, a, q0); q1 = fmaf(b, b, q1);
    }
    r[23] = __float_as_uint(s0 + s1); r[24] = __float_as_uint(q0 + q1);
  } else if (k == LS + 2) {
    float s0 = f(23), q0 = f(24);
#pragma unroll
    for (int o = 8; o > 0; o >>= 1) { s0 += __shfl_xor_sync(~0u, s0, o); q0 += __shfl_xor_sync(~0u, q0, o); }
    s0 *= 1.f / DM;
    const float mean = f(22) + s0, var = rbf(fmaxf(fmaf(q0, 1.f / DM, -s0 * s0), 0.f));
    float sd; asm("sqrt.approx.ftz.f32 %0, %1;" : "=f"(sd) : "f"(rbf(var + 1e-5f)));
    const float inv = rcp(rbf(sd));
    r[22] = pack_bf16(mean, mean); r[23] = __float_as_uint(inv * SM_C);
    const uint32_t tag = __funnelshift_r(r[20], r[21], 7) + 1;
    if (l16 == 0) st_pkt(&p.s->stat[row], tag, __float_as_uint(inv), tag, r[22]);
  } else if (k > LS + 2 && k <= LS + 5) {
#pragma unroll
    for (int j = 2 * (k - LS - 3); j < 2 * (k - LS - 3) + 2 && j < 5; j++) {
#pragma unroll
      for (int i = 4 * j; i < 4 * j + 4; i++) { const uint32_t d = hsub2(r[i], r[22]); r[i] = pack_bf16(bf_lo(d) * f(23), bf_hi(d) * f(23)); }
      *((uint4*)(p.s->xn + (size_t)row * DM) + j * 16 + l16) = make_uint4(r[4 * j], r[4 * j + 1], r[4 * j + 2], r[4 * j + 3]);
    }
  }
}

constexpr float SM_HI = 0x1p64f, SM_LO = 0x1p-64f;
__device__ __forceinline__ void exp_block(float (&s)[32], float& l0, float& l1, int from = 0, int to = 32) {
#pragma unroll
  for (int i = from; i < to; i++) { s[i] = ex2(s[i]); if (i & 2) l1 += s[i]; else l0 += s[i]; }
}
__device__ __forceinline__ float quad_sum(float v) { v += __shfl_xor_sync(~0u, v, 1); return v + __shfl_xor_sync(~0u, v, 2); }
__device__ __forceinline__ float quad_max(float v) { v = fmaxf(v, __shfl_xor_sync(~0u, v, 1)); return fmaxf(v, __shfl_xor_sync(~0u, v, 2)); }
__device__ __noinline__ void safe_head(const uint32_t* kp, const uint32_t* vp, uint4* io) {
  uint32_t fq[48];
#pragma unroll
  for (int i = 0; i < 12; i++) { const uint4 v = io[(i >> 1) * 512 + (i & 1) * 32]; fq[4 * i] = v.x; fq[4 * i + 1] = v.y; fq[4 * i + 2] = v.z; fq[4 * i + 3] = v.w; }
  float m0 = -INFINITY, m1 = -INFINITY;
#pragma unroll 1
  for (int pass = 0; pass < 3; pass++) {
    float o[48] = {}, l0 = 0.f, l1 = 0.f;
#pragma unroll 1
    for (int n = 0; n < 64; n++) {
      const uint32_t *kr = kp + n * (8 * DH / 2), *vr = vp + n * (8 * DH / 2) + (pass - 1) * 48;
      float d[4] = {};
#pragma unroll
      for (int t = 0; t < 12; t++)
        asm volatile("mma.sync.aligned.m16n8k16.row.col.f32.bf16.bf16.f32 {%0,%1,%2,%3}, {%4,%5,%6,%7}, {%8,%9}, {%0,%1,%2,%3};"
                     : "+f"(d[0]), "+f"(d[1]), "+f"(d[2]), "+f"(d[3])
                     : "r"(fq[4 * t]), "r"(fq[4 * t + 1]), "r"(fq[4 * t + 2]), "r"(fq[4 * t + 3]), "r"(__ldg(kr + 8 * t)), "r"(__ldg(kr + 8 * t + 4)));
      if (pass == 0) { m0 = fmaxf(m0, fmaxf(d[0], d[1])); m1 = fmaxf(m1, fmaxf(d[2], d[3])); continue; }
      d[0] = ex2(d[0] - m0); d[1] = ex2(d[1] - m0); d[2] = ex2(d[2] - m1); d[3] = ex2(d[3] - m1);
      l0 += d[0] + d[1]; l1 += d[2] + d[3];
      const uint32_t p0 = pack_bf16(d[0], d[1]), p1 = pack_bf16(d[2], d[3]);
#pragma unroll
      for (int c = 0; c < 12; c++)
        asm volatile("{\n.reg .b32 t;\nmovmatrix.sync.aligned.m8n8.trans.b16 t, %6;\n"
                     "mma.sync.aligned.m16n8k8.row.col.f32.bf16.bf16.f32 {%0,%1,%2,%3}, {%4,%5}, {t}, {%0,%1,%2,%3};\n}\n"
                     : "+f"(o[4 * c]), "+f"(o[4 * c + 1]), "+f"(o[4 * c + 2]), "+f"(o[4 * c + 3]) : "r"(p0), "r"(p1), "r"(__ldg(vr + 4 * c)));
    }
    if (pass == 0) { m0 = quad_max(m0); m1 = quad_max(m1); continue; }
    l0 = rcp(quad_sum(l0)); l1 = rcp(quad_sum(l1));
#pragma unroll
    for (int i = 0; i < 6; i++) {
      const float* v = o + 16 * (i >> 1) + 2 * (i & 1);
      const float r = i & 1 ? l1 : l0;
      io[(3 * (pass - 1) + (i >> 1)) * 512 + (i & 1) * 32] =
          make_uint4(pack_bf16(v[0] * r, v[1] * r), pack_bf16(v[4] * r, v[5] * r), pack_bf16(v[8] * r, v[9] * r), pack_bf16(v[12] * r, v[13] * r));
    }
  }
}

#define CVG 48
#define NE 8
#define PS1 8
#define CSW 1400
#define D0 2
#define LQ 6
__device__ __forceinline__ constexpr int end_stage(int n) { return n < 4 ? n : n < LQ ? n - 4 : n == LQ ? 4 : n % 5; }
#define Q2N 1
#define SWN 12
#define SCH 0
__device__ __forceinline__ constexpr int sent(int n) {
  constexpr int t[4][15] = {{0, 2, 4, 5, 5, 6, 7, 8,  9, 10, 11, 12, 13, 14, 15},
                            {0, 2, 4, 5, 5, 6, 7, 8,  9, 10, 12, 13, 14, 15, 15},
                            {0, 2, 4, 5, 5, 7, 8, 9, 10, 10, 12, 14, 15, 15, 15},
                            {0, 2, 4, 5, 5, 7, 8, 9, 10, 10, 13, 15, 15, 15, 15}};
  return n < LQ + 2 ? 0 : LQ == 6 && n == 8 ? 3 : t[SCH][n - 6];
}
template <int N> struct IntC { static constexpr int value = N; };
template <int N, int I = 0, class F> __device__ __forceinline__ void static_for(F&& f) { if constexpr (I < N) { f(IntC<I>{}); static_for<N, I + 1>(f); } }

extern __shared__ __align__(1024) uint8_t smem_raw[];
constexpr uint32_t EA = 160, EB = 184;
#define SMEM_LAYOUT                                                                                                          \
  [[maybe_unused]] const uint32_t sb = smem_u32(smem_raw), bar_a = sb + OFF_M, bar_b = bar_a + 40, bar_x = bar_a + 88,      \
      bar_u = bar_a + 96, bar_e = bar_a + 104, bar_o = bar_a + 200, bar_w = bar_a + 208, bar_z = bar_a + 288,                \
      bar_s = bar_a + 296, bar_d = bar_a + 304, s_stat = bar_a + 512, s_sel = s_stat + 1024;

__device__ __forceinline__ int k_block(int t, int hg) {
  const int i = (t * 11) >> 5;
  return ((i < 6 ? (hg & 6) + (i & 1) : hg ^ (i & 1)) * 4 + (i >> 1)) * 6 + (t == 3 * i ? 4 : 2 * (t - 3 * i) - 2);
}

__device__ __noinline__ int errands(Scratch* s, const Maps& m, int warp, uint32_t tag, int budget) {
  SMEM_LAYOUT
  const int lane = threadIdx.x & 31, cl = blockIdx.x >> 1, qt = (cl >> 3) * 2 + (blockIdx.x & 1), hg = cl & 7, kq = hg >> 1, nh = hg & 1;
  if (warp == 1) {
#pragma unroll 1
    for (int u = 0; u < 5; u++) {
      mbar_wait(bar_o, u & 1);
      if (lane == 0) red_release(&s->flag[u ? FL_O + (qt * 8 + hg) * 8 : FL_XN + qt * 32]);
      __syncwarp();
    }
  } else if (warp == 2) {
    mbar_wait(bar_x, 0, budget);
    while ((int)(ld_acquire(&s->flag[FL_FFN]) - tag) < 0 && --budget >= 0) {}
    if (lane < 21) {
      const uint4 v = __ldcg(lane ? (const uint4*)(s->gsel + (lane > 10 ? DM - 80 : 0) + nh * 320 + kq * 80) + lane - 1 : (const uint4*)s->sel);
      asm volatile("st.shared.v4.u32 [%0], {%1,%2,%3,%4};" ::"r"(s_sel + 16 * lane), "r"(v.x), "r"(v.y), "r"(v.z), "r"(v.w) : "memory");
    }
    __syncwarp();
    if (lane == 0) { mbar_arrive(bar_u); asm volatile("red.relaxed.gpu.global.add.u64 [%0], 1;" ::"l"(&s->done) : "memory"); }
    while ((int)(ld_acquire(&s->flag[FL_RD + (qt * 8 + (hg ^ 1)) * 8]) - tag) < 0 && --budget >= 0) {}
    if (lane < 3) mbar_arrive(bar_z);
  } else {
    wait_flag(&s->flag[FL_XN + qt * 32], tag * 8);
    fence_proxy_async();
    mbar_wait(bar_a + EA + 32, 1);
    uint32_t a8 = 0, pha = 1;
    const int kb = (qt * 192 + k_block(lane, hg)) * 512;
#pragma unroll 1
    for (int n = 0; n < 54; n++) {
      const int t = n - 30, ko = __shfl_sync(~0u, kb, t);
      if (t == 0 || t == 18) {
        wait_flag(&s->flag[FL_O + (qt * 8 + (t ? 2 * kq + (lane & 1) : lane & 7)) * 8], tag * 4 - (t ? 0 : 1));
        fence_proxy_async();
      }
      mbar_wait(bar_a + EA + a8, pha);
      const uint32_t fb = bar_a + a8, dst = sb + a8 * (TA >> 3);
      if (elect()) {
        if (t >= 0) {
          mbar_expect_tx(fb, TA);
          bulk_load(dst, s->o + ko, TA, fb);
          if (t == 8) {
            mbar_expect_tx(bar_x, 6 * 3840);
#pragma unroll 1
            for (int e = 0; e < 6; e++) tma2d(sb + OFF_B + TW + e * TB, &m.xg, nh * 320 + kq * 80, qt * 128 + e * 24, bar_x);
            asm volatile("prefetch.tensormap [%0];\nprefetch.tensormap [%1];\nprefetch.tensormap [%2];\nprefetch.tensormap [%3];"
                         ::"l"(m.w3), "l"(m.w3 + 1), "l"(&m.xe), "l"(&m.out) : "memory");
          }
          if (t == 22) asm volatile("red.relaxed.gpu.global.add.u32 [%0], 1;" ::"l"(&s->flag[FL_RD + (qt * 8 + hg) * 8]) : "memory");
        } else if (n >= 10 && pha) mbar_arrive(fb);
        else { mbar_expect_tx(fb, TA); tma2d(dst, &m.xn, 8 * a8 + (pha || (n >= 15 && n < 20) ? 0 : 320), qt * 128, fb); }
      }
      a8 += 8; if (a8 == 40) { a8 = 0; pha ^= 1; }
    }
    if (lane < 3) mbar_arrive(bar_z);
  }
  return budget;
}

__global__ void __launch_bounds__(384, 1) __cluster_dims__(2, 1, 1)
fused_kernel(const Params p, const __grid_constant__ Maps m) {
  SMEM_LAYOUT
  const int wi = __shfl_sync(~0u, threadIdx.x >> 5, 0), wg = wi >> 2;
  const int lane = threadIdx.x & 31;
  const int cl = blockIdx.x >> 1;
  const int rank = blockIdx.x & 1;

  if (cl >= 64) {
    const unsigned epoch = (unsigned)(__ldcg(&p.s->done) >> 7);
    side_cta(p, blockIdx.x - 128, epoch, (float*)smem_raw);
    return;
  }
  const int qt = (cl >> 3) * 2 + rank, hg = cl & 7;
  const int kq = hg >> 1, nh = hg & 1;

  const int s0 = (5 * (qt >> 1)) >> 2;
  if (elect()) {
    const int c = (int)(0x5ff7700000ull >> (4 * wi) & 15) + 1;
    for (int i = 0; i < 4; i++) mbar_init(bar_a + 32 * wi + 8 * i, c);
    asm volatile("fence.mbarrier_init.release.cluster;" ::: "memory");
  }
  __syncwarp();
  cluster_arrive();
  if (wi < 2 && elect()) {
    if (wi) { asm volatile("prefetch.tensormap [%0];" ::"l"(&m.wq) : "memory"); mbar_expect_tx(bar_b, TB); mbar_expect_tx(bar_b + 8, TB); }
    else for (int i = 0; i < 2; i++) { mbar_expect_tx(bar_a + 8 * i, TA); tma2d(sb + i * TA, &m.x, 64 * (s0 + i), qt * 128, bar_a + 8 * i); }
  }
  __syncwarp();
  cluster_wait();
  if (wi == 1 && elect())
    for (int i = 0; i < 2; i++) tma4d_mc(sb + OFF_B + i * TB + rank * (TB / 2), &m.wq, 12 * hg, 8 * (s0 + i) + 4 * rank, bar_b + 8 * i);
  if (wg > 0) {
    const int w = wg - 1;
    const int cw = wi - 4;
    asm volatile("setmaxnreg.inc.sync.aligned.u32 232;");
    uint32_t fr[48];
    reg_fence(fr);
    auto ln_row = [&]() { int v = qt * 128 + hg * 16 + cw * 2 + (lane >> 4); asm volatile("" : "+r"(v)); return v; };
    uint32_t rel_addr;
    asm volatile("mapa.shared::cluster.u32 %0, %1, %2;" : "=r"(rel_addr) : "r"(bar_b + EB), "r"(lane & 1));
    auto rel_a = [&](uint32_t o8) { if (lane == 0) mbar_arrive(bar_a + EA + o8); };
    auto rel_b = [&](uint32_t o8) { if (lane < 2) mbar_arrive_cluster(rel_addr + o8); };
    uint32_t b8 = 0, phb = 0;
    auto next_pair = [&]() { b8 += 16; if (b8 == 48) { b8 = 0; phb ^= 1; } };
    const int g = lane >> 2, q = lane & 3;
    constexpr uint64_t HI_A = desc_hi(16, 1024, 1);
    constexpr uint64_t HI_W = desc_hi(1024, 3072, 1);
    constexpr uint64_t HI_O = desc_hi(2048, 512, 2);
    if (w == 1) asm volatile("bar.arrive 1, 256;" ::: "memory");

    uint32_t zero; asm volatile("mov.u32 %0, %%tid.y;" : "=r"(zero));
    float acc[96];
    uint4* optr = p.s->o + (size_t)(qt * 192 + hg * 24) * 512 + (cw * 16 + g) * 4 + (q ^ ((g >> 1) & 3));
    uint32_t rl[4];
    auto store_o = [&](int pp) {
#pragma unroll
      for (int i = (12 * pp + 8) / 9; i < (12 * (pp + 1) + 8) / 9; i++) {
#pragma unroll
        for (int k = 4 * i; k < 4 * i + 4; k++)
          asm volatile("{\n.reg .b32 t;\nmul.rn.bf16x2 t, %0, %2;\nfma.rn.bf16x2 %0, %0, %1, t;\n}\n" : "+r"(fr[k]) : "r"(rl[i & 1]), "r"(rl[2 + (i & 1)]));
        fr[4 * i] &= ~1u;
        optr[(i >> 1) * 512 + (i & 1) * 32] = make_uint4(fr[4 * i], fr[4 * i + 1], fr[4 * i + 2], fr[4 * i + 3]);
      }
      if (pp == 8) optr += 6 * 512;
    };
    auto fresh = [&]() { uint32_t v = sb; asm volatile("" : "+r"(v)); return v; };
    reg_fence(rl);

#pragma unroll 1
    for (int u = 0; u < 4; u++) {
      const uint32_t sq = fresh();
      const uint64_t dA = mkdesc(sq + w * 8192, HI_A), dB0 = mkdesc(sq + OFF_B, HI_W);
      uint32_t pb8 = 0;
#pragma unroll
      for (int s = 0; s < 10; s++) {
        const uint32_t o8 = b8 + 8 * (s & 1);
        const uint64_t dW = dB0 + o8 * (TB >> 7);
        mbar_wait(bar_a + 8 * (s % 5), s / 5);
        mbar_wait(bar_b + o8, phb);
        if (s == 9) asm volatile("bar.sync %0, 256;" ::"r"(1 + w) : "memory");
        WG_FENCE();
#pragma unroll
        for (int kk = 0; kk < 4; kk++) wg_ss192t(acc, dA + ((s % 5) * (TA >> 4) + kk * 2), dW + kk * 384, kk != 0 || s != 0);
        WG_COMMIT();
        if (s == 9) asm volatile("bar.arrive %0, 256;" ::"r"(2 - w) : "memory");
        if (s > 0) { WG_WAIT(1); rel_a(8 * ((s - 1) % 5)); rel_b(pb8); }
        if (s < 9) { if (u > 0) store_o(s); else ln_piece(p, fr, s, ln_row(), lane & 15); }
        if (s == 8) { __syncwarp(); if (lane == 0) mbar_arrive(bar_o); }
        pb8 = o8;
        if (s & 1) next_pair();
      }
      if (u == 0) {
        mbar_wait(bar_s, 0);
        const uint2 s0 = lds64(s_stat + (cw * 16 + g) * 8), s1 = lds64(s_stat + 64 + (cw * 16 + g) * 8);
        const uint32_t msk = q == 0 ? 0xffffffffu : q == 1 ? 0xffffu : 0u;
        const float c0 = SM_C * __uint_as_float(s0.y), c1 = SM_C * __uint_as_float(s1.y);
        uint32_t am[4] = {(s0.x ^ 0x80008000u) & msk, (s1.x ^ 0x80008000u) & msk, 0, 0};
        reg_fence(am);
        WG_FENCE();
        wg_rs192t(acc, am[0], am[1], am[2], am[3], mkdesc(sb, desc_hi(1024, 0, 1)), 1);
        WG_COMMIT();
        WG_WAIT(0);
        reg_fence(acc);
#pragma unroll
        for (int i = 0; i < 24; i++) { acc[4 * i] *= c0; acc[4 * i + 1] *= c0; acc[4 * i + 2] *= c1; acc[4 * i + 3] *= c1; }
      } else { WG_WAIT(0); reg_fence(acc); }
      rel_b(pb8);
      rel_a(32);
      auto pack_q = [&](int from, int to) {
#pragma unroll
        for (int i = from; i < to; i++) { fr[i] = pack_bf16(acc[2 * i], acc[2 * i + 1]); asm volatile("" : "+r"(fr[i])::"memory"); }
      };
      pack_q(0, CVG);
      float sc[32], l0 = 0.f, l1 = 0.f;
      uint32_t pf[16], k8;
      auto pack_p = [&](const float (&s_)[32], int from = 0, int to = 16) {
#pragma unroll
        for (int i = from; i < to; i++) pf[i] = pack_bf16(s_[2 * i], s_[2 * i + 1]);
      };
      auto scores = [&](int j, int pass = 11) {
        k8 = b8 + 8;
        mbar_wait(bar_b + k8, phb);
        next_pair();
        mbar_wait(bar_b + b8, phb);
        const uint64_t dk = mkdesc(sb + OFF_B, HI_W) + k8 * (TB >> 7);
        asm volatile("bar.sync %0, 256;" ::"r"(1 + w) : "memory");
        WG_FENCE();
#pragma unroll
        for (int t = 0; t < 12; t++) {
          wg_rs64(sc, fr[4 * t], fr[4 * t + 1], fr[4 * t + 2], fr[4 * t + 3], dk + (t >> 2) * 64 + (t & 3) * 2, t != 0);
          if (t == 11) WG_COMMIT();
          if (t == pass) asm volatile("bar.arrive %0, 256;" ::"r"(2 - w) : "memory");
        }
      };
      auto pv = [&](int add) {
        const uint64_t dv = mkdesc(sb + OFF_B, HI_W) + b8 * (TB >> 7);
#pragma unroll
        for (int kk = 0; kk < 4; kk++) wg_rs192t(acc, pf[4 * kk], pf[4 * kk + 1], pf[4 * kk + 2], pf[4 * kk + 3], dv + kk * 384, kk != 0 || add);
        WG_COMMIT();
      };
      auto finish = [&]() {
        WG_WAIT(1);
        reg_fence(sc);
        exp_block(sc, l0, l1);
        rel_b(k8 + (__float_as_uint(l0) & __float_as_uint(l1) & zero));
        WG_WAIT(0);
        reg_fence(acc); reg_fence(pf);
        rel_b(b8);
        pack_p(sc);
      };
      {
        mbar_wait(bar_b + b8, phb);
        const uint64_t dk = mkdesc(sb + OFF_B, HI_W) + b8 * (TB >> 7);
        asm volatile("bar.sync %0, 256;" ::"r"(1 + w) : "memory");
#pragma unroll
        for (int t = 0; t < 12; t++) {
          if (t && (4 * t) % CVG == 0) pack_q(4 * t, 4 * t + CVG);
          if ((4 * t) % CVG == 0) WG_FENCE();
          wg_rs64(sc, fr[4 * t], fr[4 * t + 1], fr[4 * t + 2], fr[4 * t + 3], dk + (t >> 2) * 64 + (t & 3) * 2, t != 0);
          if (t == 7) asm volatile("bar.arrive %0, 256;" ::"r"(2 - w) : "memory");
        }
        WG_COMMIT();
        WG_WAIT(0);
        reg_fence(sc);
        float s0[32];
#pragma unroll
        for (int i = 0; i < 32; i++) s0[i] = i < NE ? sc[i] : __uint_as_float(__float_as_uint(sc[i]) ^ zero);
        exp_block(s0, l0, l1, 0, NE);
        pack_p(s0, 0, NE / 2);
#pragma unroll
        for (int i = NE; i < 32; i++) asm volatile("" : "+f"(s0[i])::"memory");
#pragma unroll
        for (int i = 0; i < NE / 2; i++) asm volatile("" : "+r"(pf[i])::"memory");
        rel_b(b8);
        scores(1, PS1);
        const uint32_t z = lds32(s_stat) & zero;
#pragma unroll
        for (int i = NE; i < 32; i++) {
          asm("{\n.reg .pred p;\nsetp.eq.u32 p, %1, 0;\n@p ex2.approx.ftz.f32 %0, %0;\n}\n" : "+f"(s0[i]) : "r"(z));
          if (i & 2) l1 += s0[i]; else l0 += s0[i];
        }
        pack_p(s0, NE / 2, 16);
        reg_fence(pf);
        WG_FENCE();
        pv(0);
        finish();
      }
#pragma unroll 1
      for (int j = NE < 32 ? 2 : 1; j < 8; j++) { scores(j); pv(j > 1); finish(); }
      const uint32_t v8 = b8 + 8;
      mbar_wait(bar_b + v8, phb);
      next_pair();
      {
        const uint64_t dv = mkdesc(sb + OFF_B, HI_W) + v8 * (TB >> 7);
        asm volatile("bar.sync %0, 256;" ::"r"(1 + w) : "memory");
        WG_FENCE();
#pragma unroll
        for (int kk = 0; kk < 4; kk++) {
          wg_rs192t(acc, pf[4 * kk], pf[4 * kk + 1], pf[4 * kk + 2], pf[4 * kk + 3], dv + kk * 384, 1);
          if (kk == 1 && (u < 3 || w == 0)) asm volatile("bar.arrive %0, 256;" ::"r"(2 - w) : "memory");
        }
        WG_COMMIT();
      }
      l0 = quad_sum(l0); l1 = quad_sum(l1);
      const bool unsafe = __any_sync(~0u, !(l0 >= SM_LO && l1 >= SM_LO && l0 + l1 <= SM_HI));
      l0 = rcp(l0); l1 = rcp(l1);
      rl[0] = pack_bf16(l0, l0); rl[1] = pack_bf16(l1, l1);
      l0 -= bf_lo(rl[0]); l1 -= bf_lo(rl[1]);
      rl[2] = pack_bf16(l0, l0); rl[3] = pack_bf16(l1, l1);
      WG_WAIT(0);
      reg_fence(acc);
      rel_b(v8);
      if (__builtin_expect(unsafe, 0)) {
        int o = hg * 4 + u; asm volatile("" : "+r"(o));
        o = (o * SKC + (SKC - WIN) + g) * (DH / 2) + q;
#pragma unroll
        for (int i = 0; i < 12; i++) optr[(i >> 1) * 512 + (i & 1) * 32] = make_uint4(fr[4 * i], fr[4 * i + 1], fr[4 * i + 2], fr[4 * i + 3]);
        safe_head((const uint32_t*)p.k + o, (const uint32_t*)p.v + o, optr);
#pragma unroll
        for (int i = 0; i < 12; i++) { const uint4 v = optr[(i >> 1) * 512 + (i & 1) * 32]; fr[4 * i] = v.x; fr[4 * i + 1] = v.y; fr[4 * i + 2] = v.z; fr[4 * i + 3] = v.w; }
        rl[0] = rl[1] = 0x3f803f80u; rl[2] = rl[3] = 0;
      } else {
#pragma unroll
        for (int i = 0; i < 24; i++) {
          fr[8 * (i >> 2) + (i & 3)] = pack_bf16(acc[4 * i], acc[4 * i + 1]);
          fr[8 * (i >> 2) + 4 + (i & 3)] = pack_bf16(acc[4 * i + 2], acc[4 * i + 3]);
        }
      }
    }

    float aF[80], aS[80];
    uint32_t pha = 0, a8 = 0, pa8 = 0, pb8 = 0;
#pragma unroll 1
    for (int s = 0; s < 19; s++) {
      const uint64_t d0 = mkdesc(sb, HI_O), dO = d0 + (a8 * (TA >> 7) + w * 256), dB = d0 + ((OFF_B >> 4) + b8 * (TB >> 7));
      mbar_wait(bar_a + a8, pha);
      mbar_wait(bar_b + b8, phb);
      WG_FENCE();
#pragma unroll
      for (int kk = 0; kk < 4; kk++) wg_ss160t(aF, dO + ((kk >> 1) * 512 + (kk & 1) * 2), dB + ((kk >> 1) * 640 + (kk & 1) * 64), kk != 0 || s != 0);
      WG_COMMIT();
      mbar_wait(bar_b + b8 + 8, phb);
      WG_WAIT(1);
      if (s > 0) { rel_a(pa8); rel_b(pb8 + 8); }
      WG_FENCE();
#pragma unroll
      for (int kk = 0; kk < 4; kk++) wg_ss160t(aS, dO + ((kk >> 1) * 512 + (kk & 1) * 2), dB + ((TB >> 4) + (kk >> 1) * 640 + (kk & 1) * 64), kk != 0 || s != 0);
      WG_COMMIT();
      if (s < 9) {
#pragma unroll
        for (int pp = 0; pp < 9; pp++) if (s == pp) store_o(pp);
        if (s == 8) { __syncwarp(); if (lane == 0) mbar_arrive(bar_o); }
      } else if (s < 15) {
        const int b = 2 * cw + ((lane >> 3) & 1);
        uint32_t ga = sb + OFF_B + TW + ((b * 11) >> 5) * (TB - 3840) + b * 1280 + (lane & 7) * 160 + (lane >> 4) * 16;
        if (s < 14) {
          mbar_wait(bar_x, 0);
          ga += 32 * (s - 9);
          ldsm4(ga, fr);
#pragma unroll
          for (int i = 0; i < 4; i++) {
            const uint2 st = lds64(s_stat + (cw * 16 + g + 8 * (i & 1)) * 8);
            const uint32_t d = hsub2(fr[i], st.x), xn = pack_bf16(bf_lo(d) * __uint_as_float(st.y), bf_hi(d) * __uint_as_float(st.y));
            fr[i] = pack_bf16(silu_f(bf_lo(xn)), silu_f(bf_hi(xn)));
          }
          stsm4(ga, fr);
        } else {
          mbar_wait(bar_u, 0);
          const uint2 sel = lds64(s_sel);
          const uint32_t row = qt * 128 + cw * 16 + (lane & 15);
          if (row == sel.x || row == sel.y) ga = s_sel + 16 + (row == sel.y ? 160 : 0) + (lane >> 4) * 16;
#pragma unroll
          for (int k = 0; k < 5; k++) ldsm4(ga + 32 * k, fr + 4 * k);
        }
      }
      WG_WAIT(1);
      rel_b(b8);
      pa8 = a8; a8 += 8; if (a8 == 40) { a8 = 0; pha ^= 1; }
      pb8 = b8; next_pair();
    }
    const int t128 = threadIdx.x & 127;
    uint4* const xbase = p.s->o + (size_t)(qt * 192 + nh * 24 + 10) * 512 + w * 640 + t128;
    uint4* const dst = xbase + kq * (48 * 512);
    float q1[40], q2[40], oth[40], own[40];
    auto take = [&](float (&x)[40], const float* a) {
#pragma unroll
      for (int k = 0; k < 40; k++) x[k] = __uint_as_float(__float_as_uint(a[k]) ^ zero);
      reg_fence(x);
    };
    reg_fence(aF);
    take(q1, aF);
    auto fa = [&](int i) { return mbar_try(bar_a + 8 * ((4 + i) % 5), i == 0); };
    auto fb = [&](int e) { return mbar_try(bar_b + 8 * (e % 6), (e / 6) & 1); };
    auto send = [&](int m) {
      const float* v = (m < 5 ? q1 : m < 10 ? q2 : oth) + 8 * (m % 5);
      st_pkt(dst + (m / 5) * 1280 + (m % 5) * 128, pack_bf16(v[0], v[1]) | 1, pack_bf16(v[2], v[3]), pack_bf16(v[4], v[5]), pack_bf16(v[6], v[7]));
    };
    static_for<20>([&](auto n_) {
      constexpr int n = n_.value, i = end_stage(n), e = 142 + n / 2, qi = n == 4 ? 1 : n == LQ ? 0 : n / 5;
      float (&acc_)[40] = qi == 0 ? q1 : qi == 1 ? q2 : qi == 2 ? oth : own;
      if (n == 0) while (!(fa(0) & fa(1) & fb(142) & fb(143))) {}
      if (n == 2) while (!(fa(2) & fa(3) & fb(144))) {}
      if (n == LQ) while (!(fa(4) & fb(145) & fb(146) & mbar_try(bar_z, 0))) {}
      if (n == 10) while (!(fb(147) & fb(148) & fb(149))) {}
      const uint64_t d0 = mkdesc(fresh(), HI_O);
      WG_FENCE();
#pragma unroll
      for (int kk = 0; kk < 4; kk++)
        wg_ss80t(acc_, d0 + w * 256 + (((4 + i) % 5) * (TA >> 4) + (kk >> 1) * 512 + (kk & 1) * 2),
                 d0 + ((OFF_B >> 4) + (e % 6) * (TB >> 4) + (n & 1) * 768 + (kk >> 1) * 384 + (kk & 1) * 64), 1);
      WG_COMMIT();
      if ((!(n & 1) && n <= 16) || n == 15 || n == LQ + 1) WG_WAIT(1);
      if (n == 0) rel_a(24);
      if (!(n & 1) && n <= 10) rel_b(8 * ((e - 1) % 6));
      if (n == Q2N) take(q2, aF + 40);
      if (n == 10) cluster_arrive();
      if (n == 12 || n == 14 || n == 16) rel_a(4u * n - 48);
      if (n == LQ + 1) reg_fence(q1);
      if (n == 10) reg_fence(q2);
      if (n == 15) reg_fence(oth);
      if (n == 15) while (!(fb(150) & fb(151))) {}
      static_for<sent(n + 1) - sent(n)>([&](auto k_) { send(sent(n) + k_.value); });
      if (n == 8) {
        reg_fence(aS);
#pragma unroll
        for (int k = 0; k < 40; k++) oth[k] = kq & 1 ? aS[k] : aS[40 + k];
        reg_fence(oth);
      }
      if (n == SWN) {
        reg_fence(aS);
#pragma unroll
        for (int k = 0; k < 40; k++) own[k] = kq & 1 ? aS[40 + k] : aS[k];
        reg_fence(own);
      }
    });
    uint32_t xr[20];
    const uint32_t xs = sb + OFF_B + 2 * TB + cw * 2560, xa = xs + (lane & 15) * 160 + (lane >> 4) * 16;
    mbar_wait(bar_b + 16, 1);
#pragma unroll
    for (int k = 0; k < 5; k++) ldsm4(xa + 32 * k, xr + 4 * k);
    {
      auto fetch = [&](int e, uint4 (&v)[5]) {
        mbar_wait(bar_e + 16 * e + 8 * w, 0);
#pragma unroll
        for (int i = 0; i < 5; i++) v[i] = lds128(sb + OFF_B + (3 + e) * TB + (w * 640 + i * 128 + t128) * 16);
      };
      auto add = [&](int e, uint4 (&v)[5]) {
        while (!(v[0].x & v[1].x & v[2].x & v[3].x & v[4].x & 1)) {
#pragma unroll
          for (int i = 0; i < 5; i++) v[i] = ld_pkt(xbase + (kq ^ ((0x132 >> (4 * e)) & 3)) * (48 * 512) + (e < 2 ? kq & 1 : 2) * 1280 + i * 128);
        }
#pragma unroll
        for (int i = 0; i < 5; i++) {
          float* o = own + 8 * i;
          o[0] += bf_lo(v[i].x); o[1] += bf_hi(v[i].x); o[2] += bf_lo(v[i].y); o[3] += bf_hi(v[i].y);
          o[4] += bf_lo(v[i].z); o[5] += bf_hi(v[i].z); o[6] += bf_lo(v[i].w); o[7] += bf_hi(v[i].w);
        }
      };
      WG_WAIT(0);
      reg_fence(own);
#pragma unroll 1
      for (int e = 0; e < 3; e++) { uint4 v[5]; fetch(e, v); add(e, v); }
      if (lane == 0) mbar_arrive(bar_w);
#pragma unroll
      for (int i = 0; i < 20; i++) xr[i] = hadd2(xr[i], hmul2(pack_bf16(own[2 * i], own[2 * i + 1]), fr[i]));
#pragma unroll
      for (int k = 0; k < 5; k++) stsm4(xa + 32 * k, xr + 4 * k);
      asm volatile("fence.proxy.async.shared::cta;" ::: "memory");
      __syncwarp();
      if (elect()) {
        tma2d_store(&m.out, xs, nh * 320 + kq * 80, qt * 128 + cw * 16);
        asm volatile("cp.async.bulk.commit_group;\ncp.async.bulk.wait_group.read 0;" ::: "memory");
      }
      __syncwarp();
    }
    cluster_wait();
  } else {
    asm volatile("setmaxnreg.dec.sync.aligned.u32 40;");
    uint32_t tid_; asm volatile("mov.u32 %0, %%tid.x;" : "=r"(tid_));
    const int warp = __shfl_sync(~0u, tid_ >> 5, 0);
    auto is_warp = [&](int k) { uint32_t e; asm volatile("{\n.reg .pred q;\nsetp.eq.u32 q, %1, %2;\nselp.u32 %0, 1, 0, q;\n}" : "=r"(e) : "r"(warp), "r"(k)); return e != 0; };
    if (warp > 0) {
      const unsigned epoch = (unsigned)(__ldcg(&p.s->done) >> 7);
      int budget = WAIT_BUDGET;
      const uint32_t tag = epoch + 1;
      mbar_wait(bar_b, 0, budget); mbar_wait(bar_b + 8, 0, budget);
      float cs0 = 0.f, cs1 = 0.f;
      const int n = rank * 96 + (warp - 1) * 32 + (lane & 15) * 2;
#pragma unroll 1
      for (int kg = ((qt >> 1) & 3) * 2 + (lane >> 4) * 5, e = kg + 5; kg < e; kg++) {
        const uint32_t ad = sb + OFF_B + kg * 3072 + (n >> 6) * 1024 + (n & 63) * 2;
#pragma unroll
        for (int k = 0; k < 8; k++) { const uint32_t v = lds32(ad ^ (k * 0x90)); cs0 += bf_lo(v); cs1 += bf_hi(v); }
      }
      cs0 += __shfl_xor_sync(~0u, cs0, 16); cs1 += __shfl_xor_sync(~0u, cs1, 16);
      if (lane < 16)
        asm volatile("{\n.reg .b64 v;\nmov.b64 v, {%1, %2};\nst.relaxed.gpu.global.b64 [%0], v;\n}\n" ::"l"((uint2*)(p.s->cs + (hg * 4 + (qt >> 2)) * 96 + (n >> 1)) + ((qt >> 1) & 1)),
                     "r"((__float_as_uint(cs0) & ~3u) | (tag & 3)), "r"(__float_as_uint(cs1)) : "memory");
      mbar_wait(bar_a + EA, 0, budget);
      if (lane < 2) { uint32_t a; asm volatile("mapa.shared::cluster.u32 %0, %1, %2;" : "=r"(a) : "r"(bar_d), "r"(lane)); mbar_arrive_cluster(a); }
      cs0 = cs1 = 0.f;
      for (const uint32_t c0 = clock(); clock() - c0 < CSW;) {}
#pragma unroll 1
      for (int e = 0; e < 2; e++) {
        if (e) {
          mbar_wait(bar_a + EA, 1, budget);
#pragma unroll 1
          for (int k = 0; k < 8; k++) {
            const uint32_t v = pack_bf16(cs0, cs1);
            sts32((sb + ((tid_ - 32) >> 5) * 1024 + lane * 4) ^ (k * 0x90), k < 3 ? v : 0);
            cs0 -= bf_lo(v); cs1 -= bf_hi(v);
          }
          if (!is_warp(3)) break;
        }
        const uint4* src = e ? p.s->stat + qt * 128 + lane : p.s->cs + hg * 4 * 96 + (tid_ - 32);
        const int step = e ? 32 : 96;
        uint4 v[4];
        while (true) {
          uint32_t bad = 0;
#pragma unroll
          for (int i = 0; i < 4; i++) v[i] = ld_pkt(src + i * step);
#pragma unroll
          for (int i = 0; i < 4; i++) bad |= (v[i].x ^ tag) | (v[i].z ^ tag);
          if (!__any_sync(~0u, bad & 3) || --budget < 0) break;
        }
#pragma unroll
        for (int i = 0; i < 4; i++) {
          cs0 += __uint_as_float(v[i].x & ~3u) + __uint_as_float(v[i].z & ~3u); cs1 += __uint_as_float(v[i].y) + __uint_as_float(v[i].w);
          if (e) asm volatile("st.shared.v2.u32 [%0], {%1,%2};" ::"r"(s_stat + (i * 32 + lane) * 8), "r"(v[i].w), "r"(v[i].y) : "memory");
        }
      }
      asm volatile("fence.proxy.async.shared::cta;" ::: "memory");
      __syncwarp();
      if (lane < 2) mbar_arrive(bar_s);
      budget = errands(p.s, m, warp, tag, budget);
      if (is_warp(2)) {
        mbar_wait(bar_w, 0, budget);
        if (budget < 0) asm volatile("st.global.u32 [%0], %1;" ::"l"(0ull), "r"(budget) : "memory");
      }
    } else {
      uint32_t fb = bar_b + 16, dst = sb + OFF_B + 2 * TB, ph = 1;
      auto next = [&]() { fb += 8; dst += TB; if (fb == bar_b + 48) { fb = bar_b; dst = sb + OFF_B; ph ^= 1; } };
#pragma unroll 1
      for (int u = 0; u < 4; u++) {
        const int h = hg * 4 + u;
        int s = u ? (u == 2 ? 5 : 0) : (s0 + 2) % 10;
#pragma unroll 1
        for (int i = u ? 0 : 2; i < 10; i++) {
          if (u == 0) {
            const uint32_t a8 = 8 * (i < 5 ? i : i - 5);
            if (D0 && i >= D0) { const int j = i - D0; mbar_wait(bar_a + 8 * (j < 5 ? j : j - 5), j >= 5); }
            mbar_wait(bar_a + EA + a8, i < 5);
            if (elect()) { mbar_expect_tx(bar_a + a8, TA); tma2d(sb + a8 * (TA >> 3), &m.x, 64 * s, qt * 128, bar_a + a8); }
            if (i == 6) mbar_wait(bar_d, 0);
          }
          mbar_wait(fb + EB, ph);
          if (elect()) { mbar_expect_tx(fb, TB); tma4d_mc(dst + rank * (TB / 2), &m.wq, 3 * h, 8 * s + 4 * rank, fb); }
          next();
          if (++s == 10) s = 0;
        }
        const int kv0 = (h * SKC + (SKC - WIN)) / 8 + 4 * rank;
#pragma unroll 1
        for (int i = 0; i < 16; i++) {
          const bool isk = (0x2AAB >> i) & 1;
          mbar_wait(fb + EB, ph);
          if (elect()) { mbar_expect_tx(fb, TB); tma4d_mc(dst + rank * (TB / 2), isk ? &m.k : &m.v, 0, kv0 + 8 * (isk ? (i + 1) >> 1 : (i - 1) >> 1), fb); }
          next();
        }
      }
      const int cF = 10 * nh + 5 - 5 * (kq >> 1), cS = 10 * nh + 5 * (kq >> 1);
      const int kb = 4 * (k_block(lane, hg) + rank);
#pragma unroll 1
      for (int n = 0; n < 38; n++) {
        const int c2 = __shfl_sync(~0u, kb, n >> 1);
        mbar_wait(fb + EB, ph);
        if (elect()) { mbar_expect_tx(fb, TW); tma5d_mc(dst + rank * (TW / 2), &m.wo, c2, n & 1 ? cS : cF, fb); }
        next();
      }
      const int odd = (((0x7ff0 ^ 1 << LQ) ^ (kq & 1 ? 0xffc00 : 0)) >> lane) & 1;
      const int tq = __shfl_sync(~0u, kb, 19 + end_stage(lane)) << 16 | odd << 7 | ((lane < 10 ? cF : cS) + 2 * odd);
#pragma unroll 1
      for (int n = 0; n < 20; n += 2) {
        const int t0 = __shfl_sync(~0u, tq, n), t1 = __shfl_sync(~0u, tq, n + 1);
        mbar_wait(fb + EB, ph);
        if (elect()) {
          mbar_expect_tx(fb, TB);
          tma5d_mc(dst + rank * (TB / 4), (const CUtensorMap*)((const char*)m.w3 + (t0 & 128)), t0 >> 16, t0 & 31, fb);
          tma5d_mc(dst + TB / 2 + rank * (TB / 4), (const CUtensorMap*)((const char*)m.w3 + (t1 & 128)), t1 >> 16, t1 & 31, fb);
        }
        next();
      }
      mbar_wait(fb + EB, ph);
      if (elect()) { mbar_expect_tx(fb, TW); tma2d(dst, &m.xe, nh * 320 + kq * 80, qt * 128, fb); }
    }
    if (!is_warp(2)) {
      const int e = warp - (warp >> 1), ms = 2 * e + ((lane >> 2) & 1);
      const uint4* src = p.s->o + (size_t)(qt * 192 + nh * 24 + 10 + (kq ^ ((0x132 >> (4 * e)) & 3)) * 48) * 512 + (e < 2 ? kq & 1 : 2) * 1280 + (ms & 1) * 640;
      uint32_t todo = 0xff;
      bool ok = lane >= 8;
      mbar_wait(bar_z, 0);
#pragma unroll 1
      while (todo) {
        if (!ok) ok = ld_pkt(src + 4 * 128 + (lane & 3) * 32 + 31).x & 1;
        const uint32_t got = __ballot_sync(~0u, ok) & todo, go = __ballot_sync(~0u, ((got >> (lane & 28)) & 15) == 15);
        if (go) mbar_wait(bar_a + EA + 8 * e, 0);
        if ((go & 0x11) >> lane & 1) {
          mbar_expect_tx(bar_e + 8 * ms, TW / 2); bulk_load(sb + OFF_B + (3 + e) * TB + (ms & 1) * (TW / 2), src, TW / 2, bar_e + 8 * ms);
        }
        todo &= ~go;
      }
    }
    cluster_sync();
  }
}

typedef CUresult (*EncodeFn)(CUtensorMap*, CUtensorMapDataType, cuuint32_t, void*, const cuuint64_t*, const cuuint64_t*,
                             const cuuint32_t*, const cuuint32_t*, CUtensorMapInterleave, CUtensorMapSwizzle,
                             CUtensorMapL2promotion, CUtensorMapFloatOOBfill);

void encode(EncodeFn fn, CUtensorMap* tm, void* base, int rank, const cuuint64_t* dims, const cuuint64_t* strides,
            const cuuint32_t* box, CUtensorMapSwizzle sw) {
  const cuuint32_t es[5] = {1, 1, 1, 1, 1};
  fn(tm, CU_TENSOR_MAP_DATA_TYPE_BFLOAT16, rank, base, dims, strides, box, es, CU_TENSOR_MAP_INTERLEAVE_NONE, sw,
     CU_TENSOR_MAP_L2_PROMOTION_L2_128B, CU_TENSOR_MAP_FLOAT_OOB_FILL_NONE);
}

}

extern "C" void kernel_launch(void* const* d_in, const int* in_sizes, int n_in, void* d_out, int out_size) {
  static EncodeFn fn = nullptr;
  static Scratch* scr = nullptr;
  if (!fn) {
    void* f = nullptr;
    cudaDriverEntryPointQueryResult st;
    cudaGetDriverEntryPoint("cuTensorMapEncodeTiled", &f, cudaEnableDefault, &st);
    fn = (EncodeFn)f;
    cudaGetSymbolAddress((void**)&scr, g_scratch);
    cudaFuncSetAttribute(fused_kernel, cudaFuncAttributeMaxDynamicSharedMemorySize, SMEM_BYTES);
  }
  Maps m;
  { const cuuint64_t d[2] = {DM, SQ}, s[1] = {DM * 2}; const cuuint32_t b[2] = {64, 128};
    encode(fn, &m.x, d_in[0], 2, d, s, b, CU_TENSOR_MAP_SWIZZLE_128B);
    encode(fn, &m.xn, scr->xn, 2, d, s, b, CU_TENSOR_MAP_SWIZZLE_128B); }
  { const cuuint64_t d[4] = {64, 8, QD / 64, DM / 8}, s[3] = {QD * 2, 128, 8 * QD * 2}; const cuuint32_t b[4] = {64, 8, 3, 4};
    encode(fn, &m.wq, d_in[3], 4, d, s, b, CU_TENSOR_MAP_SWIZZLE_128B); }
  { const cuuint64_t d[4] = {64, 8, 3, NH * SKC / 8}, s[3] = {DH * 2, 128, 8 * DH * 2}; const cuuint32_t b[4] = {64, 8, 3, 4};
    encode(fn, &m.k, d_in[1], 4, d, s, b, CU_TENSOR_MAP_SWIZZLE_128B);
    encode(fn, &m.v, d_in[2], 4, d, s, b, CU_TENSOR_MAP_SWIZZLE_128B); }
  {
    const cuuint64_t d[5] = {32, 2, QD / 8, 4, DM / 32}, s[4] = {DM * 2, 8 * DM * 2, 2 * DM * 2, 64}; const cuuint32_t b[5] = {32, 2, 4, 4, 5};
    encode(fn, &m.wo, d_in[4], 5, d, s, b, CU_TENSOR_MAP_SWIZZLE_64B);
    const cuuint32_t b3[5] = {32, 2, 4, 4, 3};
    encode(fn, &m.w3[0], d_in[4], 5, d, s, b3, CU_TENSOR_MAP_SWIZZLE_64B);
    encode(fn, &m.w3[1], (char*)d_in[4] + 32, 5, d, s, b3, CU_TENSOR_MAP_SWIZZLE_64B); }
  { const cuuint64_t d[2] = {DM, SQ}, s[1] = {DM * 2}; const cuuint32_t bg[2] = {80, 24}, bx[2] = {80, 128}, bo[2] = {80, 16};
    encode(fn, &m.xg, d_in[0], 2, d, s, bg, CU_TENSOR_MAP_SWIZZLE_NONE);
    encode(fn, &m.xe, d_in[0], 2, d, s, bx, CU_TENSOR_MAP_SWIZZLE_NONE);
    encode(fn, &m.out, d_out, 2, d, s, bo, CU_TENSOR_MAP_SWIZZLE_NONE); }
  Params p;
  p.x = (const __nv_bfloat16*)d_in[0]; p.wr = (const __nv_bfloat16*)d_in[6]; p.wg = (const __nv_bfloat16*)d_in[7];
  p.wu = (const __nv_bfloat16*)d_in[8]; p.wd = (const __nv_bfloat16*)d_in[9];

  p.k = (const __nv_bfloat16*)d_in[1]; p.v = (const __nv_bfloat16*)d_in[2]; p.s = scr;
  cudaLaunchConfig_t cfg = {};
  cfg.gridDim = dim3(132); cfg.blockDim = dim3(384); cfg.dynamicSmemBytes = SMEM_BYTES; cfg.stream = cudaStreamPerThread;
  cudaLaunchKernelEx(&cfg, fused_kernel, p, m);
}
```

```cpp
#include <cuda_runtime.h>
#include <cuda_bf16.h>
#include <cuda.h>
#include <stdint.h>

namespace {

constexpr int SQ = 2048, DM = 640, NH = 32, DH = 192, SKC = 2048, WIN = 512, FF = 1536;
constexpr int QD = NH * DH;
constexpr uint32_t TA = 16384, TB = 24576, TW = 20480, OFF_B = 5 * TA, OFF_M = OFF_B + 6 * TB, SMEM_BYTES = OFF_M + 3072;
constexpr int WAIT_BUDGET = 1 << 20;

constexpr int FL_XN = 0;
constexpr int FL_O = 512;
constexpr int FL_RD = FL_O + 1024;
constexpr int FL_FFN = FL_RD + 1024;
constexpr int FL_SIDE = FL_FFN + 32;
struct __align__(1024) Scratch {
  unsigned long long done, pad0[15];
  unsigned flag[FL_SIDE + 32];
  uint4 cand[8];
  float ffn[4 * 2 * DM];
  int sel[4];
  __nv_bfloat16 gsel[2 * DM];
  uint4 cs[8 * 4 * DH / 2];
  uint4 stat[SQ];
  __align__(1024) __nv_bfloat16 xn[SQ * DM];
  __align__(1024) uint4 o[SQ * QD / 8];
};
__device__ Scratch g_scratch;

__device__ __forceinline__ uint32_t smem_u32(const void* p) { return (uint32_t)__cvta_generic_to_shared(p); }
__device__ __forceinline__ void mbar_init(uint32_t bar, int cnt) { asm volatile("mbarrier.init.shared::cta.b64 [%0], %1;" ::"r"(bar), "r"(cnt)); }
__device__ __forceinline__ void mbar_expect_tx(uint32_t bar, uint32_t bytes) {
  asm volatile("mbarrier.arrive.expect_tx.shared::cta.b64 _, [%0], %1;" ::"r"(bar), "r"(bytes) : "memory");
}
__device__ __forceinline__ void mbar_arrive(uint32_t bar) { asm volatile("mbarrier.arrive.shared::cta.b64 _, [%0];" ::"r"(bar) : "memory"); }
__device__ __forceinline__ void mbar_arrive_cluster(uint32_t addr) { asm volatile("mbarrier.arrive.shared::cluster.b64 _, [%0];" ::"r"(addr) : "memory"); }
__device__ __forceinline__ bool mbar_try(uint32_t bar, uint32_t parity) {
  uint32_t ok;
  asm volatile("{\n.reg .pred p;\nmbarrier.try_wait.parity.shared::cta.b64 p, [%1], %2;\nselp.u32 %0, 1, 0, p;\n}\n" : "=r"(ok) : "r"(bar), "r"(parity) : "memory");
  return ok;
}
__device__ __forceinline__ void mbar_wait(uint32_t bar, uint32_t parity, int& budget) {
#pragma unroll 1
  while (!mbar_try(bar, parity)) { if (--budget < 0) break; }
}
__device__ __forceinline__ void mbar_wait(uint32_t bar, uint32_t parity) {
#pragma unroll 1
  while (!mbar_try(bar, parity)) {}
}
__device__ __forceinline__ unsigned ld_acquire(const unsigned* p) { unsigned v; asm volatile("ld.acquire.gpu.global.u32 %0, [%1];" : "=r"(v) : "l"(p) : "memory"); return v; }
__device__ __forceinline__ void wait_flag(const unsigned* p, unsigned target) {
#pragma unroll 1
  while (__any_sync(~0u, (int)(ld_acquire(p) - target) < 0)) {}
}
__device__ __forceinline__ void red_release(unsigned* p) { asm volatile("red.release.gpu.global.add.u32 [%0], 1;" ::"l"(p) : "memory"); }
__device__ __forceinline__ void fence_proxy_async() { asm volatile("fence.proxy.async.global;" ::: "memory"); }
__device__ __forceinline__ bool elect() {
  uint32_t p;
  asm volatile("{\n.reg .pred P;\nelect.sync _|P, 0xffffffff;\nselp.u32 %0, 1, 0, P;\n}\n" : "=r"(p));
  return p;
}
__device__ __forceinline__ void cluster_arrive() { asm volatile("barrier.cluster.arrive.relaxed.aligned;" ::: "memory"); }
__device__ __forceinline__ void cluster_wait() { asm volatile("barrier.cluster.wait.aligned;" ::: "memory"); }
__device__ __forceinline__ void cluster_sync() { cluster_arrive(); cluster_wait(); }
__device__ __forceinline__ void tma2d(uint32_t dst, const CUtensorMap* tm, int c0, int c1, uint32_t bar) {
  asm volatile("cp.async.bulk.tensor.2d.shared::cluster.global.mbarrier::complete_tx::bytes [%0], [%1, {%3, %4}], [%2];"
               ::"r"(dst), "l"(tm), "r"(bar), "r"(c0), "r"(c1) : "memory");
}
constexpr uint64_t POL_FIRST = 0x12F0000000000000ull;
__device__ __forceinline__ void tma4d_mc(uint32_t dst, const CUtensorMap* tm, int c2, int c3, uint32_t bar) {
  asm volatile("cp.async.bulk.tensor.4d.shared::cluster.global.mbarrier::complete_tx::bytes.multicast::cluster.L2::cache_hint [%0], [%1, {%3, %3, %4, %5}], [%2], %6, %7;"
               ::"r"(dst), "l"(tm), "r"(bar), "r"(0), "r"(c2), "r"(c3), "h"((uint16_t)3), "l"(POL_FIRST) : "memory");
}
__device__ __forceinline__ void tma5d_mc(uint32_t dst, const CUtensorMap* tm, int c2, int c4, uint32_t bar) {
  asm volatile("cp.async.bulk.tensor.5d.shared::cluster.global.mbarrier::complete_tx::bytes.multicast::cluster.L2::cache_hint [%0], [%1, {%3, %3, %4, %3, %5}], [%2], %6, %7;"
               ::"r"(dst), "l"(tm), "r"(bar), "r"(0), "r"(c2), "r"(c4), "h"((uint16_t)3), "l"(POL_FIRST) : "memory");
}
__device__ __forceinline__ void bulk_load(uint32_t dst, const void* src, uint32_t bytes, uint32_t bar) {
  asm volatile("cp.async.bulk.shared::cluster.global.mbarrier::complete_tx::bytes.L2::cache_hint [%0], [%1], %2, [%3], %4;" ::"r"(dst), "l"(src), "r"(bytes), "r"(bar), "l"(POL_FIRST) : "memory");
}
__device__ __forceinline__ void tma2d_store(const CUtensorMap* tm, uint32_t src, int c0, int c1) {
  asm volatile("cp.async.bulk.tensor.2d.global.shared::cta.bulk_group [%0, {%2, %3}], [%1];" ::"l"(tm), "r"(src), "r"(c0), "r"(c1) : "memory");
}
__device__ __forceinline__ uint32_t lds32(uint32_t a) { uint32_t v; asm volatile("ld.shared.u32 %0, [%1];" : "=r"(v) : "r"(a) : "memory"); return v; }
__device__ __forceinline__ uint2 lds64(uint32_t a) { uint2 v; asm volatile("ld.shared.v2.u32 {%0,%1}, [%2];" : "=r"(v.x), "=r"(v.y) : "r"(a) : "memory"); return v; }
__device__ __forceinline__ uint4 lds128(uint32_t a) { uint4 v; asm volatile("ld.shared.v4.u32 {%0,%1,%2,%3}, [%4];" : "=r"(v.x), "=r"(v.y), "=r"(v.z), "=r"(v.w) : "r"(a) : "memory"); return v; }
__device__ __forceinline__ void ldsm4(uint32_t a, uint32_t* v) {
  asm volatile("ldmatrix.sync.aligned.m8n8.x4.shared.b16 {%0,%1,%2,%3}, [%4];" : "=r"(v[0]), "=r"(v[1]), "=r"(v[2]), "=r"(v[3]) : "r"(a) : "memory");
}
__device__ __forceinline__ void stsm4(uint32_t a, const uint32_t* v) {
  asm volatile("stmatrix.sync.aligned.m8n8.x4.shared.b16 [%0], {%1,%2,%3,%4};" ::"r"(a), "r"(v[0]), "r"(v[1]), "r"(v[2]), "r"(v[3]) : "memory");
}
__device__ __forceinline__ void sts32(uint32_t a, uint32_t v) { asm volatile("st.shared.u32 [%0], %1;" ::"r"(a), "r"(v) : "memory"); }
__device__ __forceinline__ void st_pkt(uint4* p, uint32_t a, uint32_t b, uint32_t c, uint32_t d) {
  asm volatile("st.relaxed.gpu.global.v4.b32 [%0], {%1, %2, %3, %4};" ::"l"(p), "r"(a), "r"(b), "r"(c), "r"(d) : "memory");
}
__device__ __forceinline__ uint4 ld_pkt(const uint4* p) {
  uint4 v;
  asm volatile("{\n.reg .b128 v;\nld.relaxed.gpu.global.b128 v, [%4];\nmov.b128 {%0, %1, %2, %3}, v;\n}\n" : "=r"(v.x), "=r"(v.y), "=r"(v.z), "=r"(v.w) : "l"(p) : "memory");
  return v;
}
__device__ __forceinline__ uint4 ldg_nc(const void* p) {
  uint4 v;
  asm volatile("ld.global.nc.v4.u32 {%0,%1,%2,%3}, [%4];" : "=r"(v.x), "=r"(v.y), "=r"(v.z), "=r"(v.w) : "l"(p));
  return v;
}
#define WG_FENCE() asm volatile("wgmma.fence.sync.aligned;" ::: "memory")
#define WG_COMMIT() asm volatile("wgmma.commit_group.sync.aligned;" ::: "memory")
#define WG_WAIT(n) asm volatile("wgmma.wait_group.sync.aligned " #n ";" ::: "memory")
template <int N> __device__ __forceinline__ void reg_fence(float (&d)[N]) {
#pragma unroll
  for (int i = 0; i < N; i++) asm volatile("" : "+f"(d[i])::"memory");
}
template <int N> __device__ __forceinline__ void reg_fence(uint32_t (&d)[N]) {
#pragma unroll
  for (int i = 0; i < N; i++) asm volatile("" : "+r"(d[i])::"memory");
}
__device__ __forceinline__ constexpr uint64_t desc_hi(uint32_t lbo, uint32_t sbo, uint64_t sw) {
  return ((uint64_t)(lbo >> 4) << 16) | ((uint64_t)(sbo >> 4) << 32) | (sw << 62);
}
__device__ __forceinline__ uint64_t mkdesc(uint32_t addr, uint64_t hi) { return hi | (uint64_t)((addr & 0x3FFFF) >> 4); }
__device__ __forceinline__ uint32_t pack_bf16(float lo, float hi) { uint32_t r; asm("cvt.rn.bf16x2.f32 %0, %1, %2;" : "=r"(r) : "f"(hi), "f"(lo)); return r; }
__device__ __forceinline__ float bf_lo(uint32_t v) { return __uint_as_float(v << 16); }
__device__ __forceinline__ float bf_hi(uint32_t v) { return __uint_as_float(v & 0xffff0000u); }
__device__ __forceinline__ uint32_t hadd2(uint32_t a, uint32_t b) { uint32_t r; asm("add.rn.bf16x2 %0, %1, %2;" : "=r"(r) : "r"(a), "r"(b)); return r; }
__device__ __forceinline__ uint32_t hsub2(uint32_t a, uint32_t b) { uint32_t r; asm("sub.rn.bf16x2 %0, %1, %2;" : "=r"(r) : "r"(a), "r"(b)); return r; }
__device__ __forceinline__ uint32_t hmul2(uint32_t a, uint32_t b) { uint32_t r; asm("mul.rn.bf16x2 %0, %1, %2;" : "=r"(r) : "r"(a), "r"(b)); return r; }
__device__ __forceinline__ float rbf(float x) { return __bfloat162float(__float2bfloat16_rn(x)); }
__device__ __forceinline__ float ex2(float x) { float y; asm("ex2.approx.ftz.f32 %0, %1;" : "=f"(y) : "f"(x)); return y; }
__device__ __forceinline__ float rcp(float x) { float y; asm("rcp.approx.ftz.f32 %0, %1;" : "=f"(y) : "f"(x)); return y; }
__device__ __forceinline__ float sigmoid_f(float x) { return rcp(1.f + ex2(x * -1.4426950408889634f)); }
__device__ __forceinline__ float silu_f(float x) { return x * sigmoid_f(x); }

__device__ __forceinline__ void wg_ss192t(float (&d)[96], uint64_t da, uint64_t db, int sd) {
  asm volatile("{\n.reg .pred p;\nsetp.ne.b32 p, %98, 0;\n"
    "wgmma.mma_async.sync.aligned.m64n192k16.f32.bf16.bf16 {%0,%1,%2,%3,%4,%5,%6,%7,%8,%9,%10,%11,%12,%13,%14,%15,%16,%17,%18,%19,%20,%21,%22,%23,%24,%25,%26,%27,%28,%29,%30,%31,%32,%33,%34,%35,%36,%37,%38,%39,%40,%41,%42,%43,%44,%45,%46,%47,%48,%49,%50,%51,%52,%53,%54,%55,%56,%57,%58,%59,%60,%61,%62,%63,%64,%65,%66,%67,%68,%69,%70,%71,%72,%73,%74,%75,%76,%77,%78,%79,%80,%81,%82,%83,%84,%85,%86,%87,%88,%89,%90,%91,%92,%93,%94,%95}, %96, %97, p, 1, 1, 0, 1;\n}\n"
    : "+f"(d[0]),"+f"(d[1]),"+f"(d[2]),"+f"(d[3]),"+f"(d[4]),"+f"(d[5]),"+f"(d[6]),"+f"(d[7]),"+f"(d[8]),"+f"(d[9]),"+f"(d[10]),"+f"(d[11]),"+f"(d[12]),"+f"(d[13]),"+f"(d[14]),"+f"(d[15]),"+f"(d[16]),"+f"(d[17]),"+f"(d[18]),"+f"(d[19]),"+f"(d[20]),"+f"(d[21]),"+f"(d[22]),"+f"(d[23]),"+f"(d[24]),"+f"(d[25]),"+f"(d[26]),"+f"(d[27]),"+f"(d[28]),"+f"(d[29]),"+f"(d[30]),"+f"(d[31]),"+f"(d[32]),"+f"(d[33]),"+f"(d[34]),"+f"(d[35]),"+f"(d[36]),"+f"(d[37]),"+f"(d[38]),"+f"(d[39]),"+f"(d[40]),"+f"(d[41]),"+f"(d[42]),"+f"(d[43]),"+f"(d[44]),"+f"(d[45]),"+f"(d[46]),"+f"(d[47]),"+f"(d[48]),"+f"(d[49]),"+f"(d[50]),"+f"(d[51]),"+f"(d[52]),"+f"(d[53]),"+f"(d[54]),"+f"(d[55]),"+f"(d[56]),"+f"(d[57]),"+f"(d[58]),"+f"(d[59]),"+f"(d[60]),"+f"(d[61]),"+f"(d[62]),"+f"(d[63]),"+f"(d[64]),"+f"(d[65]),"+f"(d[66]),"+f"(d[67]),"+f"(d[68]),"+f"(d[69]),"+f"(d[70]),"+f"(d[71]),"+f"(d[72]),"+f"(d[73]),"+f"(d[74]),"+f"(d[75]),"+f"(d[76]),"+f"(d[77]),"+f"(d[78]),"+f"(d[79]),"+f"(d[80]),"+f"(d[81]),"+f"(d[82]),"+f"(d[83]),"+f"(d[84]),"+f"(d[85]),"+f"(d[86]),"+f"(d[87]),"+f"(d[88]),"+f"(d[89]),"+f"(d[90]),"+f"(d[91]),"+f"(d[92]),"+f"(d[93]),"+f"(d[94]),"+f"(d[95])
    : "l"(da), "l"(db), "r"(sd));
}
__device__ __forceinline__ void wg_rs64(float (&d)[32], uint32_t a0, uint32_t a1, uint32_t a2, uint32_t a3, uint64_t db, int sd) {
  asm volatile("{\n.reg .pred p;\nsetp.ne.b32 p, %37, 0;\n"
    "wgmma.mma_async.sync.aligned.m64n64k16.f32.bf16.bf16 {%0,%1,%2,%3,%4,%5,%6,%7,%8,%9,%10,%11,%12,%13,%14,%15,%16,%17,%18,%19,%20,%21,%22,%23,%24,%25,%26,%27,%28,%29,%30,%31}, {%32,%33,%34,%35}, %36, p, 1, 1, 0;\n}\n"
    : "+f"(d[0]),"+f"(d[1]),"+f"(d[2]),"+f"(d[3]),"+f"(d[4]),"+f"(d[5]),"+f"(d[6]),"+f"(d[7]),"+f"(d[8]),"+f"(d[9]),"+f"(d[10]),"+f"(d[11]),"+f"(d[12]),"+f"(d[13]),"+f"(d[14]),"+f"(d[15]),"+f"(d[16]),"+f"(d[17]),"+f"(d[18]),"+f"(d[19]),"+f"(d[20]),"+f"(d[21]),"+f"(d[22]),"+f"(d[23]),"+f"(d[24]),"+f"(d[25]),"+f"(d[26]),"+f"(d[27]),"+f"(d[28]),"+f"(d[29]),"+f"(d[30]),"+f"(d[31])
    : "r"(a0), "r"(a1), "r"(a2), "r"(a3), "l"(db), "r"(sd));
}
__device__ __forceinline__ void wg_rs192t(float (&d)[96], uint32_t a0, uint32_t a1, uint32_t a2, uint32_t a3, uint64_t db, int sd) {
  asm volatile("{\n.reg .pred p;\nsetp.ne.b32 p, %101, 0;\n"
    "wgmma.mma_async.sync.aligned.m64n192k16.f32.bf16.bf16 {%0,%1,%2,%3,%4,%5,%6,%7,%8,%9,%10,%11,%12,%13,%14,%15,%16,%17,%18,%19,%20,%21,%22,%23,%24,%25,%26,%27,%28,%29,%30,%31,%32,%33,%34,%35,%36,%37,%38,%39,%40,%41,%42,%43,%44,%45,%46,%47,%48,%49,%50,%51,%52,%53,%54,%55,%56,%57,%58,%59,%60,%61,%62,%63,%64,%65,%66,%67,%68,%69,%70,%71,%72,%73,%74,%75,%76,%77,%78,%79,%80,%81,%82,%83,%84,%85,%86,%87,%88,%89,%90,%91,%92,%93,%94,%95}, {%96,%97,%98,%99}, %100, p, 1, 1, 1;\n}\n"
    : "+f"(d[0]),"+f"(d[1]),"+f"(d[2]),"+f"(d[3]),"+f"(d[4]),"+f"(d[5]),"+f"(d[6]),"+f"(d[7]),"+f"(d[8]),"+f"(d[9]),"+f"(d[10]),"+f"(d[11]),"+f"(d[12]),"+f"(d[13]),"+f"(d[14]),"+f"(d[15]),"+f"(d[16]),"+f"(d[17]),"+f"(d[18]),"+f"(d[19]),"+f"(d[20]),"+f"(d[21]),"+f"(d[22]),"+f"(d[23]),"+f"(d[24]),"+f"(d[25]),"+f"(d[26]),"+f"(d[27]),"+f"(d[28]),"+f"(d[29]),"+f"(d[30]),"+f"(d[31]),"+f"(d[32]),"+f"(d[33]),"+f"(d[34]),"+f"(d[35]),"+f"(d[36]),"+f"(d[37]),"+f"(d[38]),"+f"(d[39]),"+f"(d[40]),"+f"(d[41]),"+f"(d[42]),"+f"(d[43]),"+f"(d[44]),"+f"(d[45]),"+f"(d[46]),"+f"(d[47]),"+f"(d[48]),"+f"(d[49]),"+f"(d[50]),"+f"(d[51]),"+f"(d[52]),"+f"(d[53]),"+f"(d[54]),"+f"(d[55]),"+f"(d[56]),"+f"(d[57]),"+f"(d[58]),"+f"(d[59]),"+f"(d[60]),"+f"(d[61]),"+f"(d[62]),"+f"(d[63]),"+f"(d[64]),"+f"(d[65]),"+f"(d[66]),"+f"(d[67]),"+f"(d[68]),"+f"(d[69]),"+f"(d[70]),"+f"(d[71]),"+f"(d[72]),"+f"(d[73]),"+f"(d[74]),"+f"(d[75]),"+f"(d[76]),"+f"(d[77]),"+f"(d[78]),"+f"(d[79]),"+f"(d[80]),"+f"(d[81]),"+f"(d[82]),"+f"(d[83]),"+f"(d[84]),"+f"(d[85]),"+f"(d[86]),"+f"(d[87]),"+f"(d[88]),"+f"(d[89]),"+f"(d[90]),"+f"(d[91]),"+f"(d[92]),"+f"(d[93]),"+f"(d[94]),"+f"(d[95])
    : "r"(a0), "r"(a1), "r"(a2), "r"(a3), "l"(db), "r"(sd));
}
__device__ __forceinline__ void wg_ss160t(float (&d)[80], uint64_t da, uint64_t db, int sd) {
  asm volatile("{\n.reg .pred p;\nsetp.ne.b32 p, %82, 0;\n"
    "wgmma.mma_async.sync.aligned.m64n160k16.f32.bf16.bf16 {%0,%1,%2,%3,%4,%5,%6,%7,%8,%9,%10,%11,%12,%13,%14,%15,%16,%17,%18,%19,%20,%21,%22,%23,%24,%25,%26,%27,%28,%29,%30,%31,%32,%33,%34,%35,%36,%37,%38,%39,%40,%41,%42,%43,%44,%45,%46,%47,%48,%49,%50,%51,%52,%53,%54,%55,%56,%57,%58,%59,%60,%61,%62,%63,%64,%65,%66,%67,%68,%69,%70,%71,%72,%73,%74,%75,%76,%77,%78,%79}, %80, %81, p, 1, 1, 0, 1;\n}\n"
    : "+f"(d[0]),"+f"(d[1]),"+f"(d[2]),"+f"(d[3]),"+f"(d[4]),"+f"(d[5]),"+f"(d[6]),"+f"(d[7]),"+f"(d[8]),"+f"(d[9]),"+f"(d[10]),"+f"(d[11]),"+f"(d[12]),"+f"(d[13]),"+f"(d[14]),"+f"(d[15]),"+f"(d[16]),"+f"(d[17]),"+f"(d[18]),"+f"(d[19]),"+f"(d[20]),"+f"(d[21]),"+f"(d[22]),"+f"(d[23]),"+f"(d[24]),"+f"(d[25]),"+f"(d[26]),"+f"(d[27]),"+f"(d[28]),"+f"(d[29]),"+f"(d[30]),"+f"(d[31]),"+f"(d[32]),"+f"(d[33]),"+f"(d[34]),"+f"(d[35]),"+f"(d[36]),"+f"(d[37]),"+f"(d[38]),"+f"(d[39]),"+f"(d[40]),"+f"(d[41]),"+f"(d[42]),"+f"(d[43]),"+f"(d[44]),"+f"(d[45]),"+f"(d[46]),"+f"(d[47]),"+f"(d[48]),"+f"(d[49]),"+f"(d[50]),"+f"(d[51]),"+f"(d[52]),"+f"(d[53]),"+f"(d[54]),"+f"(d[55]),"+f"(d[56]),"+f"(d[57]),"+f"(d[58]),"+f"(d[59]),"+f"(d[60]),"+f"(d[61]),"+f"(d[62]),"+f"(d[63]),"+f"(d[64]),"+f"(d[65]),"+f"(d[66]),"+f"(d[67]),"+f"(d[68]),"+f"(d[69]),"+f"(d[70]),"+f"(d[71]),"+f"(d[72]),"+f"(d[73]),"+f"(d[74]),"+f"(d[75]),"+f"(d[76]),"+f"(d[77]),"+f"(d[78]),"+f"(d[79])
    : "l"(da), "l"(db), "r"(sd));
}
__device__ __forceinline__ void wg_ss80t(float (&d)[40], uint64_t da, uint64_t db, int sd) {
  asm volatile("{\n.reg .pred p;\nsetp.ne.b32 p, %42, 0;\n"
    "wgmma.mma_async.sync.aligned.m64n80k16.f32.bf16.bf16 {%0,%1,%2,%3,%4,%5,%6,%7,%8,%9,%10,%11,%12,%13,%14,%15,%16,%17,%18,%19,%20,%21,%22,%23,%24,%25,%26,%27,%28,%29,%30,%31,%32,%33,%34,%35,%36,%37,%38,%39}, %40, %41, p, 1, 1, 0, 1;\n}\n"
    : "+f"(d[0]),"+f"(d[1]),"+f"(d[2]),"+f"(d[3]),"+f"(d[4]),"+f"(d[5]),"+f"(d[6]),"+f"(d[7]),"+f"(d[8]),"+f"(d[9]),"+f"(d[10]),"+f"(d[11]),"+f"(d[12]),"+f"(d[13]),"+f"(d[14]),"+f"(d[15]),"+f"(d[16]),"+f"(d[17]),"+f"(d[18]),"+f"(d[19]),"+f"(d[20]),"+f"(d[21]),"+f"(d[22]),"+f"(d[23]),"+f"(d[24]),"+f"(d[25]),"+f"(d[26]),"+f"(d[27]),"+f"(d[28]),"+f"(d[29]),"+f"(d[30]),"+f"(d[31]),"+f"(d[32]),"+f"(d[33]),"+f"(d[34]),"+f"(d[35]),"+f"(d[36]),"+f"(d[37]),"+f"(d[38]),"+f"(d[39])
    : "l"(da), "l"(db), "r"(sd));
}

struct Maps { CUtensorMap x, xn, wq, k, v, wo, w3[2], xg, xe, out; };
struct Params {
  const __nv_bfloat16 *x, *wr, *wg, *wu, *wd, *k, *v;
  Scratch* s;
};

__device__ __forceinline__ void side_cta(const Params& p, int sc, unsigned epoch, float* sm) {
  const int tid = threadIdx.x, lane = tid & 31, warp = tid >> 5;
  int budget = WAIT_BUDGET;
  float* s_x = sm;
  float* s_red = sm + 1280;
  float* s_h = s_red + 6144;
  uint4* s_c = (uint4*)(s_h + 768);
  uint2* s_st = (uint2*)(s_c + 16);
  constexpr int DEPTH = 7, STEP = 4 * 6144;
  const uint32_t ring = smem_u32(s_st + 512) + tid * 16;
  const int cg = tid % 96, ks = tid / 96, cd = tid % 80, kd = tid / 80;
  const __nv_bfloat16* wp = (cg < 48 ? p.wg : p.wu) + (size_t)(ks * 160) * FF + sc * 384 + (cg % 48) * 8;
  int kf = 0, pitch = FF;
  uint32_t slot = ring;
  auto refill = [&]() {
    if (kf == 40) { wp = p.wd + (size_t)(sc * 384 + kd * 96) * DM + cd * 8; pitch = DM; }
    if (kf < (tid < 320 ? 64 : 40)) {
#pragma unroll
      for (int j = 0; j < 4; j++) asm volatile("cp.async.cg.shared.global.L2::cache_hint [%0], [%1], 16, %2;" ::"r"(slot + j * 6144), "l"(wp + j * pitch), "l"(POL_FIRST) : "memory");
    }
    asm volatile("cp.async.commit_group;" ::: "memory");
    wp += 4 * pitch; kf++;
    slot += STEP; if (slot == ring + DEPTH * STEP) slot = ring;
  };
  auto gemv = [&](int n, const float* x0, const float* x1, float* out) {
    float a[2][8] = {};
#pragma unroll 1
    for (int k = 0; k < n; k += 4) {
      refill();
      asm volatile("cp.async.wait_group %0;" ::"n"(DEPTH - 1) : "memory");
      const float4 f0 = *(const float4*)(x0 + k), f1 = *(const float4*)(x1 + k);
      const float y0[4] = {f0.x, f0.y, f0.z, f0.w}, y1[4] = {f1.x, f1.y, f1.z, f1.w};
#pragma unroll
      for (int j = 0; j < 4; j++) {
        const uint4 v = lds128(slot + j * 6144);
        const uint32_t u[4] = {v.x, v.y, v.z, v.w};
#pragma unroll
        for (int i = 0; i < 4; i++) {
          a[0][2 * i] += y0[j] * bf_lo(u[i]); a[0][2 * i + 1] += y0[j] * bf_hi(u[i]);
          a[1][2 * i] += y1[j] * bf_lo(u[i]); a[1][2 * i + 1] += y1[j] * bf_hi(u[i]);
        }
      }
    }
#pragma unroll
    for (int i = 0; i < 16; i++) out[(i >> 3) * 768 + (i & 7)] = a[i >> 3][i & 7];
  };
  auto load_row = [&](const __nv_bfloat16* r, uint32_t (&v)[10]) {
    const uint4 a = __ldg((const uint4*)r + lane), b = __ldg((const uint4*)r + 32 + lane);
    const uint2 c = __ldg((const uint2*)r + 128 + lane);
    v[0] = a.x; v[1] = a.y; v[2] = a.z; v[3] = a.w; v[4] = b.x; v[5] = b.y; v[6] = b.z; v[7] = b.w; v[8] = c.x; v[9] = c.y;
  };
  uint32_t wr[10], xb[3][10];
  load_row(p.wr, wr);
#pragma unroll 1
  for (int i = tid; i < 512; i += 384) {
    uint4 v;
    do v = ld_pkt(p.s->stat + sc * 512 + i); while (v.x != epoch + 1 && --budget >= 0);
    s_st[i] = make_uint2(v.w, v.y);
  }
  __syncthreads();
#pragma unroll
  for (int b = 0; b < 3; b++) load_row(p.x + (size_t)(sc * 512 + warp + 12 * b) * DM, xb[b]);
#pragma unroll 1
  for (int k = 0; k < DEPTH - 1; k++) refill();
  float v0 = -INFINITY, v1 = -INFINITY; int i0 = 0xfff, i1 = 0xfff;
  auto better = [](float a, int ia, float b, int ib) { return a > b || (a == b && ia < ib); };
  auto push = [&](float v, int i) {
    if (better(v, i, v0, i0)) { v1 = v0; i1 = i0; v0 = v; i0 = i; }
    else if (better(v, i, v1, i1)) { v1 = v; i1 = i; }
  };
  auto push2 = [&](uint4 c) { push(__uint_as_float(c.x), c.y & 0xfff); push(__uint_as_float(c.z), c.w & 0xfff); };
#pragma unroll 1
  for (int l3 = warp; l3 < 512; l3 += 36) {
#pragma unroll
    for (int b = 0; b < 3; b++) {
      const int lr = l3 + 12 * b;
      if (lr >= 512) break;
      const uint2 st = s_st[lr];
      uint32_t v[10];
#pragma unroll
      for (int i = 0; i < 10; i++) v[i] = hsub2(xb[b][i], st.x);
      if (lr + 36 < 512) load_row(p.x + (size_t)(sc * 512 + lr + 36) * DM, xb[b]);
      float r0 = 0.f, r1 = 0.f;
#pragma unroll
      for (int i = 0; i < 10; i++) {
        const uint32_t xn = pack_bf16(bf_lo(v[i]) * __uint_as_float(st.y), bf_hi(v[i]) * __uint_as_float(st.y));
        r0 = fmaf(bf_lo(xn), bf_lo(wr[i]), r0); r1 = fmaf(bf_hi(xn), bf_hi(wr[i]), r1);
      }
      r0 += r1;
#pragma unroll
      for (int o = 16; o > 0; o >>= 1) r0 += __shfl_xor_sync(~0u, r0, o);
      push(rbf(r0), sc * 512 + lr);
    }
  }
  if (lane == 0) s_c[warp] = make_uint4(__float_as_uint(v0), i0, __float_as_uint(v1), i1);
  __syncthreads();
#pragma unroll 1
  for (int w = 1; w < 12; w++) push2(s_c[(warp + w) % 12]);
  const uint32_t tag = (epoch + 1) << 12;
  if (tid == 0) st_pkt(p.s->cand + sc, __float_as_uint(v0), i0 | tag, __float_as_uint(v1), i1);
  {
    uint4 c;
    do c = ld_pkt(p.s->cand + (lane & 3)); while (((c.y ^ tag) >> 12) && --budget >= 0);
#pragma unroll 1
    for (int w = 1; w < 4; w++) { const int o = (sc + w) & 3; push2(make_uint4(__shfl_sync(~0u, c.x, o), __shfl_sync(~0u, c.y, o), __shfl_sync(~0u, c.z, o), __shfl_sync(~0u, c.w, o))); }
  }
  if (i0 >= SQ) i0 = 0;
  if (i1 >= SQ) i1 = (i0 == 0) ? 1 : 0;
  if (tid < 320) {
    const int row = tid < 160 ? i0 : i1;
    const uint2 u = __ldg((const uint2*)(p.x + (size_t)row * DM) + tid % 160);
    uint4 st;
    do st = ld_pkt(p.s->stat + row); while (st.x != epoch + 1 && --budget >= 0);
    const uint32_t d0 = hsub2(u.x, st.w), d1 = hsub2(u.y, st.w);
    const float inv = __uint_as_float(st.y);
    ((float4*)s_x)[tid] = make_float4(rbf(bf_lo(d0) * inv), rbf(bf_hi(d0) * inv), rbf(bf_lo(d1) * inv), rbf(bf_hi(d1) * inv));
  }
  __syncthreads();
  gemv(160, s_x + ks * 160, s_x + DM + ks * 160, s_red + ks * 1536 + cg * 8);
  __syncthreads();
#pragma unroll
  for (int t = 0; t < 2; t++) {
    float g = 0.f, u = 0.f;
#pragma unroll
    for (int k = 0; k < 4; k++) { g += s_red[(k * 2 + t) * 768 + tid]; u += s_red[(k * 2 + t) * 768 + 384 + tid]; }
    s_h[t * 384 + tid] = rbf(rbf(silu_f(rbf(g))) * rbf(u));
  }
  __syncthreads();
  if (tid < 320) gemv(96, s_h + kd * 96, s_h + 384 + kd * 96, s_red + kd * 1536 + cd * 8);
  __syncthreads();
  const int o4 = tid + (tid < 160 ? 0 : 32);
  if (tid < 320) {
    const float4 *r = (const float4*)s_red + o4, a = r[0], b = r[384], c = r[768], d = r[1152];
    ((float4*)p.s->ffn)[sc * 320 + tid] = make_float4(a.x + b.x + c.x + d.x, a.y + b.y + c.y + d.y, a.z + b.z + c.z + d.z, a.w + b.w + c.w + d.w);
  }
  __syncthreads();
  if (tid == 0) { __threadfence(); s_c[0].x = (atomicAdd(&p.s->flag[FL_SIDE], 1u) & 3u) == 3u; __threadfence(); }
  __syncthreads();
  if (s_c[0].x) {
    if (tid < 320) {
      const float4 *r = (const float4*)p.s->ffn + tid, a = __ldcg(r), b = __ldcg(r + 320), c = __ldcg(r + 640), d = __ldcg(r + 960), x = ((float4*)s_x)[tid];
      const float rs = rbf(sigmoid_f(tid < 160 ? v0 : v1));
      auto gate = [&](float xn, float y) { return silu_f(rbf(xn + rbf(rbf(y) * rs))); };
      if (tid == 0) { p.s->sel[0] = i0; p.s->sel[1] = i1; }
      ((uint2*)p.s->gsel)[tid] =
          make_uint2(pack_bf16(gate(x.x, a.x + b.x + c.x + d.x), gate(x.y, a.y + b.y + c.y + d.y)), pack_bf16(gate(x.z, a.z + b.z + c.z + d.z), gate(x.w, a.w + b.w + c.w + d.w)));
    }
    __syncthreads();
    if (tid == 0) red_release(&p.s->flag[FL_FFN]);
  }
}

constexpr float SM_C = 0.07216878364870322f * 1.4426950408889634f;

#define LD 0
#define LS 3
__device__ __forceinline__ void ln_piece(const Params& p, uint32_t (&r)[48], int k, int row, int l16) {
  auto f = [&](int i) { return __uint_as_float(r[i]); };
  if (k == LD) {
#pragma unroll
    for (int i = 0; i < 5; i++) {
      const uint4 v = ldg_nc((const uint4*)(p.x + (size_t)row * DM) + i * 16 + l16);
      r[4 * i] = v.x; r[4 * i + 1] = v.y; r[4 * i + 2] = v.z; r[4 * i + 3] = v.w;
    }
    asm volatile("ld.relaxed.gpu.global.v2.u32 {%0,%1}, [%2];" : "=r"(r[20]), "=r"(r[21]) : "l"(&p.s->done));
  } else if (k == LS || k == LS + 1) {
    if (k == LS) { r[22] = __shfl_sync(~0u, r[0], 0, 16) << 16; r[23] = r[24] = 0; }
    float s0 = f(23), s1 = 0.f, q0 = f(24), q1 = 0.f;
#pragma unroll
    for (int i = 10 * (k - LS); i < 10 * (k - LS) + 10; i++) {
      const float a = bf_lo(r[i]) - f(22), b = bf_hi(r[i]) - f(22);
      s0 += a; s1 += b; q0 = fmaf(a, a, q0); q1 = fmaf(b, b, q1);
    }
    r[23] = __float_as_uint(s0 + s1); r[24] = __float_as_uint(q0 + q1);
  } else if (k == LS + 2) {
    float s0 = f(23), q0 = f(24);
#pragma unroll
    for (int o = 8; o > 0; o >>= 1) { s0 += __shfl_xor_sync(~0u, s0, o); q0 += __shfl_xor_sync(~0u, q0, o); }
    s0 *= 1.f / DM;
    const float mean = f(22) + s0, var = rbf(fmaxf(fmaf(q0, 1.f / DM, -s0 * s0), 0.f));
    float sd; asm("sqrt.approx.ftz.f32 %0, %1;" : "=f"(sd) : "f"(rbf(var + 1e-5f)));
    const float inv = rcp(rbf(sd));
    r[22] = pack_bf16(mean, mean); r[23] = __float_as_uint(inv * SM_C);
    const uint32_t tag = __funnelshift_r(r[20], r[21], 7) + 1;
    if (l16 == 0) st_pkt(&p.s->stat[row], tag, __float_as_uint(inv), tag, r[22]);
  } else if (k > LS + 2 && k <= LS + 5) {
#pragma unroll
    for (int j = 2 * (k - LS - 3); j < 2 * (k - LS - 3) + 2 && j < 5; j++) {
#pragma unroll
      for (int i = 4 * j; i < 4 * j + 4; i++) { const uint32_t d = hsub2(r[i], r[22]); r[i] = pack_bf16(bf_lo(d) * f(23), bf_hi(d) * f(23)); }
      *((uint4*)(p.s->xn + (size_t)row * DM) + j * 16 + l16) = make_uint4(r[4 * j], r[4 * j + 1], r[4 * j + 2], r[4 * j + 3]);
    }
  }
}

constexpr float SM_HI = 0x1p64f, SM_LO = 0x1p-64f;
__device__ __forceinline__ void exp_block(float (&s)[32], float& l0, float& l1, int from = 0, int to = 32) {
#pragma unroll
  for (int i = from; i < to; i++) { s[i] = ex2(s[i]); if (i & 2) l1 += s[i]; else l0 += s[i]; }
}
__device__ __forceinline__ float quad_sum(float v) { v += __shfl_xor_sync(~0u, v, 1); return v + __shfl_xor_sync(~0u, v, 2); }
__device__ __forceinline__ float quad_max(float v) { v = fmaxf(v, __shfl_xor_sync(~0u, v, 1)); return fmaxf(v, __shfl_xor_sync(~0u, v, 2)); }
__device__ __noinline__ void safe_head(const uint32_t* kp, const uint32_t* vp, uint4* io) {
  uint32_t fq[48];
#pragma unroll
  for (int i = 0; i < 12; i++) { const uint4 v = io[(i >> 1) * 512 + (i & 1) * 32]; fq[4 * i] = v.x; fq[4 * i + 1] = v.y; fq[4 * i + 2] = v.z; fq[4 * i + 3] = v.w; }
  float m0 = -INFINITY, m1 = -INFINITY;
#pragma unroll 1
  for (int pass = 0; pass < 3; pass++) {
    float o[48] = {}, l0 = 0.f, l1 = 0.f;
#pragma unroll 1
    for (int n = 0; n < 64; n++) {
      const uint32_t *kr = kp + n * (8 * DH / 2), *vr = vp + n * (8 * DH / 2) + (pass - 1) * 48;
      float d[4] = {};
#pragma unroll
      for (int t = 0; t < 12; t++)
        asm volatile("mma.sync.aligned.m16n8k16.row.col.f32.bf16.bf16.f32 {%0,%1,%2,%3}, {%4,%5,%6,%7}, {%8,%9}, {%0,%1,%2,%3};"
                     : "+f"(d[0]), "+f"(d[1]), "+f"(d[2]), "+f"(d[3])
                     : "r"(fq[4 * t]), "r"(fq[4 * t + 1]), "r"(fq[4 * t + 2]), "r"(fq[4 * t + 3]), "r"(__ldg(kr + 8 * t)), "r"(__ldg(kr + 8 * t + 4)));
      if (pass == 0) { m0 = fmaxf(m0, fmaxf(d[0], d[1])); m1 = fmaxf(m1, fmaxf(d[2], d[3])); continue; }
      d[0] = ex2(d[0] - m0); d[1] = ex2(d[1] - m0); d[2] = ex2(d[2] - m1); d[3] = ex2(d[3] - m1);
      l0 += d[0] + d[1]; l1 += d[2] + d[3];
      const uint32_t p0 = pack_bf16(d[0], d[1]), p1 = pack_bf16(d[2], d[3]);
#pragma unroll
      for (int c = 0; c < 12; c++)
        asm volatile("{\n.reg .b32 t;\nmovmatrix.sync.aligned.m8n8.trans.b16 t, %6;\n"
                     "mma.sync.aligned.m16n8k8.row.col.f32.bf16.bf16.f32 {%0,%1,%2,%3}, {%4,%5}, {t}, {%0,%1,%2,%3};\n}\n"
                     : "+f"(o[4 * c]), "+f"(o[4 * c + 1]), "+f"(o[4 * c + 2]), "+f"(o[4 * c + 3]) : "r"(p0), "r"(p1), "r"(__ldg(vr + 4 * c)));
    }
    if (pass == 0) { m0 = quad_max(m0); m1 = quad_max(m1); continue; }
    l0 = rcp(quad_sum(l0)); l1 = rcp(quad_sum(l1));
#pragma unroll
    for (int i = 0; i < 6; i++) {
      const float* v = o + 16 * (i >> 1) + 2 * (i & 1);
      const float r = i & 1 ? l1 : l0;
      io[(3 * (pass - 1) + (i >> 1)) * 512 + (i & 1) * 32] =
          make_uint4(pack_bf16(v[0] * r, v[1] * r), pack_bf16(v[4] * r, v[5] * r), pack_bf16(v[8] * r, v[9] * r), pack_bf16(v[12] * r, v[13] * r));
    }
  }
}

#define CVG 48
#define NE 8
#define PS1 8
#define CSW 1400
#define D0 2
#define ROT 2
#define CSJ (ROT == 2 ? 3 : ROT == 4 ? 1 : 0)
#define LQ 6
__device__ __forceinline__ constexpr int end_stage(int n) { return n < 4 ? n : n < LQ ? n - 4 : n == LQ ? 4 : n % 5; }
#define Q2N 1
#define SWN 12
#define SCH 0
__device__ __forceinline__ constexpr int sent(int n) {
  constexpr int t[4][15] = {{0, 2, 4, 5, 5, 6, 7, 8,  9, 10, 11, 12, 13, 14, 15},
                            {0, 2, 4, 5, 5, 6, 7, 8,  9, 10, 12, 13, 14, 15, 15},
                            {0, 2, 4, 5, 5, 7, 8, 9, 10, 10, 12, 14, 15, 15, 15},
                            {0, 2, 4, 5, 5, 7, 8, 9, 10, 10, 13, 15, 15, 15, 15}};
  return n < LQ + 2 ? 0 : LQ == 6 && n == 8 ? 3 : t[SCH][n - 6];
}
template <int N> struct IntC { static constexpr int value = N; };
template <int N, int I = 0, class F> __device__ __forceinline__ void static_for(F&& f) { if constexpr (I < N) { f(IntC<I>{}); static_for<N, I + 1>(f); } }

extern __shared__ __align__(1024) uint8_t smem_raw[];
constexpr uint32_t EA = 160, EB = 184;
#define SMEM_LAYOUT                                                                                                          \
  [[maybe_unused]] const uint32_t sb = smem_u32(smem_raw), bar_a = sb + OFF_M, bar_b = bar_a + 40, bar_x = bar_a + 88,      \
      bar_u = bar_a + 96, bar_e = bar_a + 104, bar_o = bar_a + 200, bar_w = bar_a + 208, bar_z = bar_a + 288,                \
      bar_s = bar_a + 296, bar_d = bar_a + 304, s_stat = bar_a + 512, s_sel = s_stat + 1024;

__device__ __forceinline__ int k_block(int t, int hg) {
  const int i = (t * 11) >> 5;
  return ((i < 6 ? (hg & 6) + (i & 1) : hg ^ (i & 1)) * 4 + (i >> 1)) * 6 + (t == 3 * i ? 4 : 2 * (t - 3 * i) - 2);
}

__device__ __noinline__ int errands(Scratch* s, const Maps& m, int warp, uint32_t tag, int budget) {
  SMEM_LAYOUT
  const int lane = threadIdx.x & 31, cl = blockIdx.x >> 1, qt = blockIdx.x & 15, hg = cl >> 3, kq = hg >> 1, nh = hg & 1;
  if (warp == 1) {
#pragma unroll 1
    for (int u = 0; u < 5; u++) {
      mbar_wait(bar_o, u & 1);
      if (lane == 0) red_release(&s->flag[u ? FL_O + (qt * 8 + hg) * 8 : FL_XN + qt * 32]);
      __syncwarp();
    }
  } else if (warp == 2) {
    mbar_wait(bar_x, 0, budget);
    while ((int)(ld_acquire(&s->flag[FL_FFN]) - tag) < 0 && --budget >= 0) {}
    if (lane < 21) {
      const uint4 v = __ldcg(lane ? (const uint4*)(s->gsel + (lane > 10 ? DM - 80 : 0) + nh * 320 + kq * 80) + lane - 1 : (const uint4*)s->sel);
      asm volatile("st.shared.v4.u32 [%0], {%1,%2,%3,%4};" ::"r"(s_sel + 16 * lane), "r"(v.x), "r"(v.y), "r"(v.z), "r"(v.w) : "memory");
    }
    __syncwarp();
    if (lane == 0) { mbar_arrive(bar_u); asm volatile("red.relaxed.gpu.global.add.u64 [%0], 1;" ::"l"(&s->done) : "memory"); }
    while ((int)(ld_acquire(&s->flag[FL_RD + (qt * 8 + (hg ^ 1)) * 8]) - tag) < 0 && --budget >= 0) {}
    if (lane < 3) mbar_arrive(bar_z);
  } else {
    wait_flag(&s->flag[FL_XN + qt * 32], tag * 8);
    fence_proxy_async();
    mbar_wait(bar_a + EA + 32, 1);
    uint32_t a8 = 0, pha = 1;
    const int kb = (qt * 192 + k_block(lane, hg)) * 512;
#pragma unroll 1
    for (int n = 0; n < 54; n++) {
      const int t = n - 30, ko = __shfl_sync(~0u, kb, t);
      if (t == 0 || t == 18) {
        wait_flag(&s->flag[FL_O + (qt * 8 + (t ? 2 * kq + (lane & 1) : lane & 7)) * 8], tag * 4 - (t ? 0 : 1));
        fence_proxy_async();
      }
      mbar_wait(bar_a + EA + a8, pha);
      const uint32_t fb = bar_a + a8, dst = sb + a8 * (TA >> 3);
      if (elect()) {
        if (t >= 0) {
          mbar_expect_tx(fb, TA);
          bulk_load(dst, s->o + ko, TA, fb);
          if (t == 8) {
            mbar_expect_tx(bar_x, 6 * 3840);
#pragma unroll 1
            for (int e = 0; e < 6; e++) tma2d(sb + OFF_B + TW + e * TB, &m.xg, nh * 320 + kq * 80, qt * 128 + e * 24, bar_x);
            asm volatile("prefetch.tensormap [%0];\nprefetch.tensormap [%1];\nprefetch.tensormap [%2];\nprefetch.tensormap [%3];"
                         ::"l"(m.w3), "l"(m.w3 + 1), "l"(&m.xe), "l"(&m.out) : "memory");
          }
          if (t == 22) asm volatile("red.relaxed.gpu.global.add.u32 [%0], 1;" ::"l"(&s->flag[FL_RD + (qt * 8 + hg) * 8]) : "memory");
        } else if (n >= 10 && pha) mbar_arrive(fb);
        else { mbar_expect_tx(fb, TA); tma2d(dst, &m.xn, 8 * a8 + (pha || (n >= 15 && n < 20) ? 0 : 320), qt * 128, fb); }
      }
      a8 += 8; if (a8 == 40) { a8 = 0; pha ^= 1; }
    }
    if (lane < 3) mbar_arrive(bar_z);
  }
  return budget;
}

__global__ void __launch_bounds__(384, 1) __cluster_dims__(2, 1, 1)
fused_kernel(const Params p, const __grid_constant__ Maps m) {
  SMEM_LAYOUT
  const int wi = __shfl_sync(~0u, threadIdx.x >> 5, 0), wg = wi >> 2;
  const int lane = threadIdx.x & 31;
  const int cl = blockIdx.x >> 1;
  const int rank = blockIdx.x & 1;

  if (cl >= 64) {
    const unsigned epoch = (unsigned)(__ldcg(&p.s->done) >> 7);
    side_cta(p, blockIdx.x - 128, epoch, (float*)smem_raw);
    return;
  }
  const int qt = blockIdx.x & 15, hg = cl >> 3;
  const int kq = hg >> 1, nh = hg & 1;

  const int s0 = (5 * ((qt >> 1) & ~(8 / ROT - 1))) >> 2, kg0 = 10 * (qt >> 1) - 8 * s0;
  if (elect()) {
    const int c = (int)(0x5ff7700000ull >> (4 * wi) & 15) + 1;
    for (int i = 0; i < 4; i++) mbar_init(bar_a + 32 * wi + 8 * i, c);
    asm volatile("fence.mbarrier_init.release.cluster;" ::: "memory");
  }
  __syncwarp();
  cluster_arrive();
  if (wi < 2 && elect()) {
    if (wi) { asm volatile("prefetch.tensormap [%0];" ::"l"(&m.wq) : "memory"); mbar_expect_tx(bar_b, TB); mbar_expect_tx(bar_b + 8, TB); }
    else for (int i = 0; i < 2; i++) { mbar_expect_tx(bar_a + 8 * i, TA); tma2d(sb + i * TA, &m.x, 64 * (s0 + i), qt * 128, bar_a + 8 * i); }
  }
  __syncwarp();
  cluster_wait();
  if (wi == 1 && elect())
    for (int i = 0; i < 2; i++) tma4d_mc(sb + OFF_B + i * TB + rank * (TB / 2), &m.wq, 12 * hg, 8 * (s0 + i) + 4 * rank, bar_b + 8 * i);
  if (wg > 0) {
    const int w = wg - 1;
    const int cw = wi - 4;
    asm volatile("setmaxnreg.inc.sync.aligned.u32 232;");
    uint32_t fr[48];
    reg_fence(fr);
    auto ln_row = [&]() { int v = qt * 128 + hg * 16 + cw * 2 + (lane >> 4); asm volatile("" : "+r"(v)); return v; };
    uint32_t rel_addr;
    asm volatile("mapa.shared::cluster.u32 %0, %1, %2;" : "=r"(rel_addr) : "r"(bar_b + EB), "r"(lane & 1));
    auto rel_a = [&](uint32_t o8) { if (lane == 0) mbar_arrive(bar_a + EA + o8); };
    auto rel_b = [&](uint32_t o8) { if (lane < 2) mbar_arrive_cluster(rel_addr + o8); };
    uint32_t b8 = 0, phb = 0;
    auto next_pair = [&]() { b8 += 16; if (b8 == 48) { b8 = 0; phb ^= 1; } };
    const int g = lane >> 2, q = lane & 3;
    constexpr uint64_t HI_A = desc_hi(16, 1024, 1);
    constexpr uint64_t HI_W = desc_hi(1024, 3072, 1);
    constexpr uint64_t HI_O = desc_hi(2048, 512, 2);
    if (w == 1) asm volatile("bar.arrive 1, 256;" ::: "memory");

    uint32_t zero; asm volatile("mov.u32 %0, %%tid.y;" : "=r"(zero));
    float acc[96];
    uint4* optr = p.s->o + (size_t)(qt * 192 + hg * 24) * 512 + (cw * 16 + g) * 4 + (q ^ ((g >> 1) & 3));
    uint32_t rl[4];
    auto store_o = [&](int pp) {
#pragma unroll
      for (int i = (12 * pp + 8) / 9; i < (12 * (pp + 1) + 8) / 9; i++) {
#pragma unroll
        for (int k = 4 * i; k < 4 * i + 4; k++)
          asm volatile("{\n.reg .b32 t;\nmul.rn.bf16x2 t, %0, %2;\nfma.rn.bf16x2 %0, %0, %1, t;\n}\n" : "+r"(fr[k]) : "r"(rl[i & 1]), "r"(rl[2 + (i & 1)]));
        fr[4 * i] &= ~1u;
        optr[(i >> 1) * 512 + (i & 1) * 32] = make_uint4(fr[4 * i], fr[4 * i + 1], fr[4 * i + 2], fr[4 * i + 3]);
      }
      if (pp == 8) optr += 6 * 512;
    };
    auto fresh = [&]() { uint32_t v = sb; asm volatile("" : "+r"(v)); return v; };
    reg_fence(rl);

#pragma unroll 1
    for (int u = 0; u < 4; u++) {
      const uint32_t sq = fresh();
      const uint64_t dA = mkdesc(sq + w * 8192, HI_A), dB0 = mkdesc(sq + OFF_B, HI_W);
      uint32_t pb8 = 0;
#pragma unroll
      for (int s = 0; s < 10; s++) {
        const uint32_t o8 = b8 + 8 * (s & 1);
        const uint64_t dW = dB0 + o8 * (TB >> 7);
        mbar_wait(bar_a + 8 * (s % 5), s / 5);
        mbar_wait(bar_b + o8, phb);
        if (s == 9) asm volatile("bar.sync %0, 256;" ::"r"(1 + w) : "memory");
        WG_FENCE();
#pragma unroll
        for (int kk = 0; kk < 4; kk++) wg_ss192t(acc, dA + ((s % 5) * (TA >> 4) + kk * 2), dW + kk * 384, kk != 0 || s != 0);
        WG_COMMIT();
        if (s == 9) asm volatile("bar.arrive %0, 256;" ::"r"(2 - w) : "memory");
        if (s > 0) { WG_WAIT(1); rel_a(8 * ((s - 1) % 5)); rel_b(pb8); }
        if (s < 9) { if (u > 0) store_o(s); else ln_piece(p, fr, s, ln_row(), lane & 15); }
        if (s == 8) { __syncwarp(); if (lane == 0) mbar_arrive(bar_o); }
        pb8 = o8;
        if (s & 1) next_pair();
      }
      if (u == 0) {
        mbar_wait(bar_s, 0);
        const uint2 s0 = lds64(s_stat + (cw * 16 + g) * 8), s1 = lds64(s_stat + 64 + (cw * 16 + g) * 8);
        const uint32_t msk = q == 0 ? 0xffffffffu : q == 1 ? 0xffffu : 0u;
        const float c0 = SM_C * __uint_as_float(s0.y), c1 = SM_C * __uint_as_float(s1.y);
        uint32_t am[4] = {(s0.x ^ 0x80008000u) & msk, (s1.x ^ 0x80008000u) & msk, 0, 0};
        reg_fence(am);
        WG_FENCE();
        wg_rs192t(acc, am[0], am[1], am[2], am[3], mkdesc(sb, desc_hi(1024, 0, 1)), 1);
        WG_COMMIT();
        WG_WAIT(0);
        reg_fence(acc);
#pragma unroll
        for (int i = 0; i < 24; i++) { acc[4 * i] *= c0; acc[4 * i + 1] *= c0; acc[4 * i + 2] *= c1; acc[4 * i + 3] *= c1; }
      } else { WG_WAIT(0); reg_fence(acc); }
      rel_b(pb8);
      rel_a(32);
      auto pack_q = [&](int from, int to) {
#pragma unroll
        for (int i = from; i < to; i++) { fr[i] = pack_bf16(acc[2 * i], acc[2 * i + 1]); asm volatile("" : "+r"(fr[i])::"memory"); }
      };
      pack_q(0, CVG);
      float sc[32], l0 = 0.f, l1 = 0.f;
      uint32_t pf[16], k8;
      auto pack_p = [&](const float (&s_)[32], int from = 0, int to = 16) {
#pragma unroll
        for (int i = from; i < to; i++) pf[i] = pack_bf16(s_[2 * i], s_[2 * i + 1]);
      };
      auto scores = [&](int j, int pass = 11) {
        k8 = b8 + 8;
        mbar_wait(bar_b + k8, phb);
        next_pair();
        mbar_wait(bar_b + b8, phb);
        const uint64_t dk = mkdesc(sb + OFF_B, HI_W) + k8 * (TB >> 7);
        asm volatile("bar.sync %0, 256;" ::"r"(1 + w) : "memory");
        WG_FENCE();
#pragma unroll
        for (int t = 0; t < 12; t++) {
          wg_rs64(sc, fr[4 * t], fr[4 * t + 1], fr[4 * t + 2], fr[4 * t + 3], dk + (t >> 2) * 64 + (t & 3) * 2, t != 0);
          if (t == 11) WG_COMMIT();
          if (t == pass) asm volatile("bar.arrive %0, 256;" ::"r"(2 - w) : "memory");
        }
      };
      auto pv = [&](int add) {
        const uint64_t dv = mkdesc(sb + OFF_B, HI_W) + b8 * (TB >> 7);
#pragma unroll
        for (int kk = 0; kk < 4; kk++) wg_rs192t(acc, pf[4 * kk], pf[4 * kk + 1], pf[4 * kk + 2], pf[4 * kk + 3], dv + kk * 384, kk != 0 || add);
        WG_COMMIT();
      };
      auto finish = [&]() {
        WG_WAIT(1);
        reg_fence(sc);
        exp_block(sc, l0, l1);
        rel_b(k8 + (__float_as_uint(l0) & __float_as_uint(l1) & zero));
        WG_WAIT(0);
        reg_fence(acc); reg_fence(pf);
        rel_b(b8);
        pack_p(sc);
      };
      {
        mbar_wait(bar_b + b8, phb);
        const uint64_t dk = mkdesc(sb + OFF_B, HI_W) + b8 * (TB >> 7);
        asm volatile("bar.sync %0, 256;" ::"r"(1 + w) : "memory");
#pragma unroll
        for (int t = 0; t < 12; t++) {
          if (t && (4 * t) % CVG == 0) pack_q(4 * t, 4 * t + CVG);
          if ((4 * t) % CVG == 0) WG_FENCE();
          wg_rs64(sc, fr[4 * t], fr[4 * t + 1], fr[4 * t + 2], fr[4 * t + 3], dk + (t >> 2) * 64 + (t & 3) * 2, t != 0);
          if (t == 7) asm volatile("bar.arrive %0, 256;" ::"r"(2 - w) : "memory");
        }
        WG_COMMIT();
        WG_WAIT(0);
        reg_fence(sc);
        float s0[32];
#pragma unroll
        for (int i = 0; i < 32; i++) s0[i] = i < NE ? sc[i] : __uint_as_float(__float_as_uint(sc[i]) ^ zero);
        exp_block(s0, l0, l1, 0, NE);
        pack_p(s0, 0, NE / 2);
#pragma unroll
        for (int i = NE; i < 32; i++) asm volatile("" : "+f"(s0[i])::"memory");
#pragma unroll
        for (int i = 0; i < NE / 2; i++) asm volatile("" : "+r"(pf[i])::"memory");
        rel_b(b8);
        scores(1, PS1);
        const uint32_t z = lds32(s_stat) & zero;
#pragma unroll
        for (int i = NE; i < 32; i++) {
          asm("{\n.reg .pred p;\nsetp.eq.u32 p, %1, 0;\n@p ex2.approx.ftz.f32 %0, %0;\n}\n" : "+f"(s0[i]) : "r"(z));
          if (i & 2) l1 += s0[i]; else l0 += s0[i];
        }
        pack_p(s0, NE / 2, 16);
        reg_fence(pf);
        WG_FENCE();
        pv(0);
        finish();
      }
#pragma unroll 1
      for (int j = NE < 32 ? 2 : 1; j < 8; j++) { scores(j); pv(j > 1); finish(); }
      const uint32_t v8 = b8 + 8;
      mbar_wait(bar_b + v8, phb);
      next_pair();
      {
        const uint64_t dv = mkdesc(sb + OFF_B, HI_W) + v8 * (TB >> 7);
        asm volatile("bar.sync %0, 256;" ::"r"(1 + w) : "memory");
        WG_FENCE();
#pragma unroll
        for (int kk = 0; kk < 4; kk++) {
          wg_rs192t(acc, pf[4 * kk], pf[4 * kk + 1], pf[4 * kk + 2], pf[4 * kk + 3], dv + kk * 384, 1);
          if (kk == 1 && (u < 3 || w == 0)) asm volatile("bar.arrive %0, 256;" ::"r"(2 - w) : "memory");
        }
        WG_COMMIT();
      }
      l0 = quad_sum(l0); l1 = quad_sum(l1);
      const bool unsafe = __any_sync(~0u, !(l0 >= SM_LO && l1 >= SM_LO && l0 + l1 <= SM_HI));
      l0 = rcp(l0); l1 = rcp(l1);
      rl[0] = pack_bf16(l0, l0); rl[1] = pack_bf16(l1, l1);
      l0 -= bf_lo(rl[0]); l1 -= bf_lo(rl[1]);
      rl[2] = pack_bf16(l0, l0); rl[3] = pack_bf16(l1, l1);
      WG_WAIT(0);
      reg_fence(acc);
      rel_b(v8);
      if (__builtin_expect(unsafe, 0)) {
        int o = hg * 4 + u; asm volatile("" : "+r"(o));
        o = (o * SKC + (SKC - WIN) + g) * (DH / 2) + q;
#pragma unroll
        for (int i = 0; i < 12; i++) optr[(i >> 1) * 512 + (i & 1) * 32] = make_uint4(fr[4 * i], fr[4 * i + 1], fr[4 * i + 2], fr[4 * i + 3]);
        safe_head((const uint32_t*)p.k + o, (const uint32_t*)p.v + o, optr);
#pragma unroll
        for (int i = 0; i < 12; i++) { const uint4 v = optr[(i >> 1) * 512 + (i & 1) * 32]; fr[4 * i] = v.x; fr[4 * i + 1] = v.y; fr[4 * i + 2] = v.z; fr[4 * i + 3] = v.w; }
        rl[0] = rl[1] = 0x3f803f80u; rl[2] = rl[3] = 0;
      } else {
#pragma unroll
        for (int i = 0; i < 24; i++) {
          fr[8 * (i >> 2) + (i & 3)] = pack_bf16(acc[4 * i], acc[4 * i + 1]);
          fr[8 * (i >> 2) + 4 + (i & 3)] = pack_bf16(acc[4 * i + 2], acc[4 * i + 3]);
        }
      }
    }

    float aF[80], aS[80];
    uint32_t pha = 0, a8 = 0, pa8 = 0, pb8 = 0;
#pragma unroll 1
    for (int s = 0; s < 19; s++) {
      const uint64_t d0 = mkdesc(sb, HI_O), dO = d0 + (a8 * (TA >> 7) + w * 256), dB = d0 + ((OFF_B >> 4) + b8 * (TB >> 7));
      mbar_wait(bar_a + a8, pha);
      mbar_wait(bar_b + b8, phb);
      WG_FENCE();
#pragma unroll
      for (int kk = 0; kk < 4; kk++) wg_ss160t(aF, dO + ((kk >> 1) * 512 + (kk & 1) * 2), dB + ((kk >> 1) * 640 + (kk & 1) * 64), kk != 0 || s != 0);
      WG_COMMIT();
      mbar_wait(bar_b + b8 + 8, phb);
      WG_WAIT(1);
      if (s > 0) { rel_a(pa8); rel_b(pb8 + 8); }
      WG_FENCE();
#pragma unroll
      for (int kk = 0; kk < 4; kk++) wg_ss160t(aS, dO + ((kk >> 1) * 512 + (kk & 1) * 2), dB + ((TB >> 4) + (kk >> 1) * 640 + (kk & 1) * 64), kk != 0 || s != 0);
      WG_COMMIT();
      if (s < 9) {
#pragma unroll
        for (int pp = 0; pp < 9; pp++) if (s == pp) store_o(pp);
        if (s == 8) { __syncwarp(); if (lane == 0) mbar_arrive(bar_o); }
      } else if (s < 15) {
        const int b = 2 * cw + ((lane >> 3) & 1);
        uint32_t ga = sb + OFF_B + TW + ((b * 11) >> 5) * (TB - 3840) + b * 1280 + (lane & 7) * 160 + (lane >> 4) * 16;
        if (s < 14) {
          mbar_wait(bar_x, 0);
          ga += 32 * (s - 9);
          ldsm4(ga, fr);
#pragma unroll
          for (int i = 0; i < 4; i++) {
            const uint2 st = lds64(s_stat + (cw * 16 + g + 8 * (i & 1)) * 8);
            const uint32_t d = hsub2(fr[i], st.x), xn = pack_bf16(bf_lo(d) * __uint_as_float(st.y), bf_hi(d) * __uint_as_float(st.y));
            fr[i] = pack_bf16(silu_f(bf_lo(xn)), silu_f(bf_hi(xn)));
          }
          stsm4(ga, fr);
        } else {
          mbar_wait(bar_u, 0);
          const uint2 sel = lds64(s_sel);
          const uint32_t row = qt * 128 + cw * 16 + (lane & 15);
          if (row == sel.x || row == sel.y) ga = s_sel + 16 + (row == sel.y ? 160 : 0) + (lane >> 4) * 16;
#pragma unroll
          for (int k = 0; k < 5; k++) ldsm4(ga + 32 * k, fr + 4 * k);
        }
      }
      WG_WAIT(1);
      rel_b(b8);
      pa8 = a8; a8 += 8; if (a8 == 40) { a8 = 0; pha ^= 1; }
      pb8 = b8; next_pair();
    }
    const int t128 = threadIdx.x & 127;
    uint4* const xbase = p.s->o + (size_t)(qt * 192 + nh * 24 + 10) * 512 + w * 640 + t128;
    uint4* const dst = xbase + kq * (48 * 512);
    float q1[40], q2[40], oth[40], own[40];
    auto take = [&](float (&x)[40], const float* a) {
#pragma unroll
      for (int k = 0; k < 40; k++) x[k] = __uint_as_float(__float_as_uint(a[k]) ^ zero);
      reg_fence(x);
    };
    reg_fence(aF);
    take(q1, aF);
    auto fa = [&](int i) { return mbar_try(bar_a + 8 * ((4 + i) % 5), i == 0); };
    auto fb = [&](int e) { return mbar_try(bar_b + 8 * (e % 6), (e / 6) & 1); };
    auto send = [&](int m) {
      const float* v = (m < 5 ? q1 : m < 10 ? q2 : oth) + 8 * (m % 5);
      st_pkt(dst + (m / 5) * 1280 + (m % 5) * 128, pack_bf16(v[0], v[1]) | 1, pack_bf16(v[2], v[3]), pack_bf16(v[4], v[5]), pack_bf16(v[6], v[7]));
    };
    static_for<20>([&](auto n_) {
      constexpr int n = n_.value, i = end_stage(n), e = 142 + n / 2, qi = n == 4 ? 1 : n == LQ ? 0 : n / 5;
      float (&acc_)[40] = qi == 0 ? q1 : qi == 1 ? q2 : qi == 2 ? oth : own;
      if (n == 0) while (!(fa(0) & fa(1) & fb(142) & fb(143))) {}
      if (n == 2) while (!(fa(2) & fa(3) & fb(144))) {}
      if (n == LQ) while (!(fa(4) & fb(145) & fb(146) & mbar_try(bar_z, 0))) {}
      if (n == 10) while (!(fb(147) & fb(148) & fb(149))) {}
      const uint64_t d0 = mkdesc(fresh(), HI_O);
      WG_FENCE();
#pragma unroll
      for (int kk = 0; kk < 4; kk++)
        wg_ss80t(acc_, d0 + w * 256 + (((4 + i) % 5) * (TA >> 4) + (kk >> 1) * 512 + (kk & 1) * 2),
                 d0 + ((OFF_B >> 4) + (e % 6) * (TB >> 4) + (n & 1) * 768 + (kk >> 1) * 384 + (kk & 1) * 64), 1);
      WG_COMMIT();
      if ((!(n & 1) && n <= 16) || n == 15 || n == LQ + 1) WG_WAIT(1);
      if (n == 0) rel_a(24);
      if (!(n & 1) && n <= 10) rel_b(8 * ((e - 1) % 6));
      if (n == Q2N) take(q2, aF + 40);
      if (n == 10) cluster_arrive();
      if (n == 12 || n == 14 || n == 16) rel_a(4u * n - 48);
      if (n == LQ + 1) reg_fence(q1);
      if (n == 10) reg_fence(q2);
      if (n == 15) reg_fence(oth);
      if (n == 15) while (!(fb(150) & fb(151))) {}
      static_for<sent(n + 1) - sent(n)>([&](auto k_) { send(sent(n) + k_.value); });
      if (n == 8) {
        reg_fence(aS);
#pragma unroll
        for (int k = 0; k < 40; k++) oth[k] = kq & 1 ? aS[k] : aS[40 + k];
        reg_fence(oth);
      }
      if (n == SWN) {
        reg_fence(aS);
#pragma unroll
        for (int k = 0; k < 40; k++) own[k] = kq & 1 ? aS[40 + k] : aS[k];
        reg_fence(own);
      }
    });
    uint32_t xr[20];
    const uint32_t xs = sb + OFF_B + 2 * TB + cw * 2560, xa = xs + (lane & 15) * 160 + (lane >> 4) * 16;
    mbar_wait(bar_b + 16, 1);
#pragma unroll
    for (int k = 0; k < 5; k++) ldsm4(xa + 32 * k, xr + 4 * k);
    {
      auto fetch = [&](int e, uint4 (&v)[5]) {
        mbar_wait(bar_e + 16 * e + 8 * w, 0);
#pragma unroll
        for (int i = 0; i < 5; i++) v[i] = lds128(sb + OFF_B + (3 + e) * TB + (w * 640 + i * 128 + t128) * 16);
      };
      auto add = [&](int e, uint4 (&v)[5]) {
        while (!(v[0].x & v[1].x & v[2].x & v[3].x & v[4].x & 1)) {
#pragma unroll
          for (int i = 0; i < 5; i++) v[i] = ld_pkt(xbase + (kq ^ ((0x132 >> (4 * e)) & 3)) * (48 * 512) + (e < 2 ? kq & 1 : 2) * 1280 + i * 128);
        }
#pragma unroll
        for (int i = 0; i < 5; i++) {
          float* o = own + 8 * i;
          o[0] += bf_lo(v[i].x); o[1] += bf_hi(v[i].x); o[2] += bf_lo(v[i].y); o[3] += bf_hi(v[i].y);
          o[4] += bf_lo(v[i].z); o[5] += bf_hi(v[i].z); o[6] += bf_lo(v[i].w); o[7] += bf_hi(v[i].w);
        }
      };
      WG_WAIT(0);
      reg_fence(own);
#pragma unroll 1
      for (int e = 0; e < 3; e++) { uint4 v[5]; fetch(e, v); add(e, v); }
      if (lane == 0) mbar_arrive(bar_w);
#pragma unroll
      for (int i = 0; i < 20; i++) xr[i] = hadd2(xr[i], hmul2(pack_bf16(own[2 * i], own[2 * i + 1]), fr[i]));
#pragma unroll
      for (int k = 0; k < 5; k++) stsm4(xa + 32 * k, xr + 4 * k);
      asm volatile("fence.proxy.async.shared::cta;" ::: "memory");
      __syncwarp();
      if (elect()) {
        tma2d_store(&m.out, xs, nh * 320 + kq * 80, qt * 128 + cw * 16);
        asm volatile("cp.async.bulk.commit_group;\ncp.async.bulk.wait_group.read 0;" ::: "memory");
      }
      __syncwarp();
    }
    cluster_wait();
  } else {
    asm volatile("setmaxnreg.dec.sync.aligned.u32 40;");
    uint32_t tid_; asm volatile("mov.u32 %0, %%tid.x;" : "=r"(tid_));
    const int warp = __shfl_sync(~0u, tid_ >> 5, 0);
    auto is_warp = [&](int k) { uint32_t e; asm volatile("{\n.reg .pred q;\nsetp.eq.u32 q, %1, %2;\nselp.u32 %0, 1, 0, q;\n}" : "=r"(e) : "r"(warp), "r"(k)); return e != 0; };
    if (warp > 0) {
      const unsigned epoch = (unsigned)(__ldcg(&p.s->done) >> 7);
      int budget = WAIT_BUDGET;
      const uint32_t tag = epoch + 1;
      mbar_wait(bar_a + EA, 0, budget);
      mbar_wait(bar_b + (kg0 & ~7), 0, budget); mbar_wait(bar_b + (kg0 & ~7) + 8, 0, budget);
      float cs0 = 0.f, cs1 = 0.f;
      const int n = rank * 96 + (warp - 1) * 32 + (lane & 15) * 2;
#pragma unroll 1
      for (int kg = kg0 + (lane >> 4) * 5, e = kg + 5; kg < e; kg++) {
        const uint32_t ad = sb + OFF_B + kg * 3072 + (n >> 6) * 1024 + (n & 63) * 2;
#pragma unroll
        for (int k = 0; k < 8; k++) { const uint32_t v = lds32(ad ^ (k * 0x90)); cs0 += bf_lo(v); cs1 += bf_hi(v); }
      }
      cs0 += __shfl_xor_sync(~0u, cs0, 16); cs1 += __shfl_xor_sync(~0u, cs1, 16);
      if (lane < 16)
        asm volatile("{\n.reg .b64 v;\nmov.b64 v, {%1, %2};\nst.relaxed.gpu.global.b64 [%0], v;\n}\n" ::"l"((uint2*)(p.s->cs + (hg * 4 + (qt >> 2)) * 96 + (n >> 1)) + ((qt >> 1) & 1)),
                     "r"((__float_as_uint(cs0) & ~3u) | (tag & 3)), "r"(__float_as_uint(cs1)) : "memory");
      if (lane < 2) { uint32_t a; asm volatile("mapa.shared::cluster.u32 %0, %1, %2;" : "=r"(a) : "r"(bar_d), "r"(lane)); mbar_arrive_cluster(a); }
      cs0 = cs1 = 0.f;
      for (const uint32_t c0 = clock(); clock() - c0 < CSW + (CSJ - (kg0 >> 3)) * 700;) {}
#pragma unroll 1
      for (int e = 0; e < 2; e++) {
        if (e) {
          mbar_wait(bar_a + EA, 1, budget);
#pragma unroll 1
          for (int k = 0; k < 8; k++) {
            const uint32_t v = pack_bf16(cs0, cs1);
            sts32((sb + ((tid_ - 32) >> 5) * 1024 + lane * 4) ^ (k * 0x90), k < 3 ? v : 0);
            cs0 -= bf_lo(v); cs1 -= bf_hi(v);
          }
          if (!is_warp(3)) break;
        }
        const uint4* src = e ? p.s->stat + qt * 128 + lane : p.s->cs + hg * 4 * 96 + (tid_ - 32);
        const int step = e ? 32 : 96;
        uint4 v[4];
        while (true) {
          uint32_t bad = 0;
#pragma unroll
          for (int i = 0; i < 4; i++) v[i] = ld_pkt(src + i * step);
#pragma unroll
          for (int i = 0; i < 4; i++) bad |= (v[i].x ^ tag) | (v[i].z ^ tag);
          if (!__any_sync(~0u, bad & 3) || --budget < 0) break;
        }
#pragma unroll
        for (int i = 0; i < 4; i++) {
          cs0 += __uint_as_float(v[i].x & ~3u) + __uint_as_float(v[i].z & ~3u); cs1 += __uint_as_float(v[i].y) + __uint_as_float(v[i].w);
          if (e) asm volatile("st.shared.v2.u32 [%0], {%1,%2};" ::"r"(s_stat + (i * 32 + lane) * 8), "r"(v[i].w), "r"(v[i].y) : "memory");
        }
      }
      asm volatile("fence.proxy.async.shared::cta;" ::: "memory");
      __syncwarp();
      if (lane < 2) mbar_arrive(bar_s);
      budget = errands(p.s, m, warp, tag, budget);
      if (is_warp(2)) {
        mbar_wait(bar_w, 0, budget);
        if (budget < 0) asm volatile("st.global.u32 [%0], %1;" ::"l"(0ull), "r"(budget) : "memory");
      }
    } else {
      uint32_t fb = bar_b + 16, dst = sb + OFF_B + 2 * TB, ph = 1;
      auto next = [&]() { fb += 8; dst += TB; if (fb == bar_b + 48) { fb = bar_b; dst = sb + OFF_B; ph ^= 1; } };
#pragma unroll 1
      for (int u = 0; u < 4; u++) {
        const int h = hg * 4 + u;
        int s = u ? (u == 2 ? 5 : 0) : (s0 + 2) % 10;
#pragma unroll 1
        for (int i = u ? 0 : 2; i < 10; i++) {
          if (u == 0) {
            const uint32_t a8 = 8 * (i < 5 ? i : i - 5);
            if (D0 && i >= D0) { const int j = i - D0; mbar_wait(bar_a + 8 * (j < 5 ? j : j - 5), j >= 5); }
            mbar_wait(bar_a + EA + a8, i < 5);
            if (elect()) { mbar_expect_tx(bar_a + a8, TA); tma2d(sb + a8 * (TA >> 3), &m.x, 64 * s, qt * 128, bar_a + a8); }
            if (i == 6 + (kg0 >> 3)) mbar_wait(bar_d, 0);
          }
          mbar_wait(fb + EB, ph);
          if (elect()) { mbar_expect_tx(fb, TB); tma4d_mc(dst + rank * (TB / 2), &m.wq, 3 * h, 8 * s + 4 * rank, fb); }
          next();
          if (++s == 10) s = 0;
        }
        const int kv0 = (h * SKC + (SKC - WIN)) / 8 + 4 * rank;
#pragma unroll 1
        for (int i = 0; i < 16; i++) {
          const bool isk = (0x2AAB >> i) & 1;
          mbar_wait(fb + EB, ph);
          if (elect()) { mbar_expect_tx(fb, TB); tma4d_mc(dst + rank * (TB / 2), isk ? &m.k : &m.v, 0, kv0 + 8 * (isk ? (i + 1) >> 1 : (i - 1) >> 1), fb); }
          next();
        }
      }
      const int cF = 10 * nh + 5 - 5 * (kq >> 1), cS = 10 * nh + 5 * (kq >> 1);
      const int kb = 4 * (k_block(lane, hg) + rank);
#pragma unroll 1
      for (int n = 0; n < 38; n++) {
        const int c2 = __shfl_sync(~0u, kb, n >> 1);
        mbar_wait(fb + EB, ph);
        if (elect()) { mbar_expect_tx(fb, TW); tma5d_mc(dst + rank * (TW / 2), &m.wo, c2, n & 1 ? cS : cF, fb); }
        next();
      }
      const int odd = (((0x7ff0 ^ 1 << LQ) ^ (kq & 1 ? 0xffc00 : 0)) >> lane) & 1;
      const int tq = __shfl_sync(~0u, kb, 19 + end_stage(lane)) << 16 | odd << 7 | ((lane < 10 ? cF : cS) + 2 * odd);
#pragma unroll 1
      for (int n = 0; n < 20; n += 2) {
        const int t0 = __shfl_sync(~0u, tq, n), t1 = __shfl_sync(~0u, tq, n + 1);
        mbar_wait(fb + EB, ph);
        if (elect()) {
          mbar_expect_tx(fb, TB);
          tma5d_mc(dst + rank * (TB / 4), (const CUtensorMap*)((const char*)m.w3 + (t0 & 128)), t0 >> 16, t0 & 31, fb);
          tma5d_mc(dst + TB / 2 + rank * (TB / 4), (const CUtensorMap*)((const char*)m.w3 + (t1 & 128)), t1 >> 16, t1 & 31, fb);
        }
        next();
      }
      mbar_wait(fb + EB, ph);
      if (elect()) { mbar_expect_tx(fb, TW); tma2d(dst, &m.xe, nh * 320 + kq * 80, qt * 128, fb); }
    }
    if (!is_warp(2)) {
      const int e = warp - (warp >> 1), ms = 2 * e + ((lane >> 2) & 1);
      const uint4* src = p.s->o + (size_t)(qt * 192 + nh * 24 + 10 + (kq ^ ((0x132 >> (4 * e)) & 3)) * 48) * 512 + (e < 2 ? kq & 1 : 2) * 1280 + (ms & 1) * 640;
      uint32_t todo = 0xff;
      bool ok = lane >= 8;
      mbar_wait(bar_z, 0);
#pragma unroll 1
      while (todo) {
        if (!ok) ok = ld_pkt(src + 4 * 128 + (lane & 3) * 32 + 31).x & 1;
        const uint32_t got = __ballot_sync(~0u, ok) & todo, go = __ballot_sync(~0u, ((got >> (lane & 28)) & 15) == 15);
        if (go) mbar_wait(bar_a + EA + 8 * e, 0);
        if ((go & 0x11) >> lane & 1) {
          mbar_expect_tx(bar_e + 8 * ms, TW / 2); bulk_load(sb + OFF_B + (3 + e) * TB + (ms & 1) * (TW / 2), src, TW / 2, bar_e + 8 * ms);
        }
        todo &= ~go;
      }
    }
    cluster_sync();
  }
}

typedef CUresult (*EncodeFn)(CUtensorMap*, CUtensorMapDataType, cuuint32_t, void*, const cuuint64_t*, const cuuint64_t*,
                             const cuuint32_t*, const cuuint32_t*, CUtensorMapInterleave, CUtensorMapSwizzle,
                             CUtensorMapL2promotion, CUtensorMapFloatOOBfill);

void encode(EncodeFn fn, CUtensorMap* tm, void* base, int rank, const cuuint64_t* dims, const cuuint64_t* strides,
            const cuuint32_t* box, CUtensorMapSwizzle sw) {
  const cuuint32_t es[5] = {1, 1, 1, 1, 1};
  fn(tm, CU_TENSOR_MAP_DATA_TYPE_BFLOAT16, rank, base, dims, strides, box, es, CU_TENSOR_MAP_INTERLEAVE_NONE, sw,
     CU_TENSOR_MAP_L2_PROMOTION_L2_128B, CU_TENSOR_MAP_FLOAT_OOB_FILL_NONE);
}

}

extern "C" void kernel_launch(void* const* d_in, const int* in_sizes, int n_in, void* d_out, int out_size) {
  static EncodeFn fn = nullptr;
  static Scratch* scr = nullptr;
  if (!fn) {
    void* f = nullptr;
    cudaDriverEntryPointQueryResult st;
    cudaGetDriverEntryPoint("cuTensorMapEncodeTiled", &f, cudaEnableDefault, &st);
    fn = (EncodeFn)f;
    cudaGetSymbolAddress((void**)&scr, g_scratch);
    cudaFuncSetAttribute(fused_kernel, cudaFuncAttributeMaxDynamicSharedMemorySize, SMEM_BYTES);
  }
  Maps m;
  { const cuuint64_t d[2] = {DM, SQ}, s[1] = {DM * 2}; const cuuint32_t b[2] = {64, 128};
    encode(fn, &m.x, d_in[0], 2, d, s, b, CU_TENSOR_MAP_SWIZZLE_128B);
    encode(fn, &m.xn, scr->xn, 2, d, s, b, CU_TENSOR_MAP_SWIZZLE_128B); }
  { const cuuint64_t d[4] = {64, 8, QD / 64, DM / 8}, s[3] = {QD * 2, 128, 8 * QD * 2}; const cuuint32_t b[4] = {64, 8, 3, 4};
    encode(fn, &m.wq, d_in[3], 4, d, s, b, CU_TENSOR_MAP_SWIZZLE_128B); }
  { const cuuint64_t d[4] = {64, 8, 3, NH * SKC / 8}, s[3] = {DH * 2, 128, 8 * DH * 2}; const cuuint32_t b[4] = {64, 8, 3, 4};
    encode(fn, &m.k, d_in[1], 4, d, s, b, CU_TENSOR_MAP_SWIZZLE_128B);
    encode(fn, &m.v, d_in[2], 4, d, s, b, CU_TENSOR_MAP_SWIZZLE_128B); }
  {
    const cuuint64_t d[5] = {32, 2, QD / 8, 4, DM / 32}, s[4] = {DM * 2, 8 * DM * 2, 2 * DM * 2, 64}; const cuuint32_t b[5] = {32, 2, 4, 4, 5};
    encode(fn, &m.wo, d_in[4], 5, d, s, b, CU_TENSOR_MAP_SWIZZLE_64B);
    const cuuint32_t b3[5] = {32, 2, 4, 4, 3};
    encode(fn, &m.w3[0], d_in[4], 5, d, s, b3, CU_TENSOR_MAP_SWIZZLE_64B);
    encode(fn, &m.w3[1], (char*)d_in[4] + 32, 5, d, s, b3, CU_TENSOR_MAP_SWIZZLE_64B); }
  { const cuuint64_t d[2] = {DM, SQ}, s[1] = {DM * 2}; const cuuint32_t bg[2] = {80, 24}, bx[2] = {80, 128}, bo[2] = {80, 16};
    encode(fn, &m.xg, d_in[0], 2, d, s, bg, CU_TENSOR_MAP_SWIZZLE_NONE);
    encode(fn, &m.xe, d_in[0], 2, d, s, bx, CU_TENSOR_MAP_SWIZZLE_NONE);
    encode(fn, &m.out, d_out, 2, d, s, bo, CU_TENSOR_MAP_SWIZZLE_NONE); }
  Params p;
  p.x = (const __nv_bfloat16*)d_in[0]; p.wr = (const __nv_bfloat16*)d_in[6]; p.wg = (const __nv_bfloat16*)d_in[7];
  p.wu = (const __nv_bfloat16*)d_in[8]; p.wd = (const __nv_bfloat16*)d_in[9];

  p.k = (const __nv_bfloat16*)d_in[1]; p.v = (const __nv_bfloat16*)d_in[2]; p.s = scr;
  cudaLaunchConfig_t cfg = {};
  cfg.gridDim = dim3(132); cfg.blockDim = dim3(384); cfg.dynamicSmemBytes = SMEM_BYTES; cfg.stream = cudaStreamPerThread;
  cudaLaunchKernelEx(&cfg, fused_kernel, p, m);
}
```

```cpp
#include <cuda_runtime.h>
#include <cuda_bf16.h>
#include <cuda.h>
#include <stdint.h>

namespace {

constexpr int SQ = 2048, DM = 640, NH = 32, DH = 192, SKC = 2048, WIN = 512, FF = 1536;
constexpr int QD = NH * DH;
constexpr uint32_t TA = 16384, TB = 24576, TW = 20480, OFF_B = 5 * TA, OFF_M = OFF_B + 6 * TB, SMEM_BYTES = OFF_M + 3072;
constexpr int WAIT_BUDGET = 1 << 20;

constexpr int FL_XN = 0;
constexpr int FL_O = 512;
constexpr int FL_RD = FL_O + 1024;
constexpr int FL_FFN = FL_RD + 1024;
constexpr int FL_SIDE = FL_FFN + 32;
struct __align__(1024) Scratch {
  unsigned long long done, pad0[15];
  unsigned flag[FL_SIDE + 32];
  uint4 cand[8];
  float ffn[4 * 2 * DM];
  int sel[4];
  __nv_bfloat16 gsel[2 * DM];
  uint4 cs[8 * 4 * DH / 2];
  uint2 stat[SQ];
  __align__(1024) __nv_bfloat16 xn[SQ * DM];
  __align__(1024) uint4 o[SQ * QD / 8];
};
__device__ Scratch g_scratch;

__device__ __forceinline__ uint32_t smem_u32(const void* p) { return (uint32_t)__cvta_generic_to_shared(p); }
__device__ __forceinline__ void mbar_init(uint32_t bar, int cnt) { asm volatile("mbarrier.init.shared::cta.b64 [%0], %1;" ::"r"(bar), "r"(cnt)); }
__device__ __forceinline__ void mbar_expect_tx(uint32_t bar, uint32_t bytes) {
  asm volatile("mbarrier.arrive.expect_tx.shared::cta.b64 _, [%0], %1;" ::"r"(bar), "r"(bytes) : "memory");
}
__device__ __forceinline__ void mbar_arrive(uint32_t bar) { asm volatile("mbarrier.arrive.shared::cta.b64 _, [%0];" ::"r"(bar) : "memory"); }
__device__ __forceinline__ void mbar_arrive_cluster(uint32_t addr) { asm volatile("mbarrier.arrive.shared::cluster.b64 _, [%0];" ::"r"(addr) : "memory"); }
__device__ __forceinline__ bool mbar_try(uint32_t bar, uint32_t parity) {
  uint32_t ok;
  asm volatile("{\n.reg .pred p;\nmbarrier.try_wait.parity.shared::cta.b64 p, [%1], %2;\nselp.u32 %0, 1, 0, p;\n}\n" : "=r"(ok) : "r"(bar), "r"(parity) : "memory");
  return ok;
}
__device__ __forceinline__ void mbar_wait(uint32_t bar, uint32_t parity, int& budget) {
#pragma unroll 1
  while (!mbar_try(bar, parity)) { if (--budget < 0) break; }
}
__device__ __forceinline__ void mbar_wait(uint32_t bar, uint32_t parity) {
#pragma unroll 1
  while (!mbar_try(bar, parity)) {}
}
__device__ __forceinline__ unsigned ld_acquire(const unsigned* p) { unsigned v; asm volatile("ld.acquire.gpu.global.u32 %0, [%1];" : "=r"(v) : "l"(p) : "memory"); return v; }
__device__ __forceinline__ void wait_flag(const unsigned* p, unsigned target) {
#pragma unroll 1
  while (__any_sync(~0u, (int)(ld_acquire(p) - target) < 0)) {}
}
__device__ __forceinline__ void red_release(unsigned* p) { asm volatile("red.release.gpu.global.add.u32 [%0], 1;" ::"l"(p) : "memory"); }
__device__ __forceinline__ void fence_proxy_async() { asm volatile("fence.proxy.async.global;" ::: "memory"); }
__device__ __forceinline__ bool elect() {
  uint32_t p;
  asm volatile("{\n.reg .pred P;\nelect.sync _|P, 0xffffffff;\nselp.u32 %0, 1, 0, P;\n}\n" : "=r"(p));
  return p;
}
__device__ __forceinline__ void cluster_arrive() { asm volatile("barrier.cluster.arrive.relaxed.aligned;" ::: "memory"); }
__device__ __forceinline__ void cluster_wait() { asm volatile("barrier.cluster.wait.aligned;" ::: "memory"); }
__device__ __forceinline__ void cluster_sync() { cluster_arrive(); cluster_wait(); }
__device__ __forceinline__ void tma2d(uint32_t dst, const CUtensorMap* tm, int c0, int c1, uint32_t bar) {
  asm volatile("cp.async.bulk.tensor.2d.shared::cluster.global.mbarrier::complete_tx::bytes [%0], [%1, {%3, %4}], [%2];"
               ::"r"(dst), "l"(tm), "r"(bar), "r"(c0), "r"(c1) : "memory");
}
constexpr uint64_t POL_FIRST = 0x12F0000000000000ull;
__device__ __forceinline__ void tma4d_mc(uint32_t dst, const CUtensorMap* tm, int c2, int c3, uint32_t bar) {
  asm volatile("cp.async.bulk.tensor.4d.shared::cluster.global.mbarrier::complete_tx::bytes.multicast::cluster.L2::cache_hint [%0], [%1, {%3, %3, %4, %5}], [%2], %6, %7;"
               ::"r"(dst), "l"(tm), "r"(bar), "r"(0), "r"(c2), "r"(c3), "h"((uint16_t)3), "l"(POL_FIRST) : "memory");
}
__device__ __forceinline__ void tma5d_mc(uint32_t dst, const CUtensorMap* tm, int c2, int c4, uint32_t bar) {
  asm volatile("cp.async.bulk.tensor.5d.shared::cluster.global.mbarrier::complete_tx::bytes.multicast::cluster.L2::cache_hint [%0], [%1, {%3, %3, %4, %3, %5}], [%2], %6, %7;"
               ::"r"(dst), "l"(tm), "r"(bar), "r"(0), "r"(c2), "r"(c4), "h"((uint16_t)3), "l"(POL_FIRST) : "memory");
}
__device__ __forceinline__ void bulk_load(uint32_t dst, const void* src, uint32_t bytes, uint32_t bar) {
  asm volatile("cp.async.bulk.shared::cluster.global.mbarrier::complete_tx::bytes.L2::cache_hint [%0], [%1], %2, [%3], %4;" ::"r"(dst), "l"(src), "r"(bytes), "r"(bar), "l"(POL_FIRST) : "memory");
}
__device__ __forceinline__ void tma2d_store(const CUtensorMap* tm, uint32_t src, int c0, int c1) {
  asm volatile("cp.async.bulk.tensor.2d.global.shared::cta.bulk_group [%0, {%2, %3}], [%1];" ::"l"(tm), "r"(src), "r"(c0), "r"(c1) : "memory");
}
__device__ __forceinline__ uint32_t lds32(uint32_t a) { uint32_t v; asm volatile("ld.shared.u32 %0, [%1];" : "=r"(v) : "r"(a) : "memory"); return v; }
__device__ __forceinline__ uint2 lds64(uint32_t a) { uint2 v; asm volatile("ld.shared.v2.u32 {%0,%1}, [%2];" : "=r"(v.x), "=r"(v.y) : "r"(a) : "memory"); return v; }
__device__ __forceinline__ uint4 lds128(uint32_t a) { uint4 v; asm volatile("ld.shared.v4.u32 {%0,%1,%2,%3}, [%4];" : "=r"(v.x), "=r"(v.y), "=r"(v.z), "=r"(v.w) : "r"(a) : "memory"); return v; }
__device__ __forceinline__ void ldsm4(uint32_t a, uint32_t* v) {
  asm volatile("ldmatrix.sync.aligned.m8n8.x4.shared.b16 {%0,%1,%2,%3}, [%4];" : "=r"(v[0]), "=r"(v[1]), "=r"(v[2]), "=r"(v[3]) : "r"(a) : "memory");
}
__device__ __forceinline__ void stsm4(uint32_t a, const uint32_t* v) {
  asm volatile("stmatrix.sync.aligned.m8n8.x4.shared.b16 [%0], {%1,%2,%3,%4};" ::"r"(a), "r"(v[0]), "r"(v[1]), "r"(v[2]), "r"(v[3]) : "memory");
}
__device__ __forceinline__ void sts32(uint32_t a, uint32_t v) { asm volatile("st.shared.u32 [%0], %1;" ::"r"(a), "r"(v) : "memory"); }
__device__ __forceinline__ void st_pkt(uint4* p, uint32_t a, uint32_t b, uint32_t c, uint32_t d) {
  asm volatile("st.relaxed.gpu.global.v4.b32 [%0], {%1, %2, %3, %4};" ::"l"(p), "r"(a), "r"(b), "r"(c), "r"(d) : "memory");
}
__device__ __forceinline__ void st_pkt8(void* p, uint32_t a, uint32_t b) {
  asm volatile("{\n.reg .b64 v;\nmov.b64 v, {%1, %2};\nst.relaxed.gpu.global.b64 [%0], v;\n}\n" ::"l"(p), "r"(a), "r"(b) : "memory");
}
__device__ __forceinline__ uint4 ld_pkt(const uint4* p) {
  uint4 v;
  asm volatile("{\n.reg .b128 v;\nld.relaxed.gpu.global.b128 v, [%4];\nmov.b128 {%0, %1, %2, %3}, v;\n}\n" : "=r"(v.x), "=r"(v.y), "=r"(v.z), "=r"(v.w) : "l"(p) : "memory");
  return v;
}
__device__ __forceinline__ uint4 ldg_nc(const void* p) {
  uint4 v;
  asm volatile("ld.global.nc.v4.u32 {%0,%1,%2,%3}, [%4];" : "=r"(v.x), "=r"(v.y), "=r"(v.z), "=r"(v.w) : "l"(p));
  return v;
}
#define WG_FENCE() asm volatile("wgmma.fence.sync.aligned;" ::: "memory")
#define WG_COMMIT() asm volatile("wgmma.commit_group.sync.aligned;" ::: "memory")
#define WG_WAIT(n) asm volatile("wgmma.wait_group.sync.aligned " #n ";" ::: "memory")
template <int N> __device__ __forceinline__ void reg_fence(float (&d)[N]) {
#pragma unroll
  for (int i = 0; i < N; i++) asm volatile("" : "+f"(d[i])::"memory");
}
template <int N> __device__ __forceinline__ void reg_fence(uint32_t (&d)[N]) {
#pragma unroll
  for (int i = 0; i < N; i++) asm volatile("" : "+r"(d[i])::"memory");
}
__device__ __forceinline__ constexpr uint64_t desc_hi(uint32_t lbo, uint32_t sbo, uint64_t sw) {
  return ((uint64_t)(lbo >> 4) << 16) | ((uint64_t)(sbo >> 4) << 32) | (sw << 62);
}
__device__ __forceinline__ uint64_t mkdesc(uint32_t addr, uint64_t hi) { return hi | (uint64_t)((addr & 0x3FFFF) >> 4); }
__device__ __forceinline__ uint32_t pack_bf16(float lo, float hi) { uint32_t r; asm("cvt.rn.bf16x2.f32 %0, %1, %2;" : "=r"(r) : "f"(hi), "f"(lo)); return r; }
__device__ __forceinline__ float bf_lo(uint32_t v) { return __uint_as_float(v << 16); }
__device__ __forceinline__ float bf_hi(uint32_t v) { return __uint_as_float(v & 0xffff0000u); }
__device__ __forceinline__ uint32_t hadd2(uint32_t a, uint32_t b) { uint32_t r; asm("add.rn.bf16x2 %0, %1, %2;" : "=r"(r) : "r"(a), "r"(b)); return r; }
__device__ __forceinline__ uint32_t hsub2(uint32_t a, uint32_t b) { uint32_t r; asm("sub.rn.bf16x2 %0, %1, %2;" : "=r"(r) : "r"(a), "r"(b)); return r; }
__device__ __forceinline__ uint32_t hmul2(uint32_t a, uint32_t b) { uint32_t r; asm("mul.rn.bf16x2 %0, %1, %2;" : "=r"(r) : "r"(a), "r"(b)); return r; }
__device__ __forceinline__ float rbf(float x) { return __bfloat162float(__float2bfloat16_rn(x)); }
__device__ __forceinline__ float ex2(float x) { float y; asm("ex2.approx.ftz.f32 %0, %1;" : "=f"(y) : "f"(x)); return y; }
__device__ __forceinline__ float rcp(float x) { float y; asm("rcp.approx.ftz.f32 %0, %1;" : "=f"(y) : "f"(x)); return y; }
__device__ __forceinline__ float sigmoid_f(float x) { return rcp(1.f + ex2(x * -1.4426950408889634f)); }
__device__ __forceinline__ float silu_f(float x) { return x * sigmoid_f(x); }

__device__ __forceinline__ void wg_ss192t(float (&d)[96], uint64_t da, uint64_t db, int sd) {
  asm volatile("{\n.reg .pred p;\nsetp.ne.b32 p, %98, 0;\n"
    "wgmma.mma_async.sync.aligned.m64n192k16.f32.bf16.bf16 {%0,%1,%2,%3,%4,%5,%6,%7,%8,%9,%10,%11,%12,%13,%14,%15,%16,%17,%18,%19,%20,%21,%22,%23,%24,%25,%26,%27,%28,%29,%30,%31,%32,%33,%34,%35,%36,%37,%38,%39,%40,%41,%42,%43,%44,%45,%46,%47,%48,%49,%50,%51,%52,%53,%54,%55,%56,%57,%58,%59,%60,%61,%62,%63,%64,%65,%66,%67,%68,%69,%70,%71,%72,%73,%74,%75,%76,%77,%78,%79,%80,%81,%82,%83,%84,%85,%86,%87,%88,%89,%90,%91,%92,%93,%94,%95}, %96, %97, p, 1, 1, 0, 1;\n}\n"
    : "+f"(d[0]),"+f"(d[1]),"+f"(d[2]),"+f"(d[3]),"+f"(d[4]),"+f"(d[5]),"+f"(d[6]),"+f"(d[7]),"+f"(d[8]),"+f"(d[9]),"+f"(d[10]),"+f"(d[11]),"+f"(d[12]),"+f"(d[13]),"+f"(d[14]),"+f"(d[15]),"+f"(d[16]),"+f"(d[17]),"+f"(d[18]),"+f"(d[19]),"+f"(d[20]),"+f"(d[21]),"+f"(d[22]),"+f"(d[23]),"+f"(d[24]),"+f"(d[25]),"+f"(d[26]),"+f"(d[27]),"+f"(d[28]),"+f"(d[29]),"+f"(d[30]),"+f"(d[31]),"+f"(d[32]),"+f"(d[33]),"+f"(d[34]),"+f"(d[35]),"+f"(d[36]),"+f"(d[37]),"+f"(d[38]),"+f"(d[39]),"+f"(d[40]),"+f"(d[41]),"+f"(d[42]),"+f"(d[43]),"+f"(d[44]),"+f"(d[45]),"+f"(d[46]),"+f"(d[47]),"+f"(d[48]),"+f"(d[49]),"+f"(d[50]),"+f"(d[51]),"+f"(d[52]),"+f"(d[53]),"+f"(d[54]),"+f"(d[55]),"+f"(d[56]),"+f"(d[57]),"+f"(d[58]),"+f"(d[59]),"+f"(d[60]),"+f"(d[61]),"+f"(d[62]),"+f"(d[63]),"+f"(d[64]),"+f"(d[65]),"+f"(d[66]),"+f"(d[67]),"+f"(d[68]),"+f"(d[69]),"+f"(d[70]),"+f"(d[71]),"+f"(d[72]),"+f"(d[73]),"+f"(d[74]),"+f"(d[75]),"+f"(d[76]),"+f"(d[77]),"+f"(d[78]),"+f"(d[79]),"+f"(d[80]),"+f"(d[81]),"+f"(d[82]),"+f"(d[83]),"+f"(d[84]),"+f"(d[85]),"+f"(d[86]),"+f"(d[87]),"+f"(d[88]),"+f"(d[89]),"+f"(d[90]),"+f"(d[91]),"+f"(d[92]),"+f"(d[93]),"+f"(d[94]),"+f"(d[95])
    : "l"(da), "l"(db), "r"(sd));
}
__device__ __forceinline__ void wg_rs64(float (&d)[32], uint32_t a0, uint32_t a1, uint32_t a2, uint32_t a3, uint64_t db, int sd) {
  asm volatile("{\n.reg .pred p;\nsetp.ne.b32 p, %37, 0;\n"
    "wgmma.mma_async.sync.aligned.m64n64k16.f32.bf16.bf16 {%0,%1,%2,%3,%4,%5,%6,%7,%8,%9,%10,%11,%12,%13,%14,%15,%16,%17,%18,%19,%20,%21,%22,%23,%24,%25,%26,%27,%28,%29,%30,%31}, {%32,%33,%34,%35}, %36, p, 1, 1, 0;\n}\n"
    : "+f"(d[0]),"+f"(d[1]),"+f"(d[2]),"+f"(d[3]),"+f"(d[4]),"+f"(d[5]),"+f"(d[6]),"+f"(d[7]),"+f"(d[8]),"+f"(d[9]),"+f"(d[10]),"+f"(d[11]),"+f"(d[12]),"+f"(d[13]),"+f"(d[14]),"+f"(d[15]),"+f"(d[16]),"+f"(d[17]),"+f"(d[18]),"+f"(d[19]),"+f"(d[20]),"+f"(d[21]),"+f"(d[22]),"+f"(d[23]),"+f"(d[24]),"+f"(d[25]),"+f"(d[26]),"+f"(d[27]),"+f"(d[28]),"+f"(d[29]),"+f"(d[30]),"+f"(d[31])
    : "r"(a0), "r"(a1), "r"(a2), "r"(a3), "l"(db), "r"(sd));
}
__device__ __forceinline__ void wg_rs192t(float (&d)[96], uint32_t a0, uint32_t a1, uint32_t a2, uint32_t a3, uint64_t db, int sd) {
  asm volatile("{\n.reg .pred p;\nsetp.ne.b32 p, %101, 0;\n"
    "wgmma.mma_async.sync.aligned.m64n192k16.f32.bf16.bf16 {%0,%1,%2,%3,%4,%5,%6,%7,%8,%9,%10,%11,%12,%13,%14,%15,%16,%17,%18,%19,%20,%21,%22,%23,%24,%25,%26,%27,%28,%29,%30,%31,%32,%33,%34,%35,%36,%37,%38,%39,%40,%41,%42,%43,%44,%45,%46,%47,%48,%49,%50,%51,%52,%53,%54,%55,%56,%57,%58,%59,%60,%61,%62,%63,%64,%65,%66,%67,%68,%69,%70,%71,%72,%73,%74,%75,%76,%77,%78,%79,%80,%81,%82,%83,%84,%85,%86,%87,%88,%89,%90,%91,%92,%93,%94,%95}, {%96,%97,%98,%99}, %100, p, 1, 1, 1;\n}\n"
    : "+f"(d[0]),"+f"(d[1]),"+f"(d[2]),"+f"(d[3]),"+f"(d[4]),"+f"(d[5]),"+f"(d[6]),"+f"(d[7]),"+f"(d[8]),"+f"(d[9]),"+f"(d[10]),"+f"(d[11]),"+f"(d[12]),"+f"(d[13]),"+f"(d[14]),"+f"(d[15]),"+f"(d[16]),"+f"(d[17]),"+f"(d[18]),"+f"(d[19]),"+f"(d[20]),"+f"(d[21]),"+f"(d[22]),"+f"(d[23]),"+f"(d[24]),"+f"(d[25]),"+f"(d[26]),"+f"(d[27]),"+f"(d[28]),"+f"(d[29]),"+f"(d[30]),"+f"(d[31]),"+f"(d[32]),"+f"(d[33]),"+f"(d[34]),"+f"(d[35]),"+f"(d[36]),"+f"(d[37]),"+f"(d[38]),"+f"(d[39]),"+f"(d[40]),"+f"(d[41]),"+f"(d[42]),"+f"(d[43]),"+f"(d[44]),"+f"(d[45]),"+f"(d[46]),"+f"(d[47]),"+f"(d[48]),"+f"(d[49]),"+f"(d[50]),"+f"(d[51]),"+f"(d[52]),"+f"(d[53]),"+f"(d[54]),"+f"(d[55]),"+f"(d[56]),"+f"(d[57]),"+f"(d[58]),"+f"(d[59]),"+f"(d[60]),"+f"(d[61]),"+f"(d[62]),"+f"(d[63]),"+f"(d[64]),"+f"(d[65]),"+f"(d[66]),"+f"(d[67]),"+f"(d[68]),"+f"(d[69]),"+f"(d[70]),"+f"(d[71]),"+f"(d[72]),"+f"(d[73]),"+f"(d[74]),"+f"(d[75]),"+f"(d[76]),"+f"(d[77]),"+f"(d[78]),"+f"(d[79]),"+f"(d[80]),"+f"(d[81]),"+f"(d[82]),"+f"(d[83]),"+f"(d[84]),"+f"(d[85]),"+f"(d[86]),"+f"(d[87]),"+f"(d[88]),"+f"(d[89]),"+f"(d[90]),"+f"(d[91]),"+f"(d[92]),"+f"(d[93]),"+f"(d[94]),"+f"(d[95])
    : "r"(a0), "r"(a1), "r"(a2), "r"(a3), "l"(db), "r"(sd));
}
__device__ __forceinline__ void wg_ss160t(float (&d)[80], uint64_t da, uint64_t db, int sd) {
  asm volatile("{\n.reg .pred p;\nsetp.ne.b32 p, %82, 0;\n"
    "wgmma.mma_async.sync.aligned.m64n160k16.f32.bf16.bf16 {%0,%1,%2,%3,%4,%5,%6,%7,%8,%9,%10,%11,%12,%13,%14,%15,%16,%17,%18,%19,%20,%21,%22,%23,%24,%25,%26,%27,%28,%29,%30,%31,%32,%33,%34,%35,%36,%37,%38,%39,%40,%41,%42,%43,%44,%45,%46,%47,%48,%49,%50,%51,%52,%53,%54,%55,%56,%57,%58,%59,%60,%61,%62,%63,%64,%65,%66,%67,%68,%69,%70,%71,%72,%73,%74,%75,%76,%77,%78,%79}, %80, %81, p, 1, 1, 0, 1;\n}\n"
    : "+f"(d[0]),"+f"(d[1]),"+f"(d[2]),"+f"(d[3]),"+f"(d[4]),"+f"(d[5]),"+f"(d[6]),"+f"(d[7]),"+f"(d[8]),"+f"(d[9]),"+f"(d[10]),"+f"(d[11]),"+f"(d[12]),"+f"(d[13]),"+f"(d[14]),"+f"(d[15]),"+f"(d[16]),"+f"(d[17]),"+f"(d[18]),"+f"(d[19]),"+f"(d[20]),"+f"(d[21]),"+f"(d[22]),"+f"(d[23]),"+f"(d[24]),"+f"(d[25]),"+f"(d[26]),"+f"(d[27]),"+f"(d[28]),"+f"(d[29]),"+f"(d[30]),"+f"(d[31]),"+f"(d[32]),"+f"(d[33]),"+f"(d[34]),"+f"(d[35]),"+f"(d[36]),"+f"(d[37]),"+f"(d[38]),"+f"(d[39]),"+f"(d[40]),"+f"(d[41]),"+f"(d[42]),"+f"(d[43]),"+f"(d[44]),"+f"(d[45]),"+f"(d[46]),"+f"(d[47]),"+f"(d[48]),"+f"(d[49]),"+f"(d[50]),"+f"(d[51]),"+f"(d[52]),"+f"(d[53]),"+f"(d[54]),"+f"(d[55]),"+f"(d[56]),"+f"(d[57]),"+f"(d[58]),"+f"(d[59]),"+f"(d[60]),"+f"(d[61]),"+f"(d[62]),"+f"(d[63]),"+f"(d[64]),"+f"(d[65]),"+f"(d[66]),"+f"(d[67]),"+f"(d[68]),"+f"(d[69]),"+f"(d[70]),"+f"(d[71]),"+f"(d[72]),"+f"(d[73]),"+f"(d[74]),"+f"(d[75]),"+f"(d[76]),"+f"(d[77]),"+f"(d[78]),"+f"(d[79])
    : "l"(da), "l"(db), "r"(sd));
}
__device__ __forceinline__ void wg_ss80t(float (&d)[40], uint64_t da, uint64_t db, int sd) {
  asm volatile("{\n.reg .pred p;\nsetp.ne.b32 p, %42, 0;\n"
    "wgmma.mma_async.sync.aligned.m64n80k16.f32.bf16.bf16 {%0,%1,%2,%3,%4,%5,%6,%7,%8,%9,%10,%11,%12,%13,%14,%15,%16,%17,%18,%19,%20,%21,%22,%23,%24,%25,%26,%27,%28,%29,%30,%31,%32,%33,%34,%35,%36,%37,%38,%39}, %40, %41, p, 1, 1, 0, 1;\n}\n"
    : "+f"(d[0]),"+f"(d[1]),"+f"(d[2]),"+f"(d[3]),"+f"(d[4]),"+f"(d[5]),"+f"(d[6]),"+f"(d[7]),"+f"(d[8]),"+f"(d[9]),"+f"(d[10]),"+f"(d[11]),"+f"(d[12]),"+f"(d[13]),"+f"(d[14]),"+f"(d[15]),"+f"(d[16]),"+f"(d[17]),"+f"(d[18]),"+f"(d[19]),"+f"(d[20]),"+f"(d[21]),"+f"(d[22]),"+f"(d[23]),"+f"(d[24]),"+f"(d[25]),"+f"(d[26]),"+f"(d[27]),"+f"(d[28]),"+f"(d[29]),"+f"(d[30]),"+f"(d[31]),"+f"(d[32]),"+f"(d[33]),"+f"(d[34]),"+f"(d[35]),"+f"(d[36]),"+f"(d[37]),"+f"(d[38]),"+f"(d[39])
    : "l"(da), "l"(db), "r"(sd));
}

struct Maps { CUtensorMap x, xn, wq, k, v, wo, w3[2], xg, xe, out; };
struct Params {
  const __nv_bfloat16 *x, *wr, *wg, *wu, *wd, *k, *v;
  Scratch* s;
};

__device__ __forceinline__ void side_cta(const Params& p, int sc, unsigned epoch, float* sm) {
  const int tid = threadIdx.x, lane = tid & 31, warp = tid >> 5;
  int budget = WAIT_BUDGET;
  float* s_x = sm;
  float* s_red = sm + 1280;
  float* s_h = s_red + 6144;
  uint4* s_c = (uint4*)(s_h + 768);
  uint2* s_st = (uint2*)(s_c + 16);
  constexpr int DEPTH = 7, STEP = 4 * 6144;
  const uint32_t ring = smem_u32(s_st + 512) + tid * 16;
  const int cg = tid % 96, ks = tid / 96, cd = tid % 80, kd = tid / 80;
  const __nv_bfloat16* wp = (cg < 48 ? p.wg : p.wu) + (size_t)(ks * 160) * FF + sc * 384 + (cg % 48) * 8;
  int kf = 0, pitch = FF;
  uint32_t slot = ring;
  auto refill = [&]() {
    if (kf == 40) { wp = p.wd + (size_t)(sc * 384 + kd * 96) * DM + cd * 8; pitch = DM; }
    if (kf < (tid < 320 ? 64 : 40)) {
#pragma unroll
      for (int j = 0; j < 4; j++) asm volatile("cp.async.cg.shared.global.L2::cache_hint [%0], [%1], 16, %2;" ::"r"(slot + j * 6144), "l"(wp + j * pitch), "l"(POL_FIRST) : "memory");
    }
    asm volatile("cp.async.commit_group;" ::: "memory");
    wp += 4 * pitch; kf++;
    slot += STEP; if (slot == ring + DEPTH * STEP) slot = ring;
  };
  auto gemv = [&](int n, const float* x0, const float* x1, float* out) {
    float a[2][8] = {};
#pragma unroll 1
    for (int k = 0; k < n; k += 4) {
      refill();
      asm volatile("cp.async.wait_group %0;" ::"n"(DEPTH - 1) : "memory");
      const float4 f0 = *(const float4*)(x0 + k), f1 = *(const float4*)(x1 + k);
      const float y0[4] = {f0.x, f0.y, f0.z, f0.w}, y1[4] = {f1.x, f1.y, f1.z, f1.w};
#pragma unroll
      for (int j = 0; j < 4; j++) {
        const uint4 v = lds128(slot + j * 6144);
        const uint32_t u[4] = {v.x, v.y, v.z, v.w};
#pragma unroll
        for (int i = 0; i < 4; i++) {
          a[0][2 * i] += y0[j] * bf_lo(u[i]); a[0][2 * i + 1] += y0[j] * bf_hi(u[i]);
          a[1][2 * i] += y1[j] * bf_lo(u[i]); a[1][2 * i + 1] += y1[j] * bf_hi(u[i]);
        }
      }
    }
#pragma unroll
    for (int i = 0; i < 16; i++) out[(i >> 3) * 768 + (i & 7)] = a[i >> 3][i & 7];
  };
  auto load_row = [&](const __nv_bfloat16* r, uint32_t (&v)[10]) {
    const uint4 a = __ldg((const uint4*)r + lane), b = __ldg((const uint4*)r + 32 + lane);
    const uint2 c = __ldg((const uint2*)r + 128 + lane);
    v[0] = a.x; v[1] = a.y; v[2] = a.z; v[3] = a.w; v[4] = b.x; v[5] = b.y; v[6] = b.z; v[7] = b.w; v[8] = c.x; v[9] = c.y;
  };
  uint32_t wr[10], xb[3][10];
  load_row(p.wr, wr);
  auto stat2 = [&](int pair) {
    uint4 v;
    do v = ld_pkt((const uint4*)p.s->stat + pair); while ((((v.x ^ (epoch + 1)) | (v.z ^ (epoch + 1))) & 0xffff) && --budget >= 0);
    return make_uint4(__byte_perm(v.x, 0, 0x3232), v.y, __byte_perm(v.z, 0, 0x3232), v.w);
  };
  if (tid < 256) ((uint4*)s_st)[tid] = stat2(sc * 256 + tid);
  __syncthreads();
#pragma unroll
  for (int b = 0; b < 3; b++) load_row(p.x + (size_t)(sc * 512 + warp + 12 * b) * DM, xb[b]);
#pragma unroll 1
  for (int k = 0; k < DEPTH - 1; k++) refill();
  float v0 = -INFINITY, v1 = -INFINITY; int i0 = 0xfff, i1 = 0xfff;
  auto better = [](float a, int ia, float b, int ib) { return a > b || (a == b && ia < ib); };
  auto push = [&](float v, int i) {
    if (better(v, i, v0, i0)) { v1 = v0; i1 = i0; v0 = v; i0 = i; }
    else if (better(v, i, v1, i1)) { v1 = v; i1 = i; }
  };
  auto push2 = [&](uint4 c) { push(__uint_as_float(c.x), c.y & 0xfff); push(__uint_as_float(c.z), c.w & 0xfff); };
#pragma unroll 1
  for (int l3 = warp; l3 < 512; l3 += 36) {
#pragma unroll
    for (int b = 0; b < 3; b++) {
      const int lr = l3 + 12 * b;
      if (lr >= 512) break;
      const uint2 st = s_st[lr];
      uint32_t v[10];
#pragma unroll
      for (int i = 0; i < 10; i++) v[i] = hsub2(xb[b][i], st.x);
      if (lr + 36 < 512) load_row(p.x + (size_t)(sc * 512 + lr + 36) * DM, xb[b]);
      float r0 = 0.f, r1 = 0.f;
#pragma unroll
      for (int i = 0; i < 10; i++) {
        const uint32_t xn = pack_bf16(bf_lo(v[i]) * __uint_as_float(st.y), bf_hi(v[i]) * __uint_as_float(st.y));
        r0 = fmaf(bf_lo(xn), bf_lo(wr[i]), r0); r1 = fmaf(bf_hi(xn), bf_hi(wr[i]), r1);
      }
      r0 += r1;
#pragma unroll
      for (int o = 16; o > 0; o >>= 1) r0 += __shfl_xor_sync(~0u, r0, o);
      push(rbf(r0), sc * 512 + lr);
    }
  }
  if (lane == 0) s_c[warp] = make_uint4(__float_as_uint(v0), i0, __float_as_uint(v1), i1);
  __syncthreads();
#pragma unroll 1
  for (int w = 1; w < 12; w++) push2(s_c[(warp + w) % 12]);
  const uint32_t tag = (epoch + 1) << 12;
  if (tid == 0) st_pkt(p.s->cand + sc, __float_as_uint(v0), i0 | tag, __float_as_uint(v1), i1);
  {
    uint4 c;
    do c = ld_pkt(p.s->cand + (lane & 3)); while (((c.y ^ tag) >> 12) && --budget >= 0);
#pragma unroll 1
    for (int w = 1; w < 4; w++) { const int o = (sc + w) & 3; push2(make_uint4(__shfl_sync(~0u, c.x, o), __shfl_sync(~0u, c.y, o), __shfl_sync(~0u, c.z, o), __shfl_sync(~0u, c.w, o))); }
  }
  if (i0 >= SQ) i0 = 0;
  if (i1 >= SQ) i1 = (i0 == 0) ? 1 : 0;
  if (tid < 320) {
    const int row = tid < 160 ? i0 : i1;
    const uint2 u = __ldg((const uint2*)(p.x + (size_t)row * DM) + tid % 160);
    const uint4 st = stat2(row >> 1);
    const uint32_t mean2 = row & 1 ? st.z : st.x, d0 = hsub2(u.x, mean2), d1 = hsub2(u.y, mean2);
    const float inv = __uint_as_float(row & 1 ? st.w : st.y);
    ((float4*)s_x)[tid] = make_float4(rbf(bf_lo(d0) * inv), rbf(bf_hi(d0) * inv), rbf(bf_lo(d1) * inv), rbf(bf_hi(d1) * inv));
  }
  __syncthreads();
  gemv(160, s_x + ks * 160, s_x + DM + ks * 160, s_red + ks * 1536 + cg * 8);
  __syncthreads();
#pragma unroll
  for (int t = 0; t < 2; t++) {
    float g = 0.f, u = 0.f;
#pragma unroll
    for (int k = 0; k < 4; k++) { g += s_red[(k * 2 + t) * 768 + tid]; u += s_red[(k * 2 + t) * 768 + 384 + tid]; }
    s_h[t * 384 + tid] = rbf(rbf(silu_f(rbf(g))) * rbf(u));
  }
  __syncthreads();
  if (tid < 320) gemv(96, s_h + kd * 96, s_h + 384 + kd * 96, s_red + kd * 1536 + cd * 8);
  __syncthreads();
  const int o4 = tid + (tid < 160 ? 0 : 32);
  if (tid < 320) {
    const float4 *r = (const float4*)s_red + o4, a = r[0], b = r[384], c = r[768], d = r[1152];
    ((float4*)p.s->ffn)[sc * 320 + tid] = make_float4(a.x + b.x + c.x + d.x, a.y + b.y + c.y + d.y, a.z + b.z + c.z + d.z, a.w + b.w + c.w + d.w);
  }
  __syncthreads();
  if (tid == 0) { __threadfence(); s_c[0].x = (atomicAdd(&p.s->flag[FL_SIDE], 1u) & 3u) == 3u; __threadfence(); }
  __syncthreads();
  if (s_c[0].x) {
    if (tid < 320) {
      const float4 *r = (const float4*)p.s->ffn + tid, a = __ldcg(r), b = __ldcg(r + 320), c = __ldcg(r + 640), d = __ldcg(r + 960), x = ((float4*)s_x)[tid];
      const float rs = rbf(sigmoid_f(tid < 160 ? v0 : v1));
      auto gate = [&](float xn, float y) { return silu_f(rbf(xn + rbf(rbf(y) * rs))); };
      if (tid == 0) { p.s->sel[0] = i0; p.s->sel[1] = i1; }
      ((uint2*)p.s->gsel)[tid] =
          make_uint2(pack_bf16(gate(x.x, a.x + b.x + c.x + d.x), gate(x.y, a.y + b.y + c.y + d.y)), pack_bf16(gate(x.z, a.z + b.z + c.z + d.z), gate(x.w, a.w + b.w + c.w + d.w)));
    }
    __syncthreads();
    if (tid == 0) red_release(&p.s->flag[FL_FFN]);
  }
}

constexpr float SM_C = 0.07216878364870322f * 1.4426950408889634f;

#define LD 0
#define LS 3
__device__ __forceinline__ void ln_piece(const Params& p, uint32_t (&r)[48], int k, int row, int l16) {
  auto f = [&](int i) { return __uint_as_float(r[i]); };
  if (k == LD) {
#pragma unroll
    for (int i = 0; i < 5; i++) {
      const uint4 v = ldg_nc((const uint4*)(p.x + (size_t)row * DM) + i * 16 + l16);
      r[4 * i] = v.x; r[4 * i + 1] = v.y; r[4 * i + 2] = v.z; r[4 * i + 3] = v.w;
    }
    asm volatile("ld.relaxed.gpu.global.v2.u32 {%0,%1}, [%2];" : "=r"(r[20]), "=r"(r[21]) : "l"(&p.s->done));
  } else if (k == LS || k == LS + 1) {
    if (k == LS) { r[22] = __shfl_sync(~0u, r[0], 0, 16) << 16; r[23] = r[24] = 0; }
    float s0 = f(23), s1 = 0.f, q0 = f(24), q1 = 0.f;
#pragma unroll
    for (int i = 10 * (k - LS); i < 10 * (k - LS) + 10; i++) {
      const float a = bf_lo(r[i]) - f(22), b = bf_hi(r[i]) - f(22);
      s0 += a; s1 += b; q0 = fmaf(a, a, q0); q1 = fmaf(b, b, q1);
    }
    r[23] = __float_as_uint(s0 + s1); r[24] = __float_as_uint(q0 + q1);
  } else if (k == LS + 2) {
    float s0 = f(23), q0 = f(24);
#pragma unroll
    for (int o = 8; o > 0; o >>= 1) { s0 += __shfl_xor_sync(~0u, s0, o); q0 += __shfl_xor_sync(~0u, q0, o); }
    s0 *= 1.f / DM;
    const float mean = f(22) + s0, var = rbf(fmaxf(fmaf(q0, 1.f / DM, -s0 * s0), 0.f));
    float sd; asm("sqrt.approx.ftz.f32 %0, %1;" : "=f"(sd) : "f"(rbf(var + 1e-5f)));
    const float inv = rcp(rbf(sd));
    r[22] = pack_bf16(mean, mean); r[23] = __float_as_uint(inv * SM_C);
    const uint32_t tag = __funnelshift_r(r[20], r[21], 7) + 1;
    if (l16 == 0) st_pkt8(&p.s->stat[row], __byte_perm(tag, r[22], 0x7610), __float_as_uint(inv));
  } else if (k > LS + 2 && k <= LS + 5) {
#pragma unroll
    for (int j = 2 * (k - LS - 3); j < 2 * (k - LS - 3) + 2 && j < 5; j++) {
#pragma unroll
      for (int i = 4 * j; i < 4 * j + 4; i++) { const uint32_t d = hsub2(r[i], r[22]); r[i] = pack_bf16(bf_lo(d) * f(23), bf_hi(d) * f(23)); }
      *((uint4*)(p.s->xn + (size_t)row * DM) + j * 16 + l16) = make_uint4(r[4 * j], r[4 * j + 1], r[4 * j + 2], r[4 * j + 3]);
    }
  }
}

constexpr float SM_HI = 0x1p64f, SM_LO = 0x1p-64f;
__device__ __forceinline__ void exp_block(float (&s)[32], float& l0, float& l1, int from = 0, int to = 32) {
#pragma unroll
  for (int i = from; i < to; i++) { s[i] = ex2(s[i]); if (i & 2) l1 += s[i]; else l0 += s[i]; }
}
__device__ __forceinline__ float quad_sum(float v) { v += __shfl_xor_sync(~0u, v, 1); return v + __shfl_xor_sync(~0u, v, 2); }
__device__ __forceinline__ float quad_max(float v) { v = fmaxf(v, __shfl_xor_sync(~0u, v, 1)); return fmaxf(v, __shfl_xor_sync(~0u, v, 2)); }
__device__ __noinline__ void safe_head(const uint32_t* kp, const uint32_t* vp, uint4* io) {
  uint32_t fq[48];
#pragma unroll
  for (int i = 0; i < 12; i++) { const uint4 v = io[(i >> 1) * 512 + (i & 1) * 32]; fq[4 * i] = v.x; fq[4 * i + 1] = v.y; fq[4 * i + 2] = v.z; fq[4 * i + 3] = v.w; }
  float m0 = -INFINITY, m1 = -INFINITY;
#pragma unroll 1
  for (int pass = 0; pass < 3; pass++) {
    float o[48] = {}, l0 = 0.f, l1 = 0.f;
#pragma unroll 1
    for (int n = 0; n < 64; n++) {
      const uint32_t *kr = kp + n * (8 * DH / 2), *vr = vp + n * (8 * DH / 2) + (pass - 1) * 48;
      float d[4] = {};
#pragma unroll
      for (int t = 0; t < 12; t++)
        asm volatile("mma.sync.aligned.m16n8k16.row.col.f32.bf16.bf16.f32 {%0,%1,%2,%3}, {%4,%5,%6,%7}, {%8,%9}, {%0,%1,%2,%3};"
                     : "+f"(d[0]), "+f"(d[1]), "+f"(d[2]), "+f"(d[3])
                     : "r"(fq[4 * t]), "r"(fq[4 * t + 1]), "r"(fq[4 * t + 2]), "r"(fq[4 * t + 3]), "r"(__ldg(kr + 8 * t)), "r"(__ldg(kr + 8 * t + 4)));
      if (pass == 0) { m0 = fmaxf(m0, fmaxf(d[0], d[1])); m1 = fmaxf(m1, fmaxf(d[2], d[3])); continue; }
      d[0] = ex2(d[0] - m0); d[1] = ex2(d[1] - m0); d[2] = ex2(d[2] - m1); d[3] = ex2(d[3] - m1);
      l0 += d[0] + d[1]; l1 += d[2] + d[3];
      const uint32_t p0 = pack_bf16(d[0], d[1]), p1 = pack_bf16(d[2], d[3]);
#pragma unroll
      for (int c = 0; c < 12; c++)
        asm volatile("{\n.reg .b32 t;\nmovmatrix.sync.aligned.m8n8.trans.b16 t, %6;\n"
                     "mma.sync.aligned.m16n8k8.row.col.f32.bf16.bf16.f32 {%0,%1,%2,%3}, {%4,%5}, {t}, {%0,%1,%2,%3};\n}\n"
                     : "+f"(o[4 * c]), "+f"(o[4 * c + 1]), "+f"(o[4 * c + 2]), "+f"(o[4 * c + 3]) : "r"(p0), "r"(p1), "r"(__ldg(vr + 4 * c)));
    }
    if (pass == 0) { m0 = quad_max(m0); m1 = quad_max(m1); continue; }
    l0 = rcp(quad_sum(l0)); l1 = rcp(quad_sum(l1));
#pragma unroll
    for (int i = 0; i < 6; i++) {
      const float* v = o + 16 * (i >> 1) + 2 * (i & 1);
      const float r = i & 1 ? l1 : l0;
      io[(3 * (pass - 1) + (i >> 1)) * 512 + (i & 1) * 32] =
          make_uint4(pack_bf16(v[0] * r, v[1] * r), pack_bf16(v[4] * r, v[5] * r), pack_bf16(v[8] * r, v[9] * r), pack_bf16(v[12] * r, v[13] * r));
    }
  }
}

#define CVG 48
#define NE 8
#define PS1 8
#define CSW 0
#define D0 2
#define ROT 2
#define LQ 6
__device__ __forceinline__ constexpr int end_stage(int n) { return n < 4 ? n : n < LQ ? n - 4 : n == LQ ? 4 : n % 5; }
#define Q2N 1
#define SWN 12
#define SCH 0
__device__ __forceinline__ constexpr int sent(int n) {
  constexpr int t[4][15] = {{0, 2, 4, 5, 5, 6, 7, 8,  9, 10, 11, 12, 13, 14, 15},
                            {0, 2, 4, 5, 5, 6, 7, 8,  9, 10, 12, 13, 14, 15, 15},
                            {0, 2, 4, 5, 5, 7, 8, 9, 10, 10, 12, 14, 15, 15, 15},
                            {0, 2, 4, 5, 5, 7, 8, 9, 10, 10, 13, 15, 15, 15, 15}};
  return n < LQ + 2 ? 0 : LQ == 6 && n == 8 ? 3 : t[SCH][n - 6];
}
template <int N> struct IntC { static constexpr int value = N; };
template <int N, int I = 0, class F> __device__ __forceinline__ void static_for(F&& f) { if constexpr (I < N) { f(IntC<I>{}); static_for<N, I + 1>(f); } }

extern __shared__ __align__(1024) uint8_t smem_raw[];
constexpr uint32_t EA = 160, EB = 184;
#define SMEM_LAYOUT                                                                                                          \
  [[maybe_unused]] const uint32_t sb = smem_u32(smem_raw), bar_a = sb + OFF_M, bar_b = bar_a + 40, bar_x = bar_a + 88,      \
      bar_u = bar_a + 96, bar_e = bar_a + 104, bar_o = bar_a + 200, bar_w = bar_a + 208, bar_z = bar_a + 288,                \
      bar_s = bar_a + 296, bar_d = bar_a + 304, s_stat = bar_a + 512, s_sel = s_stat + 1024;

__device__ __forceinline__ int k_block(int t, int hg) {
  const int i = (t * 11) >> 5;
  return ((i < 6 ? (hg & 6) + (i & 1) : hg ^ (i & 1)) * 4 + (i >> 1)) * 6 + (t == 3 * i ? 4 : 2 * (t - 3 * i) - 2);
}

__device__ __noinline__ int errands(Scratch* s, const Maps& m, int warp, uint32_t tag, int budget) {
  SMEM_LAYOUT
  const int lane = threadIdx.x & 31, cl = blockIdx.x >> 1, qt = blockIdx.x & 15, hg = cl >> 3, kq = hg >> 1, nh = hg & 1;
  if (warp == 1) {
#pragma unroll 1
    for (int u = 0; u < 5; u++) {
      mbar_wait(bar_o, u & 1);
      if (lane == 0) red_release(&s->flag[u ? FL_O + (qt * 8 + hg) * 8 : FL_XN + qt * 32]);
      __syncwarp();
    }
  } else if (warp == 2) {
    mbar_wait(bar_x, 0, budget);
    while ((int)(ld_acquire(&s->flag[FL_FFN]) - tag) < 0 && --budget >= 0) {}
    if (lane < 21) {
      const uint4 v = __ldcg(lane ? (const uint4*)(s->gsel + (lane > 10 ? DM - 80 : 0) + nh * 320 + kq * 80) + lane - 1 : (const uint4*)s->sel);
      asm volatile("st.shared.v4.u32 [%0], {%1,%2,%3,%4};" ::"r"(s_sel + 16 * lane), "r"(v.x), "r"(v.y), "r"(v.z), "r"(v.w) : "memory");
    }
    __syncwarp();
    if (lane == 0) { mbar_arrive(bar_u); asm volatile("red.relaxed.gpu.global.add.u64 [%0], 1;" ::"l"(&s->done) : "memory"); }
    while ((int)(ld_acquire(&s->flag[FL_RD + (qt * 8 + (hg ^ 1)) * 8]) - tag) < 0 && --budget >= 0) {}
    if (lane < 3) mbar_arrive(bar_z);
  } else {
    wait_flag(&s->flag[FL_XN + qt * 32], tag * 8);
    fence_proxy_async();
    mbar_wait(bar_a + EA + 32, 1);
    uint32_t a8 = 0, pha = 1;
    const int kb = (qt * 192 + k_block(lane, hg)) * 512;
#pragma unroll 1
    for (int n = 0; n < 54; n++) {
      const int t = n - 30, ko = __shfl_sync(~0u, kb, t);
      if (t == 0 || t == 18) {
        wait_flag(&s->flag[FL_O + (qt * 8 + (t ? 2 * kq + (lane & 1) : lane & 7)) * 8], tag * 4 - (t ? 0 : 1));
        fence_proxy_async();
      }
      mbar_wait(bar_a + EA + a8, pha);
      const uint32_t fb = bar_a + a8, dst = sb + a8 * (TA >> 3);
      if (elect()) {
        if (t >= 0) {
          mbar_expect_tx(fb, TA);
          bulk_load(dst, s->o + ko, TA, fb);
          if (t == 8) {
            mbar_expect_tx(bar_x, 6 * 3840);
#pragma unroll 1
            for (int e = 0; e < 6; e++) tma2d(sb + OFF_B + TW + e * TB, &m.xg, nh * 320 + kq * 80, qt * 128 + e * 24, bar_x);
            asm volatile("prefetch.tensormap [%0];\nprefetch.tensormap [%1];\nprefetch.tensormap [%2];\nprefetch.tensormap [%3];"
                         ::"l"(m.w3), "l"(m.w3 + 1), "l"(&m.xe), "l"(&m.out) : "memory");
          }
          if (t == 22) asm volatile("red.relaxed.gpu.global.add.u32 [%0], 1;" ::"l"(&s->flag[FL_RD + (qt * 8 + hg) * 8]) : "memory");
        } else if (n >= 10 && pha) mbar_arrive(fb);
        else { mbar_expect_tx(fb, TA); tma2d(dst, &m.xn, 8 * a8 + (pha || (n >= 15 && n < 20) ? 0 : 320), qt * 128, fb); }
      }
      a8 += 8; if (a8 == 40) { a8 = 0; pha ^= 1; }
    }
    if (lane < 3) mbar_arrive(bar_z);
  }
  return budget;
}

__global__ void __launch_bounds__(384, 1) __cluster_dims__(2, 1, 1)
fused_kernel(const Params p, const __grid_constant__ Maps m) {
  SMEM_LAYOUT
  const int wi = __shfl_sync(~0u, threadIdx.x >> 5, 0), wg = wi >> 2;
  const int lane = threadIdx.x & 31;
  const int cl = blockIdx.x >> 1;
  const int rank = blockIdx.x & 1;

  if (cl >= 64) {
    const unsigned epoch = (unsigned)(__ldcg(&p.s->done) >> 7);
    side_cta(p, blockIdx.x - 128, epoch, (float*)smem_raw);
    return;
  }
  const int qt = blockIdx.x & 15, hg = cl >> 3;
  const int kq = hg >> 1, nh = hg & 1;

  const int s0 = (5 * ((qt >> 1) & ~(8 / ROT - 1))) >> 2, kg0 = 10 * (qt >> 1) - 8 * s0;
  if (elect()) {
    const int c = (int)(0x5ff7700000ull >> (4 * wi) & 15) + 1;
    for (int i = 0; i < 4; i++) mbar_init(bar_a + 32 * wi + 8 * i, c);
    asm volatile("fence.mbarrier_init.release.cluster;" ::: "memory");
  }
  __syncwarp();
  cluster_arrive();
  if (wi < 2 && elect()) {
    if (wi) { asm volatile("prefetch.tensormap [%0];" ::"l"(&m.wq) : "memory"); mbar_expect_tx(bar_b, TB); mbar_expect_tx(bar_b + 8, TB); }
    else for (int i = 0; i < 2; i++) { mbar_expect_tx(bar_a + 8 * i, TA); tma2d(sb + i * TA, &m.x, 64 * (s0 + i), qt * 128, bar_a + 8 * i); }
  }
  __syncwarp();
  cluster_wait();
  if (wi == 1 && elect())
    for (int i = 0; i < 2; i++) tma4d_mc(sb + OFF_B + i * TB + rank * (TB / 2), &m.wq, 12 * hg, 8 * (s0 + i) + 4 * rank, bar_b + 8 * i);
  if (wg > 0) {
    const int w = wg - 1;
    const int cw = wi - 4;
    asm volatile("setmaxnreg.inc.sync.aligned.u32 232;");
    uint32_t fr[48];
    reg_fence(fr);
    auto ln_row = [&]() { int v = qt * 128 + hg * 16 + cw * 2 + (lane >> 4); asm volatile("" : "+r"(v)); return v; };
    uint32_t rel_addr;
    asm volatile("mapa.shared::cluster.u32 %0, %1, %2;" : "=r"(rel_addr) : "r"(bar_b + EB), "r"(lane & 1));
    auto rel_a = [&](uint32_t o8) { if (lane == 0) mbar_arrive(bar_a + EA + o8); };
    auto rel_b = [&](uint32_t o8) { if (lane < 2) mbar_arrive_cluster(rel_addr + o8); };
    uint32_t b8 = 0, phb = 0;
    auto next_pair = [&]() { b8 += 16; if (b8 == 48) { b8 = 0; phb ^= 1; } };
    const int g = lane >> 2, q = lane & 3;
    constexpr uint64_t HI_A = desc_hi(16, 1024, 1);
    constexpr uint64_t HI_W = desc_hi(1024, 3072, 1);
    constexpr uint64_t HI_O = desc_hi(2048, 512, 2);
    if (w == 1) asm volatile("bar.arrive 1, 256;" ::: "memory");

    uint32_t zero; asm volatile("mov.u32 %0, %%tid.y;" : "=r"(zero));
    float acc[96];
    uint4* optr = p.s->o + (size_t)(qt * 192 + hg * 24) * 512 + (cw * 16 + g) * 4 + (q ^ ((g >> 1) & 3));
    uint32_t rl[4];
    auto store_o = [&](int pp) {
#pragma unroll
      for (int i = (12 * pp + 8) / 9; i < (12 * (pp + 1) + 8) / 9; i++) {
#pragma unroll
        for (int k = 4 * i; k < 4 * i + 4; k++)
          asm volatile("{\n.reg .b32 t;\nmul.rn.bf16x2 t, %0, %2;\nfma.rn.bf16x2 %0, %0, %1, t;\n}\n" : "+r"(fr[k]) : "r"(rl[i & 1]), "r"(rl[2 + (i & 1)]));
        fr[4 * i] &= ~1u;
        optr[(i >> 1) * 512 + (i & 1) * 32] = make_uint4(fr[4 * i], fr[4 * i + 1], fr[4 * i + 2], fr[4 * i + 3]);
      }
      if (pp == 8) optr += 6 * 512;
    };
    auto fresh = [&]() { uint32_t v = sb; asm volatile("" : "+r"(v)); return v; };
    reg_fence(rl);

#pragma unroll 1
    for (int u = 0; u < 4; u++) {
      const uint32_t sq = fresh();
      const uint64_t dA = mkdesc(sq + w * 8192, HI_A), dB0 = mkdesc(sq + OFF_B, HI_W);
      uint32_t pb8 = 0;
#pragma unroll
      for (int s = 0; s < 10; s++) {
        const uint32_t o8 = b8 + 8 * (s & 1);
        const uint64_t dW = dB0 + o8 * (TB >> 7);
        mbar_wait(bar_a + 8 * (s % 5), s / 5);
        mbar_wait(bar_b + o8, phb);
        if (s == 9) asm volatile("bar.sync %0, 256;" ::"r"(1 + w) : "memory");
        WG_FENCE();
#pragma unroll
        for (int kk = 0; kk < 4; kk++) wg_ss192t(acc, dA + ((s % 5) * (TA >> 4) + kk * 2), dW + kk * 384, kk != 0 || s != 0);
        WG_COMMIT();
        if (s == 9) asm volatile("bar.arrive %0, 256;" ::"r"(2 - w) : "memory");
        if (s > 0) { WG_WAIT(1); rel_a(8 * ((s - 1) % 5)); rel_b(pb8); }
        if (s < 9) { if (u > 0) store_o(s); else ln_piece(p, fr, s, ln_row(), lane & 15); }
        if (s == 8) { __syncwarp(); if (lane == 0) mbar_arrive(bar_o); }
        pb8 = o8;
        if (s & 1) next_pair();
      }
      if (u == 0) {
        mbar_wait(bar_s, 0);
        const uint2 s0 = lds64(s_stat + (cw * 16 + g) * 8), s1 = lds64(s_stat + 64 + (cw * 16 + g) * 8);
        const uint32_t msk = q == 0 ? 0xffffffffu : q == 1 ? 0xffffu : 0u;
        const float c0 = SM_C * __uint_as_float(s0.y), c1 = SM_C * __uint_as_float(s1.y);
        uint32_t am[4] = {(s0.x ^ 0x80008000u) & msk, (s1.x ^ 0x80008000u) & msk, 0, 0};
        reg_fence(am);
        WG_FENCE();
        wg_rs192t(acc, am[0], am[1], am[2], am[3], mkdesc(sb, desc_hi(1024, 0, 1)), 1);
        WG_COMMIT();
        WG_WAIT(0);
        reg_fence(acc);
#pragma unroll
        for (int i = 0; i < 24; i++) { acc[4 * i] *= c0; acc[4 * i + 1] *= c0; acc[4 * i + 2] *= c1; acc[4 * i + 3] *= c1; }
      } else { WG_WAIT(0); reg_fence(acc); }
      rel_b(pb8);
      rel_a(32);
      auto pack_q = [&](int from, int to) {
#pragma unroll
        for (int i = from; i < to; i++) { fr[i] = pack_bf16(acc[2 * i], acc[2 * i + 1]); asm volatile("" : "+r"(fr[i])::"memory"); }
      };
      pack_q(0, CVG);
      float sc[32], l0 = 0.f, l1 = 0.f;
      uint32_t pf[16], k8;
      auto pack_p = [&](const float (&s_)[32], int from = 0, int to = 16) {
#pragma unroll
        for (int i = from; i < to; i++) pf[i] = pack_bf16(s_[2 * i], s_[2 * i + 1]);
      };
      auto scores = [&](int j, int pass = 11) {
        k8 = b8 + 8;
        mbar_wait(bar_b + k8, phb);
        next_pair();
        mbar_wait(bar_b + b8, phb);
        const uint64_t dk = mkdesc(sb + OFF_B, HI_W) + k8 * (TB >> 7);
        asm volatile("bar.sync %0, 256;" ::"r"(1 + w) : "memory");
        WG_FENCE();
#pragma unroll
        for (int t = 0; t < 12; t++) {
          wg_rs64(sc, fr[4 * t], fr[4 * t + 1], fr[4 * t + 2], fr[4 * t + 3], dk + (t >> 2) * 64 + (t & 3) * 2, t != 0);
          if (t == 11) WG_COMMIT();
          if (t == pass) asm volatile("bar.arrive %0, 256;" ::"r"(2 - w) : "memory");
        }
      };
      auto pv = [&](int add) {
        const uint64_t dv = mkdesc(sb + OFF_B, HI_W) + b8 * (TB >> 7);
#pragma unroll
        for (int kk = 0; kk < 4; kk++) wg_rs192t(acc, pf[4 * kk], pf[4 * kk + 1], pf[4 * kk + 2], pf[4 * kk + 3], dv + kk * 384, kk != 0 || add);
        WG_COMMIT();
      };
      auto finish = [&]() {
        WG_WAIT(1);
        reg_fence(sc);
        exp_block(sc, l0, l1);
        rel_b(k8 + (__float_as_uint(l0) & __float_as_uint(l1) & zero));
        WG_WAIT(0);
        reg_fence(acc); reg_fence(pf);
        rel_b(b8);
        pack_p(sc);
      };
      {
        mbar_wait(bar_b + b8, phb);
        const uint64_t dk = mkdesc(sb + OFF_B, HI_W) + b8 * (TB >> 7);
        asm volatile("bar.sync %0, 256;" ::"r"(1 + w) : "memory");
#pragma unroll
        for (int t = 0; t < 12; t++) {
          if (t && (4 * t) % CVG == 0) pack_q(4 * t, 4 * t + CVG);
          if ((4 * t) % CVG == 0) WG_FENCE();
          wg_rs64(sc, fr[4 * t], fr[4 * t + 1], fr[4 * t + 2], fr[4 * t + 3], dk + (t >> 2) * 64 + (t & 3) * 2, t != 0);
          if (t == 7) asm volatile("bar.arrive %0, 256;" ::"r"(2 - w) : "memory");
        }
        WG_COMMIT();
        WG_WAIT(0);
        reg_fence(sc);
        float s0[32];
#pragma unroll
        for (int i = 0; i < 32; i++) s0[i] = i < NE ? sc[i] : __uint_as_float(__float_as_uint(sc[i]) ^ zero);
        exp_block(s0, l0, l1, 0, NE);
        pack_p(s0, 0, NE / 2);
#pragma unroll
        for (int i = NE; i < 32; i++) asm volatile("" : "+f"(s0[i])::"memory");
#pragma unroll
        for (int i = 0; i < NE / 2; i++) asm volatile("" : "+r"(pf[i])::"memory");
        rel_b(b8);
        scores(1, PS1);
        const uint32_t z = lds32(s_stat) & zero;
#pragma unroll
        for (int i = NE; i < 32; i++) {
          asm("{\n.reg .pred p;\nsetp.eq.u32 p, %1, 0;\n@p ex2.approx.ftz.f32 %0, %0;\n}\n" : "+f"(s0[i]) : "r"(z));
          if (i & 2) l1 += s0[i]; else l0 += s0[i];
        }
        pack_p(s0, NE / 2, 16);
        reg_fence(pf);
        WG_FENCE();
        pv(0);
        finish();
      }
#pragma unroll 1
      for (int j = NE < 32 ? 2 : 1; j < 8; j++) { scores(j); pv(j > 1); finish(); }
      const uint32_t v8 = b8 + 8;
      mbar_wait(bar_b + v8, phb);
      next_pair();
      {
        const uint64_t dv = mkdesc(sb + OFF_B, HI_W) + v8 * (TB >> 7);
        asm volatile("bar.sync %0, 256;" ::"r"(1 + w) : "memory");
        WG_FENCE();
#pragma unroll
        for (int kk = 0; kk < 4; kk++) {
          wg_rs192t(acc, pf[4 * kk], pf[4 * kk + 1], pf[4 * kk + 2], pf[4 * kk + 3], dv + kk * 384, 1);
          if (kk == 1 && (u < 3 || w == 0)) asm volatile("bar.arrive %0, 256;" ::"r"(2 - w) : "memory");
        }
        WG_COMMIT();
      }
      l0 = quad_sum(l0); l1 = quad_sum(l1);
      const bool unsafe = __any_sync(~0u, !(l0 >= SM_LO && l1 >= SM_LO && l0 + l1 <= SM_HI));
      l0 = rcp(l0); l1 = rcp(l1);
      rl[0] = pack_bf16(l0, l0); rl[1] = pack_bf16(l1, l1);
      l0 -= bf_lo(rl[0]); l1 -= bf_lo(rl[1]);
      rl[2] = pack_bf16(l0, l0); rl[3] = pack_bf16(l1, l1);
      WG_WAIT(0);
      reg_fence(acc);
      rel_b(v8);
      if (__builtin_expect(unsafe, 0)) {
        int o = hg * 4 + u; asm volatile("" : "+r"(o));
        o = (o * SKC + (SKC - WIN) + g) * (DH / 2) + q;
#pragma unroll
        for (int i = 0; i < 12; i++) optr[(i >> 1) * 512 + (i & 1) * 32] = make_uint4(fr[4 * i], fr[4 * i + 1], fr[4 * i + 2], fr[4 * i + 3]);
        safe_head((const uint32_t*)p.k + o, (const uint32_t*)p.v + o, optr);
#pragma unroll
        for (int i = 0; i < 12; i++) { const uint4 v = optr[(i >> 1) * 512 + (i & 1) * 32]; fr[4 * i] = v.x; fr[4 * i + 1] = v.y; fr[4 * i + 2] = v.z; fr[4 * i + 3] = v.w; }
        rl[0] = rl[1] = 0x3f803f80u; rl[2] = rl[3] = 0;
      } else {
#pragma unroll
        for (int i = 0; i < 24; i++) {
          fr[8 * (i >> 2) + (i & 3)] = pack_bf16(acc[4 * i], acc[4 * i + 1]);
          fr[8 * (i >> 2) + 4 + (i & 3)] = pack_bf16(acc[4 * i + 2], acc[4 * i + 3]);
        }
      }
    }

    float aF[80], aS[80];
    uint32_t pha = 0, a8 = 0, pa8 = 0, pb8 = 0;
#pragma unroll 1
    for (int s = 0; s < 19; s++) {
      const uint64_t d0 = mkdesc(sb, HI_O), dO = d0 + (a8 * (TA >> 7) + w * 256), dB = d0 + ((OFF_B >> 4) + b8 * (TB >> 7));
      mbar_wait(bar_a + a8, pha);
      mbar_wait(bar_b + b8, phb);
      WG_FENCE();
#pragma unroll
      for (int kk = 0; kk < 4; kk++) wg_ss160t(aF, dO + ((kk >> 1) * 512 + (kk & 1) * 2), dB + ((kk >> 1) * 640 + (kk & 1) * 64), kk != 0 || s != 0);
      WG_COMMIT();
      mbar_wait(bar_b + b8 + 8, phb);
      WG_WAIT(1);
      if (s > 0) { rel_a(pa8); rel_b(pb8 + 8); }
      WG_FENCE();
#pragma unroll
      for (int kk = 0; kk < 4; kk++) wg_ss160t(aS, dO + ((kk >> 1) * 512 + (kk & 1) * 2), dB + ((TB >> 4) + (kk >> 1) * 640 + (kk & 1) * 64), kk != 0 || s != 0);
      WG_COMMIT();
      if (s < 9) {
#pragma unroll
        for (int pp = 0; pp < 9; pp++) if (s == pp) store_o(pp);
        if (s == 8) { __syncwarp(); if (lane == 0) mbar_arrive(bar_o); }
      } else if (s < 15) {
        const int b = 2 * cw + ((lane >> 3) & 1);
        uint32_t ga = sb + OFF_B + TW + ((b * 11) >> 5) * (TB - 3840) + b * 1280 + (lane & 7) * 160 + (lane >> 4) * 16;
        if (s < 14) {
          mbar_wait(bar_x, 0);
          ga += 32 * (s - 9);
          ldsm4(ga, fr);
#pragma unroll
          for (int i = 0; i < 4; i++) {
            const uint2 st = lds64(s_stat + (cw * 16 + g + 8 * (i & 1)) * 8);
            const uint32_t d = hsub2(fr[i], st.x), xn = pack_bf16(bf_lo(d) * __uint_as_float(st.y), bf_hi(d) * __uint_as_float(st.y));
            fr[i] = pack_bf16(silu_f(bf_lo(xn)), silu_f(bf_hi(xn)));
          }
          stsm4(ga, fr);
        } else {
          mbar_wait(bar_u, 0);
          const uint2 sel = lds64(s_sel);
          const uint32_t row = qt * 128 + cw * 16 + (lane & 15);
          if (row == sel.x || row == sel.y) ga = s_sel + 16 + (row == sel.y ? 160 : 0) + (lane >> 4) * 16;
#pragma unroll
          for (int k = 0; k < 5; k++) ldsm4(ga + 32 * k, fr + 4 * k);
        }
      }
      WG_WAIT(1);
      rel_b(b8);
      pa8 = a8; a8 += 8; if (a8 == 40) { a8 = 0; pha ^= 1; }
      pb8 = b8; next_pair();
    }
    const int t128 = threadIdx.x & 127;
    uint4* const xbase = p.s->o + (size_t)(qt * 192 + nh * 24 + 10) * 512 + w * 640 + t128;
    uint4* const dst = xbase + kq * (48 * 512);
    float q1[40], q2[40], oth[40], own[40];
    auto take = [&](float (&x)[40], const float* a) {
#pragma unroll
      for (int k = 0; k < 40; k++) x[k] = __uint_as_float(__float_as_uint(a[k]) ^ zero);
      reg_fence(x);
    };
    reg_fence(aF);
    take(q1, aF);
    auto fa = [&](int i) { return mbar_try(bar_a + 8 * ((4 + i) % 5), i == 0); };
    auto fb = [&](int e) { return mbar_try(bar_b + 8 * (e % 6), (e / 6) & 1); };
    auto send = [&](int m) {
      const float* v = (m < 5 ? q1 : m < 10 ? q2 : oth) + 8 * (m % 5);
      st_pkt(dst + (m / 5) * 1280 + (m % 5) * 128, pack_bf16(v[0], v[1]) | 1, pack_bf16(v[2], v[3]), pack_bf16(v[4], v[5]), pack_bf16(v[6], v[7]));
    };
    static_for<20>([&](auto n_) {
      constexpr int n = n_.value, i = end_stage(n), e = 142 + n / 2, qi = n == 4 ? 1 : n == LQ ? 0 : n / 5;
      float (&acc_)[40] = qi == 0 ? q1 : qi == 1 ? q2 : qi == 2 ? oth : own;
      if (n == 0) while (!(fa(0) & fa(1) & fb(142) & fb(143))) {}
      if (n == 2) while (!(fa(2) & fa(3) & fb(144))) {}
      if (n == LQ) while (!(fa(4) & fb(145) & fb(146) & mbar_try(bar_z, 0))) {}
      if (n == 10) while (!(fb(147) & fb(148) & fb(149))) {}
      const uint64_t d0 = mkdesc(fresh(), HI_O);
      WG_FENCE();
#pragma unroll
      for (int kk = 0; kk < 4; kk++)
        wg_ss80t(acc_, d0 + w * 256 + (((4 + i) % 5) * (TA >> 4) + (kk >> 1) * 512 + (kk & 1) * 2),
                 d0 + ((OFF_B >> 4) + (e % 6) * (TB >> 4) + (n & 1) * 768 + (kk >> 1) * 384 + (kk & 1) * 64), 1);
      WG_COMMIT();
      if ((!(n & 1) && n <= 16) || n == 15 || n == LQ + 1) WG_WAIT(1);
      if (n == 0) rel_a(24);
      if (!(n & 1) && n <= 10) rel_b(8 * ((e - 1) % 6));
      if (n == Q2N) take(q2, aF + 40);
      if (n == 10) cluster_arrive();
      if (n == 12 || n == 14 || n == 16) rel_a(4u * n - 48);
      if (n == LQ + 1) reg_fence(q1);
      if (n == 10) reg_fence(q2);
      if (n == 15) reg_fence(oth);
      if (n == 15) while (!(fb(150) & fb(151))) {}
      static_for<sent(n + 1) - sent(n)>([&](auto k_) { send(sent(n) + k_.value); });
      if (n == 8) {
        reg_fence(aS);
#pragma unroll
        for (int k = 0; k < 40; k++) oth[k] = kq & 1 ? aS[k] : aS[40 + k];
        reg_fence(oth);
      }
      if (n == SWN) {
        reg_fence(aS);
#pragma unroll
        for (int k = 0; k < 40; k++) own[k] = kq & 1 ? aS[40 + k] : aS[k];
        reg_fence(own);
      }
    });
    uint32_t xr[20];
    const uint32_t xs = sb + OFF_B + 2 * TB + cw * 2560, xa = xs + (lane & 15) * 160 + (lane >> 4) * 16;
    mbar_wait(bar_b + 16, 1);
#pragma unroll
    for (int k = 0; k < 5; k++) ldsm4(xa + 32 * k, xr + 4 * k);
    {
      auto fetch = [&](int e, uint4 (&v)[5]) {
        mbar_wait(bar_e + 16 * e + 8 * w, 0);
#pragma unroll
        for (int i = 0; i < 5; i++) v[i] = lds128(sb + OFF_B + (3 + e) * TB + (w * 640 + i * 128 + t128) * 16);
      };
      auto add = [&](int e, uint4 (&v)[5]) {
        while (!(v[0].x & v[1].x & v[2].x & v[3].x & v[4].x & 1)) {
#pragma unroll
          for (int i = 0; i < 5; i++) v[i] = ld_pkt(xbase + (kq ^ ((0x132 >> (4 * e)) & 3)) * (48 * 512) + (e < 2 ? kq & 1 : 2) * 1280 + i * 128);
        }
#pragma unroll
        for (int i = 0; i < 5; i++) {
          float* o = own + 8 * i;
          o[0] += bf_lo(v[i].x); o[1] += bf_hi(v[i].x); o[2] += bf_lo(v[i].y); o[3] += bf_hi(v[i].y);
          o[4] += bf_lo(v[i].z); o[5] += bf_hi(v[i].z); o[6] += bf_lo(v[i].w); o[7] += bf_hi(v[i].w);
        }
      };
      WG_WAIT(0);
      reg_fence(own);
#pragma unroll 1
      for (int e = 0; e < 3; e++) { uint4 v[5]; fetch(e, v); add(e, v); }
      if (lane == 0) mbar_arrive(bar_w);
#pragma unroll
      for (int i = 0; i < 20; i++) xr[i] = hadd2(xr[i], hmul2(pack_bf16(own[2 * i], own[2 * i + 1]), fr[i]));
#pragma unroll
      for (int k = 0; k < 5; k++) stsm4(xa + 32 * k, xr + 4 * k);
      asm volatile("fence.proxy.async.shared::cta;" ::: "memory");
      __syncwarp();
      if (elect()) {
        tma2d_store(&m.out, xs, nh * 320 + kq * 80, qt * 128 + cw * 16);
        asm volatile("cp.async.bulk.commit_group;\ncp.async.bulk.wait_group.read 0;" ::: "memory");
      }
      __syncwarp();
    }
    cluster_wait();
  } else {
    asm volatile("setmaxnreg.dec.sync.aligned.u32 40;");
    uint32_t tid_; asm volatile("mov.u32 %0, %%tid.x;" : "=r"(tid_));
    const int warp = __shfl_sync(~0u, tid_ >> 5, 0);
    auto is_warp = [&](int k) { uint32_t e; asm volatile("{\n.reg .pred q;\nsetp.eq.u32 q, %1, %2;\nselp.u32 %0, 1, 0, q;\n}" : "=r"(e) : "r"(warp), "r"(k)); return e != 0; };
    if (warp > 0) {
      const unsigned epoch = (unsigned)(__ldcg(&p.s->done) >> 7);
      int budget = WAIT_BUDGET;
      const uint32_t tag = epoch + 1;
      mbar_wait(bar_a + EA, 0, budget);
      mbar_wait(bar_b + (kg0 & ~7), 0, budget); mbar_wait(bar_b + (kg0 & ~7) + 8, 0, budget);
      float cs0 = 0.f, cs1 = 0.f;
      const int n = rank * 96 + (warp - 1) * 32;
#pragma unroll 1
      for (int kg = kg0 + (lane >> 4) * 5, e = kg + 5; kg < e; kg++) {
        const uint32_t ad = sb + OFF_B + kg * 3072 + (n >> 6) * 1024 + (n & 63) * 2 + (lane & 15) * 4;
#pragma unroll
        for (int k = 0; k < 8; k++) { const uint32_t v = lds32(ad ^ (k * 0x90)); cs0 += bf_lo(v); cs1 += bf_hi(v); }
      }
      cs0 += __shfl_xor_sync(~0u, cs0, 16); cs1 += __shfl_xor_sync(~0u, cs1, 16);
      if (lane < 16) st_pkt8((uint2*)(p.s->cs + (hg * 4 + (qt >> 2)) * 96 + (n >> 1) + lane) + ((qt >> 1) & 1), (__float_as_uint(cs0) & ~3u) | (tag & 3), __float_as_uint(cs1));
      if (lane < 2) { uint32_t a; asm volatile("mapa.shared::cluster.u32 %0, %1, %2;" : "=r"(a) : "r"(bar_d), "r"(lane)); mbar_arrive_cluster(a); }
      mbar_wait(bar_a + EA, 1, budget);
      for (const uint32_t c0 = clock(); clock() - c0 < CSW;) {}
      uint4 v[5];
      while (true) {
        uint32_t bad = 0;
#pragma unroll
        for (int i = 0; i < 5; i++) v[i] = ld_pkt(i < 4 ? p.s->cs + (hg * 4 + i) * 96 + (tid_ - 32) : (const uint4*)p.s->stat + qt * 64 + (tid_ & 63));
#pragma unroll
        for (int i = 0; i < 5; i++) bad |= (v[i].x ^ tag) | (v[i].z ^ tag);
        if (!__any_sync(~0u, bad & 3) || --budget < 0) break;
      }
      asm volatile("st.shared.v4.u32 [%0], {%1,%2,%3,%4};" ::"r"(s_stat + (tid_ & 63) * 16), "r"(__byte_perm(v[4].x, 0, 0x3232)), "r"(v[4].y), "r"(__byte_perm(v[4].z, 0, 0x3232)), "r"(v[4].w) : "memory");
      cs0 = cs1 = 0.f;
#pragma unroll
      for (int i = 0; i < 4; i++) { cs0 += __uint_as_float(v[i].x & ~3u) + __uint_as_float(v[i].z & ~3u); cs1 += __uint_as_float(v[i].y) + __uint_as_float(v[i].w); }
#pragma unroll
      for (int k = 0; k < 8; k++) {
        const uint32_t t = k < 3 ? pack_bf16(cs0, cs1) : 0;
        sts32((sb + (warp - 1) * 1024 + lane * 4) ^ (k * 0x90), t);
        cs0 -= bf_lo(t); cs1 -= bf_hi(t);
      }
      asm volatile("fence.proxy.async.shared::cta;" ::: "memory");
      __syncwarp();
      if (lane < 2) mbar_arrive(bar_s);
      budget = errands(p.s, m, warp, tag, budget);
      if (is_warp(2)) {
        mbar_wait(bar_w, 0, budget);
        if (budget < 0) asm volatile("st.global.u32 [%0], %1;" ::"l"(0ull), "r"(budget) : "memory");
      }
    } else {
      uint32_t fb = bar_b + 16, dst = sb + OFF_B + 2 * TB, ph = 1;
      auto next = [&]() { fb += 8; dst += TB; if (fb == bar_b + 48) { fb = bar_b; dst = sb + OFF_B; ph ^= 1; } };
#pragma unroll 1
      for (int u = 0; u < 4; u++) {
        const int h = hg * 4 + u;
        int s = u ? (u == 2 ? 5 : 0) : (s0 + 2) % 10;
#pragma unroll 1
        for (int i = u ? 0 : 2; i < 10; i++) {
          if (u == 0) {
            const uint32_t a8 = 8 * (i < 5 ? i : i - 5);
            if (D0 && i >= D0) { const int j = i - D0; mbar_wait(bar_a + 8 * (j < 5 ? j : j - 5), j >= 5); }
            mbar_wait(bar_a + EA + a8, i < 5);
            if (elect()) { mbar_expect_tx(bar_a + a8, TA); tma2d(sb + a8 * (TA >> 3), &m.x, 64 * s, qt * 128, bar_a + a8); }
            if (i == 6 + (kg0 >> 3)) mbar_wait(bar_d, 0);
          }
          mbar_wait(fb + EB, ph);
          if (elect()) { mbar_expect_tx(fb, TB); tma4d_mc(dst + rank * (TB / 2), &m.wq, 3 * h, 8 * s + 4 * rank, fb); }
          next();
          if (++s == 10) s = 0;
        }
        const int kv0 = (h * SKC + (SKC - WIN)) / 8 + 4 * rank;
#pragma unroll 1
        for (int i = 0; i < 16; i++) {
          const bool isk = (0x2AAB >> i) & 1;
          mbar_wait(fb + EB, ph);
          if (elect()) { mbar_expect_tx(fb, TB); tma4d_mc(dst + rank * (TB / 2), isk ? &m.k : &m.v, 0, kv0 + 8 * (isk ? (i + 1) >> 1 : (i - 1) >> 1), fb); }
          next();
        }
      }
      const int cF = 10 * nh + 5 - 5 * (kq >> 1), cS = 10 * nh + 5 * (kq >> 1);
      const int kb = 4 * (k_block(lane, hg) + rank);
#pragma unroll 1
      for (int n = 0; n < 38; n++) {
        const int c2 = __shfl_sync(~0u, kb, n >> 1);
        mbar_wait(fb + EB, ph);
        if (elect()) { mbar_expect_tx(fb, TW); tma5d_mc(dst + rank * (TW / 2), &m.wo, c2, n & 1 ? cS : cF, fb); }
        next();
      }
      const int odd = (((0x7ff0 ^ 1 << LQ) ^ (kq & 1 ? 0xffc00 : 0)) >> lane) & 1;
      const int tq = __shfl_sync(~0u, kb, 19 + end_stage(lane)) << 16 | odd << 7 | ((lane < 10 ? cF : cS) + 2 * odd);
#pragma unroll 1
      for (int n = 0; n < 20; n += 2) {
        const int t0 = __shfl_sync(~0u, tq, n), t1 = __shfl_sync(~0u, tq, n + 1);
        mbar_wait(fb + EB, ph);
        if (elect()) {
          mbar_expect_tx(fb, TB);
          tma5d_mc(dst + rank * (TB / 4), (const CUtensorMap*)((const char*)m.w3 + (t0 & 128)), t0 >> 16, t0 & 31, fb);
          tma5d_mc(dst + TB / 2 + rank * (TB / 4), (const CUtensorMap*)((const char*)m.w3 + (t1 & 128)), t1 >> 16, t1 & 31, fb);
        }
        next();
      }
      mbar_wait(fb + EB, ph);
      if (elect()) { mbar_expect_tx(fb, TW); tma2d(dst, &m.xe, nh * 320 + kq * 80, qt * 128, fb); }
    }
    if (!is_warp(2)) {
      const int e = warp - (warp >> 1), ms = 2 * e + ((lane >> 2) & 1);
      const uint4* src = p.s->o + (size_t)(qt * 192 + nh * 24 + 10 + (kq ^ ((0x132 >> (4 * e)) & 3)) * 48) * 512 + (e < 2 ? kq & 1 : 2) * 1280 + (ms & 1) * 640;
      uint32_t todo = 0xff;
      bool ok = lane >= 8;
      mbar_wait(bar_z, 0);
#pragma unroll 1
      while (todo) {
        if (!ok) ok = ld_pkt(src + 4 * 128 + (lane & 3) * 32 + 31).x & 1;
        const uint32_t got = __ballot_sync(~0u, ok) & todo, go = __ballot_sync(~0u, ((got >> (lane & 28)) & 15) == 15);
        if (go) mbar_wait(bar_a + EA + 8 * e, 0);
        if ((go & 0x11) >> lane & 1) {
          mbar_expect_tx(bar_e + 8 * ms, TW / 2); bulk_load(sb + OFF_B + (3 + e) * TB + (ms & 1) * (TW / 2), src, TW / 2, bar_e + 8 * ms);
        }
        todo &= ~go;
      }
    }
    cluster_sync();
  }
}

typedef CUresult (*EncodeFn)(CUtensorMap*, CUtensorMapDataType, cuuint32_t, void*, const cuuint64_t*, const cuuint64_t*,
                             const cuuint32_t*, const cuuint32_t*, CUtensorMapInterleave, CUtensorMapSwizzle,
                             CUtensorMapL2promotion, CUtensorMapFloatOOBfill);

void encode(EncodeFn fn, CUtensorMap* tm, void* base, int rank, const cuuint64_t* dims, const cuuint64_t* strides,
            const cuuint32_t* box, CUtensorMapSwizzle sw) {
  const cuuint32_t es[5] = {1, 1, 1, 1, 1};
  fn(tm, CU_TENSOR_MAP_DATA_TYPE_BFLOAT16, rank, base, dims, strides, box, es, CU_TENSOR_MAP_INTERLEAVE_NONE, sw,
     CU_TENSOR_MAP_L2_PROMOTION_L2_128B, CU_TENSOR_MAP_FLOAT_OOB_FILL_NONE);
}

}

extern "C" void kernel_launch(void* const* d_in, const int* in_sizes, int n_in, void* d_out, int out_size) {
  static EncodeFn fn = nullptr;
  static Scratch* scr = nullptr;
  if (!fn) {
    void* f = nullptr;
    cudaDriverEntryPointQueryResult st;
    cudaGetDriverEntryPoint("cuTensorMapEncodeTiled", &f, cudaEnableDefault, &st);
    fn = (EncodeFn)f;
    cudaGetSymbolAddress((void**)&scr, g_scratch);
    cudaFuncSetAttribute(fused_kernel, cudaFuncAttributeMaxDynamicSharedMemorySize, SMEM_BYTES);
  }
  Maps m;
  { const cuuint64_t d[2] = {DM, SQ}, s[1] = {DM * 2}; const cuuint32_t b[2] = {64, 128};
    encode(fn, &m.x, d_in[0], 2, d, s, b, CU_TENSOR_MAP_SWIZZLE_128B);
    encode(fn, &m.xn, scr->xn, 2, d, s, b, CU_TENSOR_MAP_SWIZZLE_128B); }
  { const cuuint64_t d[4] = {64, 8, QD / 64, DM / 8}, s[3] = {QD * 2, 128, 8 * QD * 2}; const cuuint32_t b[4] = {64, 8, 3, 4};
    encode(fn, &m.wq, d_in[3], 4, d, s, b, CU_TENSOR_MAP_SWIZZLE_128B); }
  { const cuuint64_t d[4] = {64, 8, 3, NH * SKC / 8}, s[3] = {DH * 2, 128, 8 * DH * 2}; const cuuint32_t b[4] = {64, 8, 3, 4};
    encode(fn, &m.k, d_in[1], 4, d, s, b, CU_TENSOR_MAP_SWIZZLE_128B);
    encode(fn, &m.v, d_in[2], 4, d, s, b, CU_TENSOR_MAP_SWIZZLE_128B); }
  {
    const cuuint64_t d[5] = {32, 2, QD / 8, 4, DM / 32}, s[4] = {DM * 2, 8 * DM * 2, 2 * DM * 2, 64}; const cuuint32_t b[5] = {32, 2, 4, 4, 5};
    encode(fn, &m.wo, d_in[4], 5, d, s, b, CU_TENSOR_MAP_SWIZZLE_64B);
    const cuuint32_t b3[5] = {32, 2, 4, 4, 3};
    encode(fn, &m.w3[0], d_in[4], 5, d, s, b3, CU_TENSOR_MAP_SWIZZLE_64B);
    encode(fn, &m.w3[1], (char*)d_in[4] + 32, 5, d, s, b3, CU_TENSOR_MAP_SWIZZLE_64B); }
  { const cuuint64_t d[2] = {DM, SQ}, s[1] = {DM * 2}; const cuuint32_t bg[2] = {80, 24}, bx[2] = {80, 128}, bo[2] = {80, 16};
    encode(fn, &m.xg, d_in[0], 2, d, s, bg, CU_TENSOR_MAP_SWIZZLE_NONE);
    encode(fn, &m.xe, d_in[0], 2, d, s, bx, CU_TENSOR_MAP_SWIZZLE_NONE);
    encode(fn, &m.out, d_out, 2, d, s, bo, CU_TENSOR_MAP_SWIZZLE_NONE); }
  Params p;
  p.x = (const __nv_bfloat16*)d_in[0]; p.wr = (const __nv_bfloat16*)d_in[6]; p.wg = (const __nv_bfloat16*)d_in[7];
  p.wu = (const __nv_bfloat16*)d_in[8]; p.wd = (const __nv_bfloat16*)d_in[9];

  p.k = (const __nv_bfloat16*)d_in[1]; p.v = (const __nv_bfloat16*)d_in[2]; p.s = scr;
  cudaLaunchConfig_t cfg = {};
  cfg.gridDim = dim3(132); cfg.blockDim = dim3(384); cfg.dynamicSmemBytes = SMEM_BYTES; cfg.stream = cudaStreamPerThread;
  cudaLaunchKernelEx(&cfg, fused_kernel, p, m);
}
```

```cpp
#include <cuda_runtime.h>
#include <cuda_bf16.h>
#include <cuda.h>
#include <stdint.h>

namespace {

constexpr int SQ = 2048, DM = 640, NH = 32, DH = 192, SKC = 2048, WIN = 512, FF = 1536;
constexpr int QD = NH * DH;
constexpr uint32_t TA = 16384, TB = 24576, TW = 20480, OFF_B = 5 * TA, OFF_M = OFF_B + 6 * TB, SMEM_BYTES = OFF_M + 3072;
constexpr int WAIT_BUDGET = 1 << 20;

constexpr int FL_XN = 0;
constexpr int FL_O = 512;
constexpr int FL_RD = FL_O + 1024;
constexpr int FL_FFN = FL_RD + 1024;
constexpr int FL_SIDE = FL_FFN + 32;
struct __align__(1024) Scratch {
  unsigned long long done, pad0[15];
  unsigned flag[FL_SIDE + 32];
  uint4 cand[8];
  float ffn[4 * 2 * DM];
  int sel[4];
  __nv_bfloat16 gsel[2 * DM];
  uint4 cs[8 * 4 * DH / 2];
  uint2 stat[SQ];
  __align__(1024) __nv_bfloat16 xn[SQ * DM];
  __align__(1024) uint4 o[SQ * QD / 8];
};
__device__ Scratch g_scratch;

__device__ __forceinline__ uint32_t smem_u32(const void* p) { return (uint32_t)__cvta_generic_to_shared(p); }
__device__ __forceinline__ void mbar_init(uint32_t bar, int cnt) { asm volatile("mbarrier.init.shared::cta.b64 [%0], %1;" ::"r"(bar), "r"(cnt)); }
__device__ __forceinline__ void mbar_expect_tx(uint32_t bar, uint32_t bytes) {
  asm volatile("mbarrier.arrive.expect_tx.shared::cta.b64 _, [%0], %1;" ::"r"(bar), "r"(bytes) : "memory");
}
__device__ __forceinline__ void mbar_arrive(uint32_t bar) { asm volatile("mbarrier.arrive.shared::cta.b64 _, [%0];" ::"r"(bar) : "memory"); }
__device__ __forceinline__ void mbar_arrive_cluster(uint32_t addr) { asm volatile("mbarrier.arrive.shared::cluster.b64 _, [%0];" ::"r"(addr) : "memory"); }
__device__ __forceinline__ bool mbar_try(uint32_t bar, uint32_t parity) {
  uint32_t ok;
  asm volatile("{\n.reg .pred p;\nmbarrier.try_wait.parity.shared::cta.b64 p, [%1], %2;\nselp.u32 %0, 1, 0, p;\n}\n" : "=r"(ok) : "r"(bar), "r"(parity) : "memory");
  return ok;
}
__device__ __forceinline__ void mbar_wait(uint32_t bar, uint32_t parity, int& budget) {
#pragma unroll 1
  while (!mbar_try(bar, parity)) { if (--budget < 0) break; }
}
__device__ __forceinline__ void mbar_wait(uint32_t bar, uint32_t parity) {
#pragma unroll 1
  while (!mbar_try(bar, parity)) {}
}
__device__ __forceinline__ unsigned ld_acquire(const unsigned* p) { unsigned v; asm volatile("ld.acquire.gpu.global.u32 %0, [%1];" : "=r"(v) : "l"(p) : "memory"); return v; }
__device__ __forceinline__ void wait_flag(const unsigned* p, unsigned target) {
#pragma unroll 1
  while (__any_sync(~0u, (int)(ld_acquire(p) - target) < 0)) {}
}
__device__ __forceinline__ void red_release(unsigned* p) { asm volatile("red.release.gpu.global.add.u32 [%0], 1;" ::"l"(p) : "memory"); }
__device__ __forceinline__ void fence_proxy_async() { asm volatile("fence.proxy.async.global;" ::: "memory"); }
__device__ __forceinline__ bool elect() {
  uint32_t p;
  asm volatile("{\n.reg .pred P;\nelect.sync _|P, 0xffffffff;\nselp.u32 %0, 1, 0, P;\n}\n" : "=r"(p));
  return p;
}
__device__ __forceinline__ void cluster_arrive() { asm volatile("barrier.cluster.arrive.relaxed.aligned;" ::: "memory"); }
__device__ __forceinline__ void cluster_wait() { asm volatile("barrier.cluster.wait.aligned;" ::: "memory"); }
__device__ __forceinline__ void cluster_sync() { cluster_arrive(); cluster_wait(); }
__device__ __forceinline__ void tma2d(uint32_t dst, const CUtensorMap* tm, int c0, int c1, uint32_t bar) {
  asm volatile("cp.async.bulk.tensor.2d.shared::cluster.global.mbarrier::complete_tx::bytes [%0], [%1, {%3, %4}], [%2];"
               ::"r"(dst), "l"(tm), "r"(bar), "r"(c0), "r"(c1) : "memory");
}
constexpr uint64_t POL_FIRST = 0x12F0000000000000ull;
__device__ __forceinline__ void tma4d_mc(uint32_t dst, const CUtensorMap* tm, int c2, int c3, uint32_t bar) {
  asm volatile("cp.async.bulk.tensor.4d.shared::cluster.global.mbarrier::complete_tx::bytes.multicast::cluster.L2::cache_hint [%0], [%1, {%3, %3, %4, %5}], [%2], %6, %7;"
               ::"r"(dst), "l"(tm), "r"(bar), "r"(0), "r"(c2), "r"(c3), "h"((uint16_t)3), "l"(POL_FIRST) : "memory");
}
__device__ __forceinline__ void tma5d_mc(uint32_t dst, const CUtensorMap* tm, int c2, int c4, uint32_t bar) {
  asm volatile("cp.async.bulk.tensor.5d.shared::cluster.global.mbarrier::complete_tx::bytes.multicast::cluster.L2::cache_hint [%0], [%1, {%3, %3, %4, %3, %5}], [%2], %6, %7;"
               ::"r"(dst), "l"(tm), "r"(bar), "r"(0), "r"(c2), "r"(c4), "h"((uint16_t)3), "l"(POL_FIRST) : "memory");
}
__device__ __forceinline__ void bulk_load(uint32_t dst, const void* src, uint32_t bytes, uint32_t bar) {
  asm volatile("cp.async.bulk.shared::cluster.global.mbarrier::complete_tx::bytes.L2::cache_hint [%0], [%1], %2, [%3], %4;" ::"r"(dst), "l"(src), "r"(bytes), "r"(bar), "l"(POL_FIRST) : "memory");
}
__device__ __forceinline__ void tma2d_store(const CUtensorMap* tm, uint32_t src, int c0, int c1) {
  asm volatile("cp.async.bulk.tensor.2d.global.shared::cta.bulk_group [%0, {%2, %3}], [%1];" ::"l"(tm), "r"(src), "r"(c0), "r"(c1) : "memory");
}
__device__ __forceinline__ uint32_t lds32(uint32_t a) { uint32_t v; asm volatile("ld.shared.u32 %0, [%1];" : "=r"(v) : "r"(a) : "memory"); return v; }
__device__ __forceinline__ uint2 lds64(uint32_t a) { uint2 v; asm volatile("ld.shared.v2.u32 {%0,%1}, [%2];" : "=r"(v.x), "=r"(v.y) : "r"(a) : "memory"); return v; }
__device__ __forceinline__ uint4 lds128(uint32_t a) { uint4 v; asm volatile("ld.shared.v4.u32 {%0,%1,%2,%3}, [%4];" : "=r"(v.x), "=r"(v.y), "=r"(v.z), "=r"(v.w) : "r"(a) : "memory"); return v; }
__device__ __forceinline__ void ldsm4(uint32_t a, uint32_t* v) {
  asm volatile("ldmatrix.sync.aligned.m8n8.x4.shared.b16 {%0,%1,%2,%3}, [%4];" : "=r"(v[0]), "=r"(v[1]), "=r"(v[2]), "=r"(v[3]) : "r"(a) : "memory");
}
__device__ __forceinline__ void stsm4(uint32_t a, const uint32_t* v) {
  asm volatile("stmatrix.sync.aligned.m8n8.x4.shared.b16 [%0], {%1,%2,%3,%4};" ::"r"(a), "r"(v[0]), "r"(v[1]), "r"(v[2]), "r"(v[3]) : "memory");
}
__device__ __forceinline__ void sts32(uint32_t a, uint32_t v) { asm volatile("st.shared.u32 [%0], %1;" ::"r"(a), "r"(v) : "memory"); }
__device__ __forceinline__ void st_pkt(uint4* p, uint32_t a, uint32_t b, uint32_t c, uint32_t d) {
  asm volatile("st.relaxed.gpu.global.v4.b32 [%0], {%1, %2, %3, %4};" ::"l"(p), "r"(a), "r"(b), "r"(c), "r"(d) : "memory");
}
__device__ __forceinline__ void st_pkt8(void* p, uint32_t a, uint32_t b) {
  asm volatile("{\n.reg .b64 v;\nmov.b64 v, {%1, %2};\nst.relaxed.gpu.global.b64 [%0], v;\n}\n" ::"l"(p), "r"(a), "r"(b) : "memory");
}
__device__ __forceinline__ uint4 ld_pkt(const uint4* p) {
  uint4 v;
  asm volatile("{\n.reg .b128 v;\nld.relaxed.gpu.global.b128 v, [%4];\nmov.b128 {%0, %1, %2, %3}, v;\n}\n" : "=r"(v.x), "=r"(v.y), "=r"(v.z), "=r"(v.w) : "l"(p) : "memory");
  return v;
}
__device__ __forceinline__ uint4 ldg_nc(const void* p) {
  uint4 v;
  asm volatile("ld.global.nc.v4.u32 {%0,%1,%2,%3}, [%4];" : "=r"(v.x), "=r"(v.y), "=r"(v.z), "=r"(v.w) : "l"(p));
  return v;
}
#define WG_FENCE() asm volatile("wgmma.fence.sync.aligned;" ::: "memory")
#define WG_COMMIT() asm volatile("wgmma.commit_group.sync.aligned;" ::: "memory")
#define WG_WAIT(n) asm volatile("wgmma.wait_group.sync.aligned " #n ";" ::: "memory")
template <int N> __device__ __forceinline__ void reg_fence(float (&d)[N]) {
#pragma unroll
  for (int i = 0; i < N; i++) asm volatile("" : "+f"(d[i])::"memory");
}
template <int N> __device__ __forceinline__ void reg_fence(uint32_t (&d)[N]) {
#pragma unroll
  for (int i = 0; i < N; i++) asm volatile("" : "+r"(d[i])::"memory");
}
__device__ __forceinline__ constexpr uint64_t desc_hi(uint32_t lbo, uint32_t sbo, uint64_t sw) {
  return ((uint64_t)(lbo >> 4) << 16) | ((uint64_t)(sbo >> 4) << 32) | (sw << 62);
}
__device__ __forceinline__ uint64_t mkdesc(uint32_t addr, uint64_t hi) { return hi | (uint64_t)((addr & 0x3FFFF) >> 4); }
__device__ __forceinline__ uint32_t pack_bf16(float lo, float hi) { uint32_t r; asm("cvt.rn.bf16x2.f32 %0, %1, %2;" : "=r"(r) : "f"(hi), "f"(lo)); return r; }
__device__ __forceinline__ float bf_lo(uint32_t v) { return __uint_as_float(v << 16); }
__device__ __forceinline__ float bf_hi(uint32_t v) { return __uint_as_float(v & 0xffff0000u); }
__device__ __forceinline__ uint32_t hadd2(uint32_t a, uint32_t b) { uint32_t r; asm("add.rn.bf16x2 %0, %1, %2;" : "=r"(r) : "r"(a), "r"(b)); return r; }
__device__ __forceinline__ uint32_t hsub2(uint32_t a, uint32_t b) { uint32_t r; asm("sub.rn.bf16x2 %0, %1, %2;" : "=r"(r) : "r"(a), "r"(b)); return r; }
__device__ __forceinline__ uint32_t hmul2(uint32_t a, uint32_t b) { uint32_t r; asm("mul.rn.bf16x2 %0, %1, %2;" : "=r"(r) : "r"(a), "r"(b)); return r; }
__device__ __forceinline__ float rbf(float x) { return __bfloat162float(__float2bfloat16_rn(x)); }
__device__ __forceinline__ float ex2(float x) { float y; asm("ex2.approx.ftz.f32 %0, %1;" : "=f"(y) : "f"(x)); return y; }
__device__ __forceinline__ float rcp(float x) { float y; asm("rcp.approx.ftz.f32 %0, %1;" : "=f"(y) : "f"(x)); return y; }
__device__ __forceinline__ float sigmoid_f(float x) { return rcp(1.f + ex2(x * -1.4426950408889634f)); }
__device__ __forceinline__ float silu_f(float x) { return x * sigmoid_f(x); }

__device__ __forceinline__ void wg_ss192t(float (&d)[96], uint64_t da, uint64_t db, int sd) {
  asm volatile("{\n.reg .pred p;\nsetp.ne.b32 p, %98, 0;\n"
    "wgmma.mma_async.sync.aligned.m64n192k16.f32.bf16.bf16 {%0,%1,%2,%3,%4,%5,%6,%7,%8,%9,%10,%11,%12,%13,%14,%15,%16,%17,%18,%19,%20,%21,%22,%23,%24,%25,%26,%27,%28,%29,%30,%31,%32,%33,%34,%35,%36,%37,%38,%39,%40,%41,%42,%43,%44,%45,%46,%47,%48,%49,%50,%51,%52,%53,%54,%55,%56,%57,%58,%59,%60,%61,%62,%63,%64,%65,%66,%67,%68,%69,%70,%71,%72,%73,%74,%75,%76,%77,%78,%79,%80,%81,%82,%83,%84,%85,%86,%87,%88,%89,%90,%91,%92,%93,%94,%95}, %96, %97, p, 1, 1, 0, 1;\n}\n"
    : "+f"(d[0]),"+f"(d[1]),"+f"(d[2]),"+f"(d[3]),"+f"(d[4]),"+f"(d[5]),"+f"(d[6]),"+f"(d[7]),"+f"(d[8]),"+f"(d[9]),"+f"(d[10]),"+f"(d[11]),"+f"(d[12]),"+f"(d[13]),"+f"(d[14]),"+f"(d[15]),"+f"(d[16]),"+f"(d[17]),"+f"(d[18]),"+f"(d[19]),"+f"(d[20]),"+f"(d[21]),"+f"(d[22]),"+f"(d[23]),"+f"(d[24]),"+f"(d[25]),"+f"(d[26]),"+f"(d[27]),"+f"(d[28]),"+f"(d[29]),"+f"(d[30]),"+f"(d[31]),"+f"(d[32]),"+f"(d[33]),"+f"(d[34]),"+f"(d[35]),"+f"(d[36]),"+f"(d[37]),"+f"(d[38]),"+f"(d[39]),"+f"(d[40]),"+f"(d[41]),"+f"(d[42]),"+f"(d[43]),"+f"(d[44]),"+f"(d[45]),"+f"(d[46]),"+f"(d[47]),"+f"(d[48]),"+f"(d[49]),"+f"(d[50]),"+f"(d[51]),"+f"(d[52]),"+f"(d[53]),"+f"(d[54]),"+f"(d[55]),"+f"(d[56]),"+f"(d[57]),"+f"(d[58]),"+f"(d[59]),"+f"(d[60]),"+f"(d[61]),"+f"(d[62]),"+f"(d[63]),"+f"(d[64]),"+f"(d[65]),"+f"(d[66]),"+f"(d[67]),"+f"(d[68]),"+f"(d[69]),"+f"(d[70]),"+f"(d[71]),"+f"(d[72]),"+f"(d[73]),"+f"(d[74]),"+f"(d[75]),"+f"(d[76]),"+f"(d[77]),"+f"(d[78]),"+f"(d[79]),"+f"(d[80]),"+f"(d[81]),"+f"(d[82]),"+f"(d[83]),"+f"(d[84]),"+f"(d[85]),"+f"(d[86]),"+f"(d[87]),"+f"(d[88]),"+f"(d[89]),"+f"(d[90]),"+f"(d[91]),"+f"(d[92]),"+f"(d[93]),"+f"(d[94]),"+f"(d[95])
    : "l"(da), "l"(db), "r"(sd));
}
__device__ __forceinline__ void wg_rs64(float (&d)[32], uint32_t a0, uint32_t a1, uint32_t a2, uint32_t a3, uint64_t db, int sd) {
  asm volatile("{\n.reg .pred p;\nsetp.ne.b32 p, %37, 0;\n"
    "wgmma.mma_async.sync.aligned.m64n64k16.f32.bf16.bf16 {%0,%1,%2,%3,%4,%5,%6,%7,%8,%9,%10,%11,%12,%13,%14,%15,%16,%17,%18,%19,%20,%21,%22,%23,%24,%25,%26,%27,%28,%29,%30,%31}, {%32,%33,%34,%35}, %36, p, 1, 1, 0;\n}\n"
    : "+f"(d[0]),"+f"(d[1]),"+f"(d[2]),"+f"(d[3]),"+f"(d[4]),"+f"(d[5]),"+f"(d[6]),"+f"(d[7]),"+f"(d[8]),"+f"(d[9]),"+f"(d[10]),"+f"(d[11]),"+f"(d[12]),"+f"(d[13]),"+f"(d[14]),"+f"(d[15]),"+f"(d[16]),"+f"(d[17]),"+f"(d[18]),"+f"(d[19]),"+f"(d[20]),"+f"(d[21]),"+f"(d[22]),"+f"(d[23]),"+f"(d[24]),"+f"(d[25]),"+f"(d[26]),"+f"(d[27]),"+f"(d[28]),"+f"(d[29]),"+f"(d[30]),"+f"(d[31])
    : "r"(a0), "r"(a1), "r"(a2), "r"(a3), "l"(db), "r"(sd));
}
__device__ __forceinline__ void wg_rs192t(float (&d)[96], uint32_t a0, uint32_t a1, uint32_t a2, uint32_t a3, uint64_t db, int sd) {
  asm volatile("{\n.reg .pred p;\nsetp.ne.b32 p, %101, 0;\n"
    "wgmma.mma_async.sync.aligned.m64n192k16.f32.bf16.bf16 {%0,%1,%2,%3,%4,%5,%6,%7,%8,%9,%10,%11,%12,%13,%14,%15,%16,%17,%18,%19,%20,%21,%22,%23,%24,%25,%26,%27,%28,%29,%30,%31,%32,%33,%34,%35,%36,%37,%38,%39,%40,%41,%42,%43,%44,%45,%46,%47,%48,%49,%50,%51,%52,%53,%54,%55,%56,%57,%58,%59,%60,%61,%62,%63,%64,%65,%66,%67,%68,%69,%70,%71,%72,%73,%74,%75,%76,%77,%78,%79,%80,%81,%82,%83,%84,%85,%86,%87,%88,%89,%90,%91,%92,%93,%94,%95}, {%96,%97,%98,%99}, %100, p, 1, 1, 1;\n}\n"
    : "+f"(d[0]),"+f"(d[1]),"+f"(d[2]),"+f"(d[3]),"+f"(d[4]),"+f"(d[5]),"+f"(d[6]),"+f"(d[7]),"+f"(d[8]),"+f"(d[9]),"+f"(d[10]),"+f"(d[11]),"+f"(d[12]),"+f"(d[13]),"+f"(d[14]),"+f"(d[15]),"+f"(d[16]),"+f"(d[17]),"+f"(d[18]),"+f"(d[19]),"+f"(d[20]),"+f"(d[21]),"+f"(d[22]),"+f"(d[23]),"+f"(d[24]),"+f"(d[25]),"+f"(d[26]),"+f"(d[27]),"+f"(d[28]),"+f"(d[29]),"+f"(d[30]),"+f"(d[31]),"+f"(d[32]),"+f"(d[33]),"+f"(d[34]),"+f"(d[35]),"+f"(d[36]),"+f"(d[37]),"+f"(d[38]),"+f"(d[39]),"+f"(d[40]),"+f"(d[41]),"+f"(d[42]),"+f"(d[43]),"+f"(d[44]),"+f"(d[45]),"+f"(d[46]),"+f"(d[47]),"+f"(d[48]),"+f"(d[49]),"+f"(d[50]),"+f"(d[51]),"+f"(d[52]),"+f"(d[53]),"+f"(d[54]),"+f"(d[55]),"+f"(d[56]),"+f"(d[57]),"+f"(d[58]),"+f"(d[59]),"+f"(d[60]),"+f"(d[61]),"+f"(d[62]),"+f"(d[63]),"+f"(d[64]),"+f"(d[65]),"+f"(d[66]),"+f"(d[67]),"+f"(d[68]),"+f"(d[69]),"+f"(d[70]),"+f"(d[71]),"+f"(d[72]),"+f"(d[73]),"+f"(d[74]),"+f"(d[75]),"+f"(d[76]),"+f"(d[77]),"+f"(d[78]),"+f"(d[79]),"+f"(d[80]),"+f"(d[81]),"+f"(d[82]),"+f"(d[83]),"+f"(d[84]),"+f"(d[85]),"+f"(d[86]),"+f"(d[87]),"+f"(d[88]),"+f"(d[89]),"+f"(d[90]),"+f"(d[91]),"+f"(d[92]),"+f"(d[93]),"+f"(d[94]),"+f"(d[95])
    : "r"(a0), "r"(a1), "r"(a2), "r"(a3), "l"(db), "r"(sd));
}
__device__ __forceinline__ void wg_ss160t(float (&d)[80], uint64_t da, uint64_t db, int sd) {
  asm volatile("{\n.reg .pred p;\nsetp.ne.b32 p, %82, 0;\n"
    "wgmma.mma_async.sync.aligned.m64n160k16.f32.bf16.bf16 {%0,%1,%2,%3,%4,%5,%6,%7,%8,%9,%10,%11,%12,%13,%14,%15,%16,%17,%18,%19,%20,%21,%22,%23,%24,%25,%26,%27,%28,%29,%30,%31,%32,%33,%34,%35,%36,%37,%38,%39,%40,%41,%42,%43,%44,%45,%46,%47,%48,%49,%50,%51,%52,%53,%54,%55,%56,%57,%58,%59,%60,%61,%62,%63,%64,%65,%66,%67,%68,%69,%70,%71,%72,%73,%74,%75,%76,%77,%78,%79}, %80, %81, p, 1, 1, 0, 1;\n}\n"
    : "+f"(d[0]),"+f"(d[1]),"+f"(d[2]),"+f"(d[3]),"+f"(d[4]),"+f"(d[5]),"+f"(d[6]),"+f"(d[7]),"+f"(d[8]),"+f"(d[9]),"+f"(d[10]),"+f"(d[11]),"+f"(d[12]),"+f"(d[13]),"+f"(d[14]),"+f"(d[15]),"+f"(d[16]),"+f"(d[17]),"+f"(d[18]),"+f"(d[19]),"+f"(d[20]),"+f"(d[21]),"+f"(d[22]),"+f"(d[23]),"+f"(d[24]),"+f"(d[25]),"+f"(d[26]),"+f"(d[27]),"+f"(d[28]),"+f"(d[29]),"+f"(d[30]),"+f"(d[31]),"+f"(d[32]),"+f"(d[33]),"+f"(d[34]),"+f"(d[35]),"+f"(d[36]),"+f"(d[37]),"+f"(d[38]),"+f"(d[39]),"+f"(d[40]),"+f"(d[41]),"+f"(d[42]),"+f"(d[43]),"+f"(d[44]),"+f"(d[45]),"+f"(d[46]),"+f"(d[47]),"+f"(d[48]),"+f"(d[49]),"+f"(d[50]),"+f"(d[51]),"+f"(d[52]),"+f"(d[53]),"+f"(d[54]),"+f"(d[55]),"+f"(d[56]),"+f"(d[57]),"+f"(d[58]),"+f"(d[59]),"+f"(d[60]),"+f"(d[61]),"+f"(d[62]),"+f"(d[63]),"+f"(d[64]),"+f"(d[65]),"+f"(d[66]),"+f"(d[67]),"+f"(d[68]),"+f"(d[69]),"+f"(d[70]),"+f"(d[71]),"+f"(d[72]),"+f"(d[73]),"+f"(d[74]),"+f"(d[75]),"+f"(d[76]),"+f"(d[77]),"+f"(d[78]),"+f"(d[79])
    : "l"(da), "l"(db), "r"(sd));
}
__device__ __forceinline__ void wg_ss80t(float (&d)[40], uint64_t da, uint64_t db, int sd) {
  asm volatile("{\n.reg .pred p;\nsetp.ne.b32 p, %42, 0;\n"
    "wgmma.mma_async.sync.aligned.m64n80k16.f32.bf16.bf16 {%0,%1,%2,%3,%4,%5,%6,%7,%8,%9,%10,%11,%12,%13,%14,%15,%16,%17,%18,%19,%20,%21,%22,%23,%24,%25,%26,%27,%28,%29,%30,%31,%32,%33,%34,%35,%36,%37,%38,%39}, %40, %41, p, 1, 1, 0, 1;\n}\n"
    : "+f"(d[0]),"+f"(d[1]),"+f"(d[2]),"+f"(d[3]),"+f"(d[4]),"+f"(d[5]),"+f"(d[6]),"+f"(d[7]),"+f"(d[8]),"+f"(d[9]),"+f"(d[10]),"+f"(d[11]),"+f"(d[12]),"+f"(d[13]),"+f"(d[14]),"+f"(d[15]),"+f"(d[16]),"+f"(d[17]),"+f"(d[18]),"+f"(d[19]),"+f"(d[20]),"+f"(d[21]),"+f"(d[22]),"+f"(d[23]),"+f"(d[24]),"+f"(d[25]),"+f"(d[26]),"+f"(d[27]),"+f"(d[28]),"+f"(d[29]),"+f"(d[30]),"+f"(d[31]),"+f"(d[32]),"+f"(d[33]),"+f"(d[34]),"+f"(d[35]),"+f"(d[36]),"+f"(d[37]),"+f"(d[38]),"+f"(d[39])
    : "l"(da), "l"(db), "r"(sd));
}

struct Maps { CUtensorMap x, xn, wq, k, v, wo, w3[2], xg, xe, out; };
struct Params {
  const __nv_bfloat16 *x, *wr, *wg, *wu, *wd, *k, *v;
  Scratch* s;
};

__device__ __forceinline__ void side_cta(const Params& p, int sc, unsigned epoch, float* sm) {
  const int tid = threadIdx.x, lane = tid & 31, warp = tid >> 5;
  int budget = WAIT_BUDGET;
  float* s_x = sm;
  float* s_red = sm + 1280;
  float* s_h = s_red + 6144;
  uint4* s_c = (uint4*)(s_h + 768);
  uint2* s_st = (uint2*)(s_c + 16);
  constexpr int DEPTH = 7, STEP = 4 * 6144;
  const uint32_t ring = smem_u32(s_st + 512) + tid * 16;
  const int cg = tid % 96, ks = tid / 96, cd = tid % 80, kd = tid / 80;
  const __nv_bfloat16* wp = (cg < 48 ? p.wg : p.wu) + (size_t)(ks * 160) * FF + sc * 384 + (cg % 48) * 8;
  int kf = 0, pitch = FF;
  uint32_t slot = ring;
  auto refill = [&]() {
    if (kf == 40) { wp = p.wd + (size_t)(sc * 384 + kd * 96) * DM + cd * 8; pitch = DM; }
    if (kf < (tid < 320 ? 64 : 40)) {
#pragma unroll
      for (int j = 0; j < 4; j++) asm volatile("cp.async.cg.shared.global.L2::cache_hint [%0], [%1], 16, %2;" ::"r"(slot + j * 6144), "l"(wp + j * pitch), "l"(POL_FIRST) : "memory");
    }
    asm volatile("cp.async.commit_group;" ::: "memory");
    wp += 4 * pitch; kf++;
    slot += STEP; if (slot == ring + DEPTH * STEP) slot = ring;
  };
  auto gemv = [&](int n, const float* x0, const float* x1, float* out) {
    float a[2][8] = {};
#pragma unroll 1
    for (int k = 0; k < n; k += 4) {
      refill();
      asm volatile("cp.async.wait_group %0;" ::"n"(DEPTH - 1) : "memory");
      const float4 f0 = *(const float4*)(x0 + k), f1 = *(const float4*)(x1 + k);
      const float y0[4] = {f0.x, f0.y, f0.z, f0.w}, y1[4] = {f1.x, f1.y, f1.z, f1.w};
#pragma unroll
      for (int j = 0; j < 4; j++) {
        const uint4 v = lds128(slot + j * 6144);
        const uint32_t u[4] = {v.x, v.y, v.z, v.w};
#pragma unroll
        for (int i = 0; i < 4; i++) {
          a[0][2 * i] += y0[j] * bf_lo(u[i]); a[0][2 * i + 1] += y0[j] * bf_hi(u[i]);
          a[1][2 * i] += y1[j] * bf_lo(u[i]); a[1][2 * i + 1] += y1[j] * bf_hi(u[i]);
        }
      }
    }
#pragma unroll
    for (int i = 0; i < 16; i++) out[(i >> 3) * 768 + (i & 7)] = a[i >> 3][i & 7];
  };
  auto load_row = [&](const __nv_bfloat16* r, uint32_t (&v)[10]) {
    const uint4 a = __ldg((const uint4*)r + lane), b = __ldg((const uint4*)r + 32 + lane);
    const uint2 c = __ldg((const uint2*)r + 128 + lane);
    v[0] = a.x; v[1] = a.y; v[2] = a.z; v[3] = a.w; v[4] = b.x; v[5] = b.y; v[6] = b.z; v[7] = b.w; v[8] = c.x; v[9] = c.y;
  };
  uint32_t wr[10], xb[3][10];
  load_row(p.wr, wr);
  auto stat2 = [&](int pair) {
    uint4 v;
    do v = ld_pkt((const uint4*)p.s->stat + pair); while ((((v.x ^ (epoch + 1)) | (v.z ^ (epoch + 1))) & 0xffff) && --budget >= 0);
    return make_uint4(__byte_perm(v.x, 0, 0x3232), v.y, __byte_perm(v.z, 0, 0x3232), v.w);
  };
  if (tid < 256) ((uint4*)s_st)[tid] = stat2(sc * 256 + tid);
  __syncthreads();
#pragma unroll
  for (int b = 0; b < 3; b++) load_row(p.x + (size_t)(sc * 512 + warp + 12 * b) * DM, xb[b]);
#pragma unroll 1
  for (int k = 0; k < DEPTH - 1; k++) refill();
  float v0 = -INFINITY, v1 = -INFINITY; int i0 = 0xfff, i1 = 0xfff;
  auto better = [](float a, int ia, float b, int ib) { return a > b || (a == b && ia < ib); };
  auto push = [&](float v, int i) {
    if (better(v, i, v0, i0)) { v1 = v0; i1 = i0; v0 = v; i0 = i; }
    else if (better(v, i, v1, i1)) { v1 = v; i1 = i; }
  };
  auto push2 = [&](uint4 c) { push(__uint_as_float(c.x), c.y & 0xfff); push(__uint_as_float(c.z), c.w & 0xfff); };
#pragma unroll 1
  for (int l3 = warp; l3 < 512; l3 += 36) {
#pragma unroll
    for (int b = 0; b < 3; b++) {
      const int lr = l3 + 12 * b;
      if (lr >= 512) break;
      const uint2 st = s_st[lr];
      uint32_t v[10];
#pragma unroll
      for (int i = 0; i < 10; i++) v[i] = hsub2(xb[b][i], st.x);
      if (lr + 36 < 512) load_row(p.x + (size_t)(sc * 512 + lr + 36) * DM, xb[b]);
      float r0 = 0.f, r1 = 0.f;
#pragma unroll
      for (int i = 0; i < 10; i++) {
        const uint32_t xn = pack_bf16(bf_lo(v[i]) * __uint_as_float(st.y), bf_hi(v[i]) * __uint_as_float(st.y));
        r0 = fmaf(bf_lo(xn), bf_lo(wr[i]), r0); r1 = fmaf(bf_hi(xn), bf_hi(wr[i]), r1);
      }
      r0 += r1;
#pragma unroll
      for (int o = 16; o > 0; o >>= 1) r0 += __shfl_xor_sync(~0u, r0, o);
      push(rbf(r0), sc * 512 + lr);
    }
  }
  if (lane == 0) s_c[warp] = make_uint4(__float_as_uint(v0), i0, __float_as_uint(v1), i1);
  __syncthreads();
#pragma unroll 1
  for (int w = 1; w < 12; w++) push2(s_c[(warp + w) % 12]);
  const uint32_t tag = (epoch + 1) << 12;
  if (tid == 0) st_pkt(p.s->cand + sc, __float_as_uint(v0), i0 | tag, __float_as_uint(v1), i1);
  {
    uint4 c;
    do c = ld_pkt(p.s->cand + (lane & 3)); while (((c.y ^ tag) >> 12) && --budget >= 0);
#pragma unroll 1
    for (int w = 1; w < 4; w++) { const int o = (sc + w) & 3; push2(make_uint4(__shfl_sync(~0u, c.x, o), __shfl_sync(~0u, c.y, o), __shfl_sync(~0u, c.z, o), __shfl_sync(~0u, c.w, o))); }
  }
  if (i0 >= SQ) i0 = 0;
  if (i1 >= SQ) i1 = (i0 == 0) ? 1 : 0;
  if (tid < 320) {
    const int row = tid < 160 ? i0 : i1;
    const uint2 u = __ldg((const uint2*)(p.x + (size_t)row * DM) + tid % 160);
    const uint4 st = stat2(row >> 1);
    const uint32_t mean2 = row & 1 ? st.z : st.x, d0 = hsub2(u.x, mean2), d1 = hsub2(u.y, mean2);
    const float inv = __uint_as_float(row & 1 ? st.w : st.y);
    ((float4*)s_x)[tid] = make_float4(rbf(bf_lo(d0) * inv), rbf(bf_hi(d0) * inv), rbf(bf_lo(d1) * inv), rbf(bf_hi(d1) * inv));
  }
  __syncthreads();
  gemv(160, s_x + ks * 160, s_x + DM + ks * 160, s_red + ks * 1536 + cg * 8);
  __syncthreads();
#pragma unroll
  for (int t = 0; t < 2; t++) {
    float g = 0.f, u = 0.f;
#pragma unroll
    for (int k = 0; k < 4; k++) { g += s_red[(k * 2 + t) * 768 + tid]; u += s_red[(k * 2 + t) * 768 + 384 + tid]; }
    s_h[t * 384 + tid] = rbf(rbf(silu_f(rbf(g))) * rbf(u));
  }
  __syncthreads();
  if (tid < 320) gemv(96, s_h + kd * 96, s_h + 384 + kd * 96, s_red + kd * 1536 + cd * 8);
  __syncthreads();
  const int o4 = tid + (tid < 160 ? 0 : 32);
  if (tid < 320) {
    const float4 *r = (const float4*)s_red + o4, a = r[0], b = r[384], c = r[768], d = r[1152];
    ((float4*)p.s->ffn)[sc * 320 + tid] = make_float4(a.x + b.x + c.x + d.x, a.y + b.y + c.y + d.y, a.z + b.z + c.z + d.z, a.w + b.w + c.w + d.w);
  }
  __syncthreads();
  if (tid == 0) { __threadfence(); s_c[0].x = (atomicAdd(&p.s->flag[FL_SIDE], 1u) & 3u) == 3u; __threadfence(); }
  __syncthreads();
  if (s_c[0].x) {
    if (tid < 320) {
      const float4 *r = (const float4*)p.s->ffn + tid, a = __ldcg(r), b = __ldcg(r + 320), c = __ldcg(r + 640), d = __ldcg(r + 960), x = ((float4*)s_x)[tid];
      const float rs = rbf(sigmoid_f(tid < 160 ? v0 : v1));
      auto gate = [&](float xn, float y) { return silu_f(rbf(xn + rbf(rbf(y) * rs))); };
      if (tid == 0) { p.s->sel[0] = i0; p.s->sel[1] = i1; }
      ((uint2*)p.s->gsel)[tid] =
          make_uint2(pack_bf16(gate(x.x, a.x + b.x + c.x + d.x), gate(x.y, a.y + b.y + c.y + d.y)), pack_bf16(gate(x.z, a.z + b.z + c.z + d.z), gate(x.w, a.w + b.w + c.w + d.w)));
    }
    __syncthreads();
    if (tid == 0) red_release(&p.s->flag[FL_FFN]);
  }
}

constexpr float SM_C = 0.07216878364870322f * 1.4426950408889634f;

#define LD 0
#define LS 3
__device__ __forceinline__ void ln_piece(const Params& p, uint32_t (&r)[48], int k, int row, int l16) {
  auto f = [&](int i) { return __uint_as_float(r[i]); };
  if (k == LD) {
#pragma unroll
    for (int i = 0; i < 5; i++) {
      const uint4 v = ldg_nc((const uint4*)(p.x + (size_t)row * DM) + i * 16 + l16);
      r[4 * i] = v.x; r[4 * i + 1] = v.y; r[4 * i + 2] = v.z; r[4 * i + 3] = v.w;
    }
    asm volatile("ld.relaxed.gpu.global.v2.u32 {%0,%1}, [%2];" : "=r"(r[20]), "=r"(r[21]) : "l"(&p.s->done));
  } else if (k == LS || k == LS + 1) {
    if (k == LS) { r[22] = __shfl_sync(~0u, r[0], 0, 16) << 16; r[23] = r[24] = 0; }
    float s0 = f(23), s1 = 0.f, q0 = f(24), q1 = 0.f;
#pragma unroll
    for (int i = 10 * (k - LS); i < 10 * (k - LS) + 10; i++) {
      const float a = bf_lo(r[i]) - f(22), b = bf_hi(r[i]) - f(22);
      s0 += a; s1 += b; q0 = fmaf(a, a, q0); q1 = fmaf(b, b, q1);
    }
    r[23] = __float_as_uint(s0 + s1); r[24] = __float_as_uint(q0 + q1);
  } else if (k == LS + 2) {
    float s0 = f(23), q0 = f(24);
#pragma unroll
    for (int o = 8; o > 0; o >>= 1) { s0 += __shfl_xor_sync(~0u, s0, o); q0 += __shfl_xor_sync(~0u, q0, o); }
    s0 *= 1.f / DM;
    const float mean = f(22) + s0, var = rbf(fmaxf(fmaf(q0, 1.f / DM, -s0 * s0), 0.f));
    float sd; asm("sqrt.approx.ftz.f32 %0, %1;" : "=f"(sd) : "f"(rbf(var + 1e-5f)));
    const float inv = rcp(rbf(sd));
    r[22] = pack_bf16(mean, mean); r[23] = __float_as_uint(inv * SM_C);
    const uint32_t tag = __funnelshift_r(r[20], r[21], 7) + 1;
    if (l16 == 0) st_pkt8(&p.s->stat[row], __byte_perm(tag, r[22], 0x7610), __float_as_uint(inv));
  } else if (k > LS + 2 && k <= LS + 5) {
#pragma unroll
    for (int j = 2 * (k - LS - 3); j < 2 * (k - LS - 3) + 2 && j < 5; j++) {
#pragma unroll
      for (int i = 4 * j; i < 4 * j + 4; i++) { const uint32_t d = hsub2(r[i], r[22]); r[i] = pack_bf16(bf_lo(d) * f(23), bf_hi(d) * f(23)); }
      *((uint4*)(p.s->xn + (size_t)row * DM) + j * 16 + l16) = make_uint4(r[4 * j], r[4 * j + 1], r[4 * j + 2], r[4 * j + 3]);
    }
  }
}

constexpr float SM_HI = 0x1p64f, SM_LO = 0x1p-64f;
__device__ __forceinline__ void exp_block(float (&s)[32], float& l0, float& l1, int from = 0, int to = 32) {
#pragma unroll
  for (int i = from; i < to; i++) { s[i] = ex2(s[i]); if (i & 2) l1 += s[i]; else l0 += s[i]; }
}
__device__ __forceinline__ float quad_sum(float v) { v += __shfl_xor_sync(~0u, v, 1); return v + __shfl_xor_sync(~0u, v, 2); }
__device__ __forceinline__ float quad_max(float v) { v = fmaxf(v, __shfl_xor_sync(~0u, v, 1)); return fmaxf(v, __shfl_xor_sync(~0u, v, 2)); }
__device__ __noinline__ void safe_head(const uint32_t* kp, const uint32_t* vp, uint4* io) {
  uint32_t fq[48];
#pragma unroll
  for (int i = 0; i < 12; i++) { const uint4 v = io[(i >> 1) * 512 + (i & 1) * 32]; fq[4 * i] = v.x; fq[4 * i + 1] = v.y; fq[4 * i + 2] = v.z; fq[4 * i + 3] = v.w; }
  float m0 = -INFINITY, m1 = -INFINITY;
#pragma unroll 1
  for (int pass = 0; pass < 3; pass++) {
    float o[48] = {}, l0 = 0.f, l1 = 0.f;
#pragma unroll 1
    for (int n = 0; n < 64; n++) {
      const uint32_t *kr = kp + n * (8 * DH / 2), *vr = vp + n * (8 * DH / 2) + (pass - 1) * 48;
      float d[4] = {};
#pragma unroll
      for (int t = 0; t < 12; t++)
        asm volatile("mma.sync.aligned.m16n8k16.row.col.f32.bf16.bf16.f32 {%0,%1,%2,%3}, {%4,%5,%6,%7}, {%8,%9}, {%0,%1,%2,%3};"
                     : "+f"(d[0]), "+f"(d[1]), "+f"(d[2]), "+f"(d[3])
                     : "r"(fq[4 * t]), "r"(fq[4 * t + 1]), "r"(fq[4 * t + 2]), "r"(fq[4 * t + 3]), "r"(__ldg(kr + 8 * t)), "r"(__ldg(kr + 8 * t + 4)));
      if (pass == 0) { m0 = fmaxf(m0, fmaxf(d[0], d[1])); m1 = fmaxf(m1, fmaxf(d[2], d[3])); continue; }
      d[0] = ex2(d[0] - m0); d[1] = ex2(d[1] - m0); d[2] = ex2(d[2] - m1); d[3] = ex2(d[3] - m1);
      l0 += d[0] + d[1]; l1 += d[2] + d[3];
      const uint32_t p0 = pack_bf16(d[0], d[1]), p1 = pack_bf16(d[2], d[3]);
#pragma unroll
      for (int c = 0; c < 12; c++)
        asm volatile("{\n.reg .b32 t;\nmovmatrix.sync.aligned.m8n8.trans.b16 t, %6;\n"
                     "mma.sync.aligned.m16n8k8.row.col.f32.bf16.bf16.f32 {%0,%1,%2,%3}, {%4,%5}, {t}, {%0,%1,%2,%3};\n}\n"
                     : "+f"(o[4 * c]), "+f"(o[4 * c + 1]), "+f"(o[4 * c + 2]), "+f"(o[4 * c + 3]) : "r"(p0), "r"(p1), "r"(__ldg(vr + 4 * c)));
    }
    if (pass == 0) { m0 = quad_max(m0); m1 = quad_max(m1); continue; }
    l0 = rcp(quad_sum(l0)); l1 = rcp(quad_sum(l1));
#pragma unroll
    for (int i = 0; i < 6; i++) {
      const float* v = o + 16 * (i >> 1) + 2 * (i & 1);
      const float r = i & 1 ? l1 : l0;
      io[(3 * (pass - 1) + (i >> 1)) * 512 + (i & 1) * 32] =
          make_uint4(pack_bf16(v[0] * r, v[1] * r), pack_bf16(v[4] * r, v[5] * r), pack_bf16(v[8] * r, v[9] * r), pack_bf16(v[12] * r, v[13] * r));
    }
  }
}

#define CVG 48
#define NE 8
#define PS1 8
#define CSW 0
#define D0 2
#define ROT 2
#define LQ 6
__device__ __forceinline__ constexpr int end_stage(int n) { return n < 4 ? n : n < LQ ? n - 4 : n == LQ ? 4 : n % 5; }
#define Q2N 1
#define SWN 12
#define SCH 0
__device__ __forceinline__ constexpr int sent(int n) {
  constexpr int t[4][15] = {{0, 2, 4, 5, 5, 6, 7, 8,  9, 10, 11, 12, 13, 14, 15},
                            {0, 2, 4, 5, 5, 6, 7, 8,  9, 10, 12, 13, 14, 15, 15},
                            {0, 2, 4, 5, 5, 7, 8, 9, 10, 10, 12, 14, 15, 15, 15},
                            {0, 2, 4, 5, 5, 7, 8, 9, 10, 10, 13, 15, 15, 15, 15}};
  return n < LQ + 2 ? 0 : LQ == 6 && n == 8 ? 3 : t[SCH][n - 6];
}
template <int N> struct IntC { static constexpr int value = N; };
template <int N, int I = 0, class F> __device__ __forceinline__ void static_for(F&& f) { if constexpr (I < N) { f(IntC<I>{}); static_for<N, I + 1>(f); } }

extern __shared__ __align__(1024) uint8_t smem_raw[];
constexpr uint32_t EA = 160, EB = 184;
#define SMEM_LAYOUT                                                                                                          \
  [[maybe_unused]] const uint32_t sb = smem_u32(smem_raw), bar_a = sb + OFF_M, bar_b = bar_a + 40, bar_x = bar_a + 88,      \
      bar_u = bar_a + 96, bar_e = bar_a + 104, bar_o = bar_a + 200, bar_w = bar_a + 208, bar_z = bar_a + 288,                \
      bar_s = bar_a + 296, bar_d = bar_a + 304, s_stat = bar_a + 512, s_sel = s_stat + 1024;

__device__ __forceinline__ int cluster_role() {
  uint32_t t, n;
  asm("mov.u32 %0, %%smid;" : "=r"(t)); asm("mov.u32 %0, %%nsmid;" : "=r"(n));
  t >>= 1;
  return n != 132 ? blockIdx.x >> 1 : t < 32 ? t : t < 60 ? t + 1 + (((t - 32) * 37) >> 8) : t < 62 ? t + 4 : (t - 58) * 8;
}

__device__ __forceinline__ int k_block(int t, int hg) {
  const int i = (t * 11) >> 5;
  return ((i < 6 ? (hg & 6) + (i & 1) : hg ^ (i & 1)) * 4 + (i >> 1)) * 6 + (t == 3 * i ? 4 : 2 * (t - 3 * i) - 2);
}

__device__ __noinline__ int errands(Scratch* s, const Maps& m, int qt, int hg, int warp, uint32_t tag, int budget) {
  SMEM_LAYOUT
  const int lane = threadIdx.x & 31, kq = hg >> 1, nh = hg & 1;
  if (warp == 1) {
#pragma unroll 1
    for (int u = 0; u < 5; u++) {
      mbar_wait(bar_o, u & 1);
      if (lane == 0) red_release(&s->flag[u ? FL_O + (qt * 8 + hg) * 8 : FL_XN + qt * 32]);
      __syncwarp();
    }
  } else if (warp == 2) {
    mbar_wait(bar_x, 0, budget);
    while ((int)(ld_acquire(&s->flag[FL_FFN]) - tag) < 0 && --budget >= 0) {}
    if (lane < 21) {
      const uint4 v = __ldcg(lane ? (const uint4*)(s->gsel + (lane > 10 ? DM - 80 : 0) + nh * 320 + kq * 80) + lane - 1 : (const uint4*)s->sel);
      asm volatile("st.shared.v4.u32 [%0], {%1,%2,%3,%4};" ::"r"(s_sel + 16 * lane), "r"(v.x), "r"(v.y), "r"(v.z), "r"(v.w) : "memory");
    }
    __syncwarp();
    if (lane == 0) { mbar_arrive(bar_u); asm volatile("red.relaxed.gpu.global.add.u64 [%0], 1;" ::"l"(&s->done) : "memory"); }
    while ((int)(ld_acquire(&s->flag[FL_RD + (qt * 8 + (hg ^ 1)) * 8]) - tag) < 0 && --budget >= 0) {}
    if (lane < 3) mbar_arrive(bar_z);
  } else {
    wait_flag(&s->flag[FL_XN + qt * 32], tag * 8);
    fence_proxy_async();
    mbar_wait(bar_a + EA + 32, 1);
    uint32_t a8 = 0, pha = 1;
    const int kb = (qt * 192 + k_block(lane, hg)) * 512;
#pragma unroll 1
    for (int n = 0; n < 54; n++) {
      const int t = n - 30, ko = __shfl_sync(~0u, kb, t);
      if (t == 0 || t == 18) {
        wait_flag(&s->flag[FL_O + (qt * 8 + (t ? 2 * kq + (lane & 1) : lane & 7)) * 8], tag * 4 - (t ? 0 : 1));
        fence_proxy_async();
      }
      mbar_wait(bar_a + EA + a8, pha);
      const uint32_t fb = bar_a + a8, dst = sb + a8 * (TA >> 3);
      if (elect()) {
        if (t >= 0) {
          mbar_expect_tx(fb, TA);
          bulk_load(dst, s->o + ko, TA, fb);
          if (t == 8) {
            mbar_expect_tx(bar_x, 6 * 3840);
#pragma unroll 1
            for (int e = 0; e < 6; e++) tma2d(sb + OFF_B + TW + e * TB, &m.xg, nh * 320 + kq * 80, qt * 128 + e * 24, bar_x);
            asm volatile("prefetch.tensormap [%0];\nprefetch.tensormap [%1];\nprefetch.tensormap [%2];\nprefetch.tensormap [%3];"
                         ::"l"(m.w3), "l"(m.w3 + 1), "l"(&m.xe), "l"(&m.out) : "memory");
          }
          if (t == 22) asm volatile("red.relaxed.gpu.global.add.u32 [%0], 1;" ::"l"(&s->flag[FL_RD + (qt * 8 + hg) * 8]) : "memory");
        } else if (n >= 10 && pha) mbar_arrive(fb);
        else { mbar_expect_tx(fb, TA); tma2d(dst, &m.xn, 8 * a8 + (pha || (n >= 15 && n < 20) ? 0 : 320), qt * 128, fb); }
      }
      a8 += 8; if (a8 == 40) { a8 = 0; pha ^= 1; }
    }
    if (lane < 3) mbar_arrive(bar_z);
  }
  return budget;
}

__global__ void __launch_bounds__(384, 1) __cluster_dims__(2, 1, 1)
fused_kernel(const Params p, const __grid_constant__ Maps m) {
  SMEM_LAYOUT
  const int wi = __shfl_sync(~0u, threadIdx.x >> 5, 0), wg = wi >> 2;
  const int lane = threadIdx.x & 31;
  const int cl = cluster_role();
  const int rank = blockIdx.x & 1;

  if (cl >= 64) {
    const unsigned epoch = (unsigned)(__ldcg(&p.s->done) >> 7);
    side_cta(p, 2 * cl + rank - 128, epoch, (float*)smem_raw);
    return;
  }
  const int qt = (cl & 7) * 2 + rank, hg = cl >> 3;
  const int kq = hg >> 1, nh = hg & 1;

  const int s0 = (5 * ((qt >> 1) & ~(8 / ROT - 1))) >> 2, kg0 = 10 * (qt >> 1) - 8 * s0;
  if (elect()) {
    const int c = (int)(0x5ff7700000ull >> (4 * wi) & 15) + 1;
    for (int i = 0; i < 4; i++) mbar_init(bar_a + 32 * wi + 8 * i, c);
    asm volatile("fence.mbarrier_init.release.cluster;" ::: "memory");
  }
  __syncwarp();
  cluster_arrive();
  if (wi < 2 && elect()) {
    if (wi) { asm volatile("prefetch.tensormap [%0];" ::"l"(&m.wq) : "memory"); mbar_expect_tx(bar_b, TB); mbar_expect_tx(bar_b + 8, TB); }
    else for (int i = 0; i < 2; i++) { mbar_expect_tx(bar_a + 8 * i, TA); tma2d(sb + i * TA, &m.x, 64 * (s0 + i), qt * 128, bar_a + 8 * i); }
  }
  __syncwarp();
  cluster_wait();
  if (wi == 1 && elect())
    for (int i = 0; i < 2; i++) tma4d_mc(sb + OFF_B + i * TB + rank * (TB / 2), &m.wq, 12 * hg, 8 * (s0 + i) + 4 * rank, bar_b + 8 * i);
  if (wg > 0) {
    const int w = wg - 1;
    const int cw = wi - 4;
    asm volatile("setmaxnreg.inc.sync.aligned.u32 232;");
    uint32_t fr[48];
    reg_fence(fr);
    auto ln_row = [&]() { int v = qt * 128 + hg * 16 + cw * 2 + (lane >> 4); asm volatile("" : "+r"(v)); return v; };
    uint32_t rel_addr;
    asm volatile("mapa.shared::cluster.u32 %0, %1, %2;" : "=r"(rel_addr) : "r"(bar_b + EB), "r"(lane & 1));
    auto rel_a = [&](uint32_t o8) { if (lane == 0) mbar_arrive(bar_a + EA + o8); };
    auto rel_b = [&](uint32_t o8) { if (lane < 2) mbar_arrive_cluster(rel_addr + o8); };
    uint32_t b8 = 0, phb = 0;
    auto next_pair = [&]() { b8 += 16; if (b8 == 48) { b8 = 0; phb ^= 1; } };
    const int g = lane >> 2, q = lane & 3;
    constexpr uint64_t HI_A = desc_hi(16, 1024, 1);
    constexpr uint64_t HI_W = desc_hi(1024, 3072, 1);
    constexpr uint64_t HI_O = desc_hi(2048, 512, 2);
    if (w == 1) asm volatile("bar.arrive 1, 256;" ::: "memory");

    uint32_t zero; asm volatile("mov.u32 %0, %%tid.y;" : "=r"(zero));
    float acc[96];
    uint4* optr = p.s->o + (size_t)(qt * 192 + hg * 24) * 512 + (cw * 16 + g) * 4 + (q ^ ((g >> 1) & 3));
    uint32_t rl[4];
    auto store_o = [&](int pp) {
#pragma unroll
      for (int i = (12 * pp + 8) / 9; i < (12 * (pp + 1) + 8) / 9; i++) {
#pragma unroll
        for (int k = 4 * i; k < 4 * i + 4; k++)
          asm volatile("{\n.reg .b32 t;\nmul.rn.bf16x2 t, %0, %2;\nfma.rn.bf16x2 %0, %0, %1, t;\n}\n" : "+r"(fr[k]) : "r"(rl[i & 1]), "r"(rl[2 + (i & 1)]));
        fr[4 * i] &= ~1u;
        optr[(i >> 1) * 512 + (i & 1) * 32] = make_uint4(fr[4 * i], fr[4 * i + 1], fr[4 * i + 2], fr[4 * i + 3]);
      }
      if (pp == 8) optr += 6 * 512;
    };
    auto fresh = [&]() { uint32_t v = sb; asm volatile("" : "+r"(v)); return v; };
    reg_fence(rl);

#pragma unroll 1
    for (int u = 0; u < 4; u++) {
      const uint32_t sq = fresh();
      const uint64_t dA = mkdesc(sq + w * 8192, HI_A), dB0 = mkdesc(sq + OFF_B, HI_W);
      uint32_t pb8 = 0;
#pragma unroll
      for (int s = 0; s < 10; s++) {
        const uint32_t o8 = b8 + 8 * (s & 1);
        const uint64_t dW = dB0 + o8 * (TB >> 7);
        mbar_wait(bar_a + 8 * (s % 5), s / 5);
        mbar_wait(bar_b + o8, phb);
        if (s == 9) asm volatile("bar.sync %0, 256;" ::"r"(1 + w) : "memory");
        WG_FENCE();
#pragma unroll
        for (int kk = 0; kk < 4; kk++) wg_ss192t(acc, dA + ((s % 5) * (TA >> 4) + kk * 2), dW + kk * 384, kk != 0 || s != 0);
        WG_COMMIT();
        if (s == 9) asm volatile("bar.arrive %0, 256;" ::"r"(2 - w) : "memory");
        if (s > 0) { WG_WAIT(1); rel_a(8 * ((s - 1) % 5)); rel_b(pb8); }
        if (s < 9) { if (u > 0) store_o(s); else ln_piece(p, fr, s, ln_row(), lane & 15); }
        if (s == 8) { __syncwarp(); if (lane == 0) mbar_arrive(bar_o); }
        pb8 = o8;
        if (s & 1) next_pair();
      }
      if (u == 0) {
        mbar_wait(bar_s, 0);
        const uint2 s0 = lds64(s_stat + (cw * 16 + g) * 8), s1 = lds64(s_stat + 64 + (cw * 16 + g) * 8);
        const uint32_t msk = q == 0 ? 0xffffffffu : q == 1 ? 0xffffu : 0u;
        const float c0 = SM_C * __uint_as_float(s0.y), c1 = SM_C * __uint_as_float(s1.y);
        uint32_t am[4] = {(s0.x ^ 0x80008000u) & msk, (s1.x ^ 0x80008000u) & msk, 0, 0};
        reg_fence(am);
        WG_FENCE();
        wg_rs192t(acc, am[0], am[1], am[2], am[3], mkdesc(sb, desc_hi(1024, 0, 1)), 1);
        WG_COMMIT();
        WG_WAIT(0);
        reg_fence(acc);
#pragma unroll
        for (int i = 0; i < 24; i++) { acc[4 * i] *= c0; acc[4 * i + 1] *= c0; acc[4 * i + 2] *= c1; acc[4 * i + 3] *= c1; }
      } else { WG_WAIT(0); reg_fence(acc); }
      rel_b(pb8);
      rel_a(32);
      auto pack_q = [&](int from, int to) {
#pragma unroll
        for (int i = from; i < to; i++) { fr[i] = pack_bf16(acc[2 * i], acc[2 * i + 1]); asm volatile("" : "+r"(fr[i])::"memory"); }
      };
      pack_q(0, CVG);
      float sc[32], l0 = 0.f, l1 = 0.f;
      uint32_t pf[16], k8;
      auto pack_p = [&](const float (&s_)[32], int from = 0, int to = 16) {
#pragma unroll
        for (int i = from; i < to; i++) pf[i] = pack_bf16(s_[2 * i], s_[2 * i + 1]);
      };
      auto scores = [&](int j, int pass = 11) {
        k8 = b8 + 8;
        mbar_wait(bar_b + k8, phb);
        next_pair();
        mbar_wait(bar_b + b8, phb);
        const uint64_t dk = mkdesc(sb + OFF_B, HI_W) + k8 * (TB >> 7);
        asm volatile("bar.sync %0, 256;" ::"r"(1 + w) : "memory");
        WG_FENCE();
#pragma unroll
        for (int t = 0; t < 12; t++) {
          wg_rs64(sc, fr[4 * t], fr[4 * t + 1], fr[4 * t + 2], fr[4 * t + 3], dk + (t >> 2) * 64 + (t & 3) * 2, t != 0);
          if (t == 11) WG_COMMIT();
          if (t == pass) asm volatile("bar.arrive %0, 256;" ::"r"(2 - w) : "memory");
        }
      };
      auto pv = [&](int add) {
        const uint64_t dv = mkdesc(sb + OFF_B, HI_W) + b8 * (TB >> 7);
#pragma unroll
        for (int kk = 0; kk < 4; kk++) wg_rs192t(acc, pf[4 * kk], pf[4 * kk + 1], pf[4 * kk + 2], pf[4 * kk + 3], dv + kk * 384, kk != 0 || add);
        WG_COMMIT();
      };
      auto finish = [&]() {
        WG_WAIT(1);
        reg_fence(sc);
        exp_block(sc, l0, l1);
        rel_b(k8 + (__float_as_uint(l0) & __float_as_uint(l1) & zero));
        WG_WAIT(0);
        reg_fence(acc); reg_fence(pf);
        rel_b(b8);
        pack_p(sc);
      };
      {
        mbar_wait(bar_b + b8, phb);
        const uint64_t dk = mkdesc(sb + OFF_B, HI_W) + b8 * (TB >> 7);
        asm volatile("bar.sync %0, 256;" ::"r"(1 + w) : "memory");
#pragma unroll
        for (int t = 0; t < 12; t++) {
          if (t && (4 * t) % CVG == 0) pack_q(4 * t, 4 * t + CVG);
          if ((4 * t) % CVG == 0) WG_FENCE();
          wg_rs64(sc, fr[4 * t], fr[4 * t + 1], fr[4 * t + 2], fr[4 * t + 3], dk + (t >> 2) * 64 + (t & 3) * 2, t != 0);
          if (t == 7) asm volatile("bar.arrive %0, 256;" ::"r"(2 - w) : "memory");
        }
        WG_COMMIT();
        WG_WAIT(0);
        reg_fence(sc);
        float s0[32];
#pragma unroll
        for (int i = 0; i < 32; i++) s0[i] = i < NE ? sc[i] : __uint_as_float(__float_as_uint(sc[i]) ^ zero);
        exp_block(s0, l0, l1, 0, NE);
        pack_p(s0, 0, NE / 2);
#pragma unroll
        for (int i = NE; i < 32; i++) asm volatile("" : "+f"(s0[i])::"memory");
#pragma unroll
        for (int i = 0; i < NE / 2; i++) asm volatile("" : "+r"(pf[i])::"memory");
        rel_b(b8);
        scores(1, PS1);
        const uint32_t z = lds32(s_stat) & zero;
#pragma unroll
        for (int i = NE; i < 32; i++) {
          asm("{\n.reg .pred p;\nsetp.eq.u32 p, %1, 0;\n@p ex2.approx.ftz.f32 %0, %0;\n}\n" : "+f"(s0[i]) : "r"(z));
          if (i & 2) l1 += s0[i]; else l0 += s0[i];
        }
        pack_p(s0, NE / 2, 16);
        reg_fence(pf);
        WG_FENCE();
        pv(0);
        finish();
      }
#pragma unroll 1
      for (int j = NE < 32 ? 2 : 1; j < 8; j++) { scores(j); pv(j > 1); finish(); }
      const uint32_t v8 = b8 + 8;
      mbar_wait(bar_b + v8, phb);
      next_pair();
      {
        const uint64_t dv = mkdesc(sb + OFF_B, HI_W) + v8 * (TB >> 7);
        asm volatile("bar.sync %0, 256;" ::"r"(1 + w) : "memory");
        WG_FENCE();
#pragma unroll
        for (int kk = 0; kk < 4; kk++) {
          wg_rs192t(acc, pf[4 * kk], pf[4 * kk + 1], pf[4 * kk + 2], pf[4 * kk + 3], dv + kk * 384, 1);
          if (kk == 1 && (u < 3 || w == 0)) asm volatile("bar.arrive %0, 256;" ::"r"(2 - w) : "memory");
        }
        WG_COMMIT();
      }
      l0 = quad_sum(l0); l1 = quad_sum(l1);
      const bool unsafe = __any_sync(~0u, !(l0 >= SM_LO && l1 >= SM_LO && l0 + l1 <= SM_HI));
      l0 = rcp(l0); l1 = rcp(l1);
      rl[0] = pack_bf16(l0, l0); rl[1] = pack_bf16(l1, l1);
      l0 -= bf_lo(rl[0]); l1 -= bf_lo(rl[1]);
      rl[2] = pack_bf16(l0, l0); rl[3] = pack_bf16(l1, l1);
      WG_WAIT(0);
      reg_fence(acc);
      rel_b(v8);
      if (__builtin_expect(unsafe, 0)) {
        int o = hg * 4 + u; asm volatile("" : "+r"(o));
        o = (o * SKC + (SKC - WIN) + g) * (DH / 2) + q;
#pragma unroll
        for (int i = 0; i < 12; i++) optr[(i >> 1) * 512 + (i & 1) * 32] = make_uint4(fr[4 * i], fr[4 * i + 1], fr[4 * i + 2], fr[4 * i + 3]);
        safe_head((const uint32_t*)p.k + o, (const uint32_t*)p.v + o, optr);
#pragma unroll
        for (int i = 0; i < 12; i++) { const uint4 v = optr[(i >> 1) * 512 + (i & 1) * 32]; fr[4 * i] = v.x; fr[4 * i + 1] = v.y; fr[4 * i + 2] = v.z; fr[4 * i + 3] = v.w; }
        rl[0] = rl[1] = 0x3f803f80u; rl[2] = rl[3] = 0;
      } else {
#pragma unroll
        for (int i = 0; i < 24; i++) {
          fr[8 * (i >> 2) + (i & 3)] = pack_bf16(acc[4 * i], acc[4 * i + 1]);
          fr[8 * (i >> 2) + 4 + (i & 3)] = pack_bf16(acc[4 * i + 2], acc[4 * i + 3]);
        }
      }
    }

    float aF[80], aS[80];
    uint32_t pha = 0, a8 = 0, pa8 = 0, pb8 = 0;
#pragma unroll 1
    for (int s = 0; s < 19; s++) {
      const uint64_t d0 = mkdesc(sb, HI_O), dO = d0 + (a8 * (TA >> 7) + w * 256), dB = d0 + ((OFF_B >> 4) + b8 * (TB >> 7));
      mbar_wait(bar_a + a8, pha);
      mbar_wait(bar_b + b8, phb);
      WG_FENCE();
#pragma unroll
      for (int kk = 0; kk < 4; kk++) wg_ss160t(aF, dO + ((kk >> 1) * 512 + (kk & 1) * 2), dB + ((kk >> 1) * 640 + (kk & 1) * 64), kk != 0 || s != 0);
      WG_COMMIT();
      mbar_wait(bar_b + b8 + 8, phb);
      WG_WAIT(1);
      if (s > 0) { rel_a(pa8); rel_b(pb8 + 8); }
      WG_FENCE();
#pragma unroll
      for (int kk = 0; kk < 4; kk++) wg_ss160t(aS, dO + ((kk >> 1) * 512 + (kk & 1) * 2), dB + ((TB >> 4) + (kk >> 1) * 640 + (kk & 1) * 64), kk != 0 || s != 0);
      WG_COMMIT();
      if (s < 9) {
#pragma unroll
        for (int pp = 0; pp < 9; pp++) if (s == pp) store_o(pp);
        if (s == 8) { __syncwarp(); if (lane == 0) mbar_arrive(bar_o); }
      } else if (s < 15) {
        const int b = 2 * cw + ((lane >> 3) & 1);
        uint32_t ga = sb + OFF_B + TW + ((b * 11) >> 5) * (TB - 3840) + b * 1280 + (lane & 7) * 160 + (lane >> 4) * 16;
        if (s < 14) {
          mbar_wait(bar_x, 0);
          ga += 32 * (s - 9);
          ldsm4(ga, fr);
#pragma unroll
          for (int i = 0; i < 4; i++) {
            const uint2 st = lds64(s_stat + (cw * 16 + g + 8 * (i & 1)) * 8);
            const uint32_t d = hsub2(fr[i], st.x), xn = pack_bf16(bf_lo(d) * __uint_as_float(st.y), bf_hi(d) * __uint_as_float(st.y));
            fr[i] = pack_bf16(silu_f(bf_lo(xn)), silu_f(bf_hi(xn)));
          }
          stsm4(ga, fr);
        } else {
          mbar_wait(bar_u, 0);
          const uint2 sel = lds64(s_sel);
          const uint32_t row = qt * 128 + cw * 16 + (lane & 15);
          if (row == sel.x || row == sel.y) ga = s_sel + 16 + (row == sel.y ? 160 : 0) + (lane >> 4) * 16;
#pragma unroll
          for (int k = 0; k < 5; k++) ldsm4(ga + 32 * k, fr + 4 * k);
        }
      }
      WG_WAIT(1);
      rel_b(b8);
      pa8 = a8; a8 += 8; if (a8 == 40) { a8 = 0; pha ^= 1; }
      pb8 = b8; next_pair();
    }
    const int t128 = threadIdx.x & 127;
    uint4* const xbase = p.s->o + (size_t)(qt * 192 + nh * 24 + 10) * 512 + w * 640 + t128;
    uint4* const dst = xbase + kq * (48 * 512);
    float q1[40], q2[40], oth[40], own[40];
    auto take = [&](float (&x)[40], const float* a) {
#pragma unroll
      for (int k = 0; k < 40; k++) x[k] = __uint_as_float(__float_as_uint(a[k]) ^ zero);
      reg_fence(x);
    };
    reg_fence(aF);
    take(q1, aF);
    auto fa = [&](int i) { return mbar_try(bar_a + 8 * ((4 + i) % 5), i == 0); };
    auto fb = [&](int e) { return mbar_try(bar_b + 8 * (e % 6), (e / 6) & 1); };
    auto send = [&](int m) {
      const float* v = (m < 5 ? q1 : m < 10 ? q2 : oth) + 8 * (m % 5);
      st_pkt(dst + (m / 5) * 1280 + (m % 5) * 128, pack_bf16(v[0], v[1]) | 1, pack_bf16(v[2], v[3]), pack_bf16(v[4], v[5]), pack_bf16(v[6], v[7]));
    };
    static_for<20>([&](auto n_) {
      constexpr int n = n_.value, i = end_stage(n), e = 142 + n / 2, qi = n == 4 ? 1 : n == LQ ? 0 : n / 5;
      float (&acc_)[40] = qi == 0 ? q1 : qi == 1 ? q2 : qi == 2 ? oth : own;
      if (n == 0) while (!(fa(0) & fa(1) & fb(142) & fb(143))) {}
      if (n == 2) while (!(fa(2) & fa(3) & fb(144))) {}
      if (n == LQ) while (!(fa(4) & fb(145) & fb(146) & mbar_try(bar_z, 0))) {}
      if (n == 10) while (!(fb(147) & fb(148) & fb(149))) {}
      const uint64_t d0 = mkdesc(fresh(), HI_O);
      WG_FENCE();
#pragma unroll
      for (int kk = 0; kk < 4; kk++)
        wg_ss80t(acc_, d0 + w * 256 + (((4 + i) % 5) * (TA >> 4) + (kk >> 1) * 512 + (kk & 1) * 2),
                 d0 + ((OFF_B >> 4) + (e % 6) * (TB >> 4) + (n & 1) * 768 + (kk >> 1) * 384 + (kk & 1) * 64), 1);
      WG_COMMIT();
      if ((!(n & 1) && n <= 16) || n == 15 || n == LQ + 1) WG_WAIT(1);
      if (n == 0) rel_a(24);
      if (!(n & 1) && n <= 10) rel_b(8 * ((e - 1) % 6));
      if (n == Q2N) take(q2, aF + 40);
      if (n == 10) cluster_arrive();
      if (n == 12 || n == 14 || n == 16) rel_a(4u * n - 48);
      if (n == LQ + 1) reg_fence(q1);
      if (n == 10) reg_fence(q2);
      if (n == 15) reg_fence(oth);
      if (n == 15) while (!(fb(150) & fb(151))) {}
      static_for<sent(n + 1) - sent(n)>([&](auto k_) { send(sent(n) + k_.value); });
      if (n == 8) {
        reg_fence(aS);
#pragma unroll
        for (int k = 0; k < 40; k++) oth[k] = kq & 1 ? aS[k] : aS[40 + k];
        reg_fence(oth);
      }
      if (n == SWN) {
        reg_fence(aS);
#pragma unroll
        for (int k = 0; k < 40; k++) own[k] = kq & 1 ? aS[40 + k] : aS[k];
        reg_fence(own);
      }
    });
    uint32_t xr[20];
    const uint32_t xs = sb + OFF_B + 2 * TB + cw * 2560, xa = xs + (lane & 15) * 160 + (lane >> 4) * 16;
    mbar_wait(bar_b + 16, 1);
#pragma unroll
    for (int k = 0; k < 5; k++) ldsm4(xa + 32 * k, xr + 4 * k);
    {
      auto fetch = [&](int e, uint4 (&v)[5]) {
        mbar_wait(bar_e + 16 * e + 8 * w, 0);
#pragma unroll
        for (int i = 0; i < 5; i++) v[i] = lds128(sb + OFF_B + (3 + e) * TB + (w * 640 + i * 128 + t128) * 16);
      };
      auto add = [&](int e, uint4 (&v)[5]) {
        while (!(v[0].x & v[1].x & v[2].x & v[3].x & v[4].x & 1)) {
#pragma unroll
          for (int i = 0; i < 5; i++) v[i] = ld_pkt(xbase + (kq ^ ((0x132 >> (4 * e)) & 3)) * (48 * 512) + (e < 2 ? kq & 1 : 2) * 1280 + i * 128);
        }
#pragma unroll
        for (int i = 0; i < 5; i++) {
          float* o = own + 8 * i;
          o[0] += bf_lo(v[i].x); o[1] += bf_hi(v[i].x); o[2] += bf_lo(v[i].y); o[3] += bf_hi(v[i].y);
          o[4] += bf_lo(v[i].z); o[5] += bf_hi(v[i].z); o[6] += bf_lo(v[i].w); o[7] += bf_hi(v[i].w);
        }
      };
      WG_WAIT(0);
      reg_fence(own);
#pragma unroll 1
      for (int e = 0; e < 3; e++) { uint4 v[5]; fetch(e, v); add(e, v); }
      if (lane == 0) mbar_arrive(bar_w);
#pragma unroll
      for (int i = 0; i < 20; i++) xr[i] = hadd2(xr[i], hmul2(pack_bf16(own[2 * i], own[2 * i + 1]), fr[i]));
#pragma unroll
      for (int k = 0; k < 5; k++) stsm4(xa + 32 * k, xr + 4 * k);
      asm volatile("fence.proxy.async.shared::cta;" ::: "memory");
      __syncwarp();
      if (elect()) {
        tma2d_store(&m.out, xs, nh * 320 + kq * 80, qt * 128 + cw * 16);
        asm volatile("cp.async.bulk.commit_group;\ncp.async.bulk.wait_group.read 0;" ::: "memory");
      }
      __syncwarp();
    }
    cluster_wait();
  } else {
    asm volatile("setmaxnreg.dec.sync.aligned.u32 40;");
    uint32_t tid_; asm volatile("mov.u32 %0, %%tid.x;" : "=r"(tid_));
    const int warp = __shfl_sync(~0u, tid_ >> 5, 0);
    auto is_warp = [&](int k) { uint32_t e; asm volatile("{\n.reg .pred q;\nsetp.eq.u32 q, %1, %2;\nselp.u32 %0, 1, 0, q;\n}" : "=r"(e) : "r"(warp), "r"(k)); return e != 0; };
    if (warp > 0) {
      const unsigned epoch = (unsigned)(__ldcg(&p.s->done) >> 7);
      int budget = WAIT_BUDGET;
      const uint32_t tag = epoch + 1;
      mbar_wait(bar_a + EA, 0, budget);
      mbar_wait(bar_b + (kg0 & ~7), 0, budget); mbar_wait(bar_b + (kg0 & ~7) + 8, 0, budget);
      float cs0 = 0.f, cs1 = 0.f;
      const int n = rank * 96 + (warp - 1) * 32;
#pragma unroll 1
      for (int kg = kg0 + (lane >> 4) * 5, e = kg + 5; kg < e; kg++) {
        const uint32_t ad = sb + OFF_B + kg * 3072 + (n >> 6) * 1024 + (n & 63) * 2 + (lane & 15) * 4;
#pragma unroll
        for (int k = 0; k < 8; k++) { const uint32_t v = lds32(ad ^ (k * 0x90)); cs0 += bf_lo(v); cs1 += bf_hi(v); }
      }
      cs0 += __shfl_xor_sync(~0u, cs0, 16); cs1 += __shfl_xor_sync(~0u, cs1, 16);
      if (lane < 16) st_pkt8((uint2*)(p.s->cs + (hg * 4 + (qt >> 2)) * 96 + (n >> 1) + lane) + ((qt >> 1) & 1), (__float_as_uint(cs0) & ~3u) | (tag & 3), __float_as_uint(cs1));
      if (lane < 2) { uint32_t a; asm volatile("mapa.shared::cluster.u32 %0, %1, %2;" : "=r"(a) : "r"(bar_d), "r"(lane)); mbar_arrive_cluster(a); }
      mbar_wait(bar_a + EA, 1, budget);
      for (const uint32_t c0 = clock(); clock() - c0 < CSW;) {}
      uint4 v[5];
      while (true) {
        uint32_t bad = 0;
#pragma unroll
        for (int i = 0; i < 5; i++) v[i] = ld_pkt(i < 4 ? p.s->cs + (hg * 4 + i) * 96 + (tid_ - 32) : (const uint4*)p.s->stat + qt * 64 + (tid_ & 63));
#pragma unroll
        for (int i = 0; i < 5; i++) bad |= (v[i].x ^ tag) | (v[i].z ^ tag);
        if (!__any_sync(~0u, bad & 3) || --budget < 0) break;
      }
      asm volatile("st.shared.v4.u32 [%0], {%1,%2,%3,%4};" ::"r"(s_stat + (tid_ & 63) * 16), "r"(__byte_perm(v[4].x, 0, 0x3232)), "r"(v[4].y), "r"(__byte_perm(v[4].z, 0, 0x3232)), "r"(v[4].w) : "memory");
      cs0 = cs1 = 0.f;
#pragma unroll
      for (int i = 0; i < 4; i++) { cs0 += __uint_as_float(v[i].x & ~3u) + __uint_as_float(v[i].z & ~3u); cs1 += __uint_as_float(v[i].y) + __uint_as_float(v[i].w); }
#pragma unroll
      for (int k = 0; k < 8; k++) {
        const uint32_t t = k < 3 ? pack_bf16(cs0, cs1) : 0;
        sts32((sb + (warp - 1) * 1024 + lane * 4) ^ (k * 0x90), t);
        cs0 -= bf_lo(t); cs1 -= bf_hi(t);
      }
      asm volatile("fence.proxy.async.shared::cta;" ::: "memory");
      __syncwarp();
      if (lane < 2) mbar_arrive(bar_s);
      budget = errands(p.s, m, qt, hg, warp, tag, budget);
      if (is_warp(2)) {
        mbar_wait(bar_w, 0, budget);
        if (budget < 0) asm volatile("st.global.u32 [%0], %1;" ::"l"(0ull), "r"(budget) : "memory");
      }
    } else {
      uint32_t fb = bar_b + 16, dst = sb + OFF_B + 2 * TB, ph = 1;
      auto next = [&]() { fb += 8; dst += TB; if (fb == bar_b + 48) { fb = bar_b; dst = sb + OFF_B; ph ^= 1; } };
#pragma unroll 1
      for (int u = 0; u < 4; u++) {
        const int h = hg * 4 + u;
        int s = u ? (u == 2 ? 5 : 0) : (s0 + 2) % 10;
#pragma unroll 1
        for (int i = u ? 0 : 2; i < 10; i++) {
          if (u == 0) {
            const uint32_t a8 = 8 * (i < 5 ? i : i - 5);
            if (D0 && i >= D0) { const int j = i - D0; mbar_wait(bar_a + 8 * (j < 5 ? j : j - 5), j >= 5); }
            mbar_wait(bar_a + EA + a8, i < 5);
            if (elect()) { mbar_expect_tx(bar_a + a8, TA); tma2d(sb + a8 * (TA >> 3), &m.x, 64 * s, qt * 128, bar_a + a8); }
            if (i == 6 + (kg0 >> 3)) mbar_wait(bar_d, 0);
          }
          mbar_wait(fb + EB, ph);
          if (elect()) { mbar_expect_tx(fb, TB); tma4d_mc(dst + rank * (TB / 2), &m.wq, 3 * h, 8 * s + 4 * rank, fb); }
          next();
          if (++s == 10) s = 0;
        }
        const int kv0 = (h * SKC + (SKC - WIN)) / 8 + 4 * rank;
#pragma unroll 1
        for (int i = 0; i < 16; i++) {
          const bool isk = (0x2AAB >> i) & 1;
          mbar_wait(fb + EB, ph);
          if (elect()) { mbar_expect_tx(fb, TB); tma4d_mc(dst + rank * (TB / 2), isk ? &m.k : &m.v, 0, kv0 + 8 * (isk ? (i + 1) >> 1 : (i - 1) >> 1), fb); }
          next();
        }
      }
      const int cF = 10 * nh + 5 - 5 * (kq >> 1), cS = 10 * nh + 5 * (kq >> 1);
      const int kb = 4 * (k_block(lane, hg) + rank);
#pragma unroll 1
      for (int n = 0; n < 38; n++) {
        const int c2 = __shfl_sync(~0u, kb, n >> 1);
        mbar_wait(fb + EB, ph);
        if (elect()) { mbar_expect_tx(fb, TW); tma5d_mc(dst + rank * (TW / 2), &m.wo, c2, n & 1 ? cS : cF, fb); }
        next();
      }
      const int odd = (((0x7ff0 ^ 1 << LQ) ^ (kq & 1 ? 0xffc00 : 0)) >> lane) & 1;
      const int tq = __shfl_sync(~0u, kb, 19 + end_stage(lane)) << 16 | odd << 7 | ((lane < 10 ? cF : cS) + 2 * odd);
#pragma unroll 1
      for (int n = 0; n < 20; n += 2) {
        const int t0 = __shfl_sync(~0u, tq, n), t1 = __shfl_sync(~0u, tq, n + 1);
        mbar_wait(fb + EB, ph);
        if (elect()) {
          mbar_expect_tx(fb, TB);
          tma5d_mc(dst + rank * (TB / 4), (const CUtensorMap*)((const char*)m.w3 + (t0 & 128)), t0 >> 16, t0 & 31, fb);
          tma5d_mc(dst + TB / 2 + rank * (TB / 4), (const CUtensorMap*)((const char*)m.w3 + (t1 & 128)), t1 >> 16, t1 & 31, fb);
        }
        next();
      }
      mbar_wait(fb + EB, ph);
      if (elect()) { mbar_expect_tx(fb, TW); tma2d(dst, &m.xe, nh * 320 + kq * 80, qt * 128, fb); }
    }
    if (!is_warp(2)) {
      const int e = warp - (warp >> 1), ms = 2 * e + ((lane >> 2) & 1);
      const uint4* src = p.s->o + (size_t)(qt * 192 + nh * 24 + 10 + (kq ^ ((0x132 >> (4 * e)) & 3)) * 48) * 512 + (e < 2 ? kq & 1 : 2) * 1280 + (ms & 1) * 640;
      uint32_t todo = 0xff;
      bool ok = lane >= 8;
      mbar_wait(bar_z, 0);
#pragma unroll 1
      while (todo) {
        if (!ok) ok = ld_pkt(src + 4 * 128 + (lane & 3) * 32 + 31).x & 1;
        const uint32_t got = __ballot_sync(~0u, ok) & todo, go = __ballot_sync(~0u, ((got >> (lane & 28)) & 15) == 15);
        if (go) mbar_wait(bar_a + EA + 8 * e, 0);
        if ((go & 0x11) >> lane & 1) {
          mbar_expect_tx(bar_e + 8 * ms, TW / 2); bulk_load(sb + OFF_B + (3 + e) * TB + (ms & 1) * (TW / 2), src, TW / 2, bar_e + 8 * ms);
        }
        todo &= ~go;
      }
    }
    cluster_sync();
  }
}

typedef CUresult (*EncodeFn)(CUtensorMap*, CUtensorMapDataType, cuuint32_t, void*, const cuuint64_t*, const cuuint64_t*,
                             const cuuint32_t*, const cuuint32_t*, CUtensorMapInterleave, CUtensorMapSwizzle,
                             CUtensorMapL2promotion, CUtensorMapFloatOOBfill);

void encode(EncodeFn fn, CUtensorMap* tm, void* base, int rank, const cuuint64_t* dims, const cuuint64_t* strides,
            const cuuint32_t* box, CUtensorMapSwizzle sw) {
  const cuuint32_t es[5] = {1, 1, 1, 1, 1};
  fn(tm, CU_TENSOR_MAP_DATA_TYPE_BFLOAT16, rank, base, dims, strides, box, es, CU_TENSOR_MAP_INTERLEAVE_NONE, sw,
     CU_TENSOR_MAP_L2_PROMOTION_L2_128B, CU_TENSOR_MAP_FLOAT_OOB_FILL_NONE);
}

}

extern "C" void kernel_launch(void* const* d_in, const int* in_sizes, int n_in, void* d_out, int out_size) {
  static EncodeFn fn = nullptr;
  static Scratch* scr = nullptr;
  if (!fn) {
    void* f = nullptr;
    cudaDriverEntryPointQueryResult st;
    cudaGetDriverEntryPoint("cuTensorMapEncodeTiled", &f, cudaEnableDefault, &st);
    fn = (EncodeFn)f;
    cudaGetSymbolAddress((void**)&scr, g_scratch);
    cudaFuncSetAttribute(fused_kernel, cudaFuncAttributeMaxDynamicSharedMemorySize, SMEM_BYTES);
  }
  Maps m;
  { const cuuint64_t d[2] = {DM, SQ}, s[1] = {DM * 2}; const cuuint32_t b[2] = {64, 128};
    encode(fn, &m.x, d_in[0], 2, d, s, b, CU_TENSOR_MAP_SWIZZLE_128B);
    encode(fn, &m.xn, scr->xn, 2, d, s, b, CU_TENSOR_MAP_SWIZZLE_128B); }
  { const cuuint64_t d[4] = {64, 8, QD / 64, DM / 8}, s[3] = {QD * 2, 128, 8 * QD * 2}; const cuuint32_t b[4] = {64, 8, 3, 4};
    encode(fn, &m.wq, d_in[3], 4, d, s, b, CU_TENSOR_MAP_SWIZZLE_128B); }
  { const cuuint64_t d[4] = {64, 8, 3, NH * SKC / 8}, s[3] = {DH * 2, 128, 8 * DH * 2}; const cuuint32_t b[4] = {64, 8, 3, 4};
    encode(fn, &m.k, d_in[1], 4, d, s, b, CU_TENSOR_MAP_SWIZZLE_128B);
    encode(fn, &m.v, d_in[2], 4, d, s, b, CU_TENSOR_MAP_SWIZZLE_128B); }
  {
    const cuuint64_t d[5] = {32, 2, QD / 8, 4, DM / 32}, s[4] = {DM * 2, 8 * DM * 2, 2 * DM * 2, 64}; const cuuint32_t b[5] = {32, 2, 4, 4, 5};
    encode(fn, &m.wo, d_in[4], 5, d, s, b, CU_TENSOR_MAP_SWIZZLE_64B);
    const cuuint32_t b3[5] = {32, 2, 4, 4, 3};
    encode(fn, &m.w3[0], d_in[4], 5, d, s, b3, CU_TENSOR_MAP_SWIZZLE_64B);
    encode(fn, &m.w3[1], (char*)d_in[4] + 32, 5, d, s, b3, CU_TENSOR_MAP_SWIZZLE_64B); }
  { const cuuint64_t d[2] = {DM, SQ}, s[1] = {DM * 2}; const cuuint32_t bg[2] = {80, 24}, bx[2] = {80, 128}, bo[2] = {80, 16};
    encode(fn, &m.xg, d_in[0], 2, d, s, bg, CU_TENSOR_MAP_SWIZZLE_NONE);
    encode(fn, &m.xe, d_in[0], 2, d, s, bx, CU_TENSOR_MAP_SWIZZLE_NONE);
    encode(fn, &m.out, d_out, 2, d, s, bo, CU_TENSOR_MAP_SWIZZLE_NONE); }
  Params p;
  p.x = (const __nv_bfloat16*)d_in[0]; p.wr = (const __nv_bfloat16*)d_in[6]; p.wg = (const __nv_bfloat16*)d_in[7];
  p.wu = (const __nv_bfloat16*)d_in[8]; p.wd = (const __nv_bfloat16*)d_in[9];

  p.k = (const __nv_bfloat16*)d_in[1]; p.v = (const __nv_bfloat16*)d_in[2]; p.s = scr;
  cudaLaunchConfig_t cfg = {};
  cfg.gridDim = dim3(132); cfg.blockDim = dim3(384); cfg.dynamicSmemBytes = SMEM_BYTES; cfg.stream = cudaStreamPerThread;
  cudaLaunchKernelEx(&cfg, fused_kernel, p, m);
}
```

```cpp
#include <cuda_runtime.h>
#include <cuda_bf16.h>
#include <cuda.h>
#include <stdint.h>

namespace {

constexpr int SQ = 2048, DM = 640, NH = 32, DH = 192, SKC = 2048, WIN = 512, FF = 1536;
constexpr int QD = NH * DH;
constexpr uint32_t TA = 16384, TB = 24576, TW = 20480, OFF_B = 5 * TA, OFF_M = OFF_B + 6 * TB, SMEM_BYTES = OFF_M + 3072;
constexpr int WAIT_BUDGET = 1 << 20;

constexpr int FL_XN = 0;
constexpr int FL_O = 512;
constexpr int FL_RD = FL_O + 1024;
constexpr int FL_FFN = FL_RD + 1024;
constexpr int FL_SIDE = FL_FFN + 32;
struct __align__(1024) Scratch {
  unsigned long long done, pad0[15];
  unsigned flag[FL_SIDE + 32];
  uint4 cand[8];
  float ffn[4 * 2 * DM];
  int sel[4];
  __nv_bfloat16 gsel[2 * DM];
  uint4 cs[8 * 4 * DH / 2];
  uint2 stat[SQ];
  __align__(1024) __nv_bfloat16 xn[SQ * DM];
  __align__(1024) uint4 o[SQ * QD / 8];
};
__device__ Scratch g_scratch;

__device__ __forceinline__ uint32_t smem_u32(const void* p) { return (uint32_t)__cvta_generic_to_shared(p); }
__device__ __forceinline__ void mbar_init(uint32_t bar, int cnt) { asm volatile("mbarrier.init.shared::cta.b64 [%0], %1;" ::"r"(bar), "r"(cnt)); }
__device__ __forceinline__ void mbar_expect_tx(uint32_t bar, uint32_t bytes) {
  asm volatile("mbarrier.arrive.expect_tx.shared::cta.b64 _, [%0], %1;" ::"r"(bar), "r"(bytes) : "memory");
}
__device__ __forceinline__ void mbar_arrive(uint32_t bar) { asm volatile("mbarrier.arrive.shared::cta.b64 _, [%0];" ::"r"(bar) : "memory"); }
__device__ __forceinline__ void mbar_arrive_cluster(uint32_t addr) { asm volatile("mbarrier.arrive.shared::cluster.b64 _, [%0];" ::"r"(addr) : "memory"); }
__device__ __forceinline__ bool mbar_try(uint32_t bar, uint32_t parity) {
  uint32_t ok;
  asm volatile("{\n.reg .pred p;\nmbarrier.try_wait.parity.shared::cta.b64 p, [%1], %2;\nselp.u32 %0, 1, 0, p;\n}\n" : "=r"(ok) : "r"(bar), "r"(parity) : "memory");
  return ok;
}
__device__ __forceinline__ void mbar_wait(uint32_t bar, uint32_t parity, int& budget) {
#pragma unroll 1
  while (!mbar_try(bar, parity)) { if (--budget < 0) break; }
}
__device__ __forceinline__ void mbar_wait(uint32_t bar, uint32_t parity) {
#pragma unroll 1
  while (!mbar_try(bar, parity)) {}
}
__device__ __forceinline__ unsigned ld_acquire(const unsigned* p) { unsigned v; asm volatile("ld.acquire.gpu.global.u32 %0, [%1];" : "=r"(v) : "l"(p) : "memory"); return v; }
__device__ __forceinline__ void wait_flag(const unsigned* p, unsigned target) {
#pragma unroll 1
  while (__any_sync(~0u, (int)(ld_acquire(p) - target) < 0)) {}
}
__device__ __forceinline__ void red_release(unsigned* p) { asm volatile("red.release.gpu.global.add.u32 [%0], 1;" ::"l"(p) : "memory"); }
__device__ __forceinline__ void fence_proxy_async() { asm volatile("fence.proxy.async.global;" ::: "memory"); }
__device__ __forceinline__ bool elect() {
  uint32_t p;
  asm volatile("{\n.reg .pred P;\nelect.sync _|P, 0xffffffff;\nselp.u32 %0, 1, 0, P;\n}\n" : "=r"(p));
  return p;
}
__device__ __forceinline__ void cluster_arrive() { asm volatile("barrier.cluster.arrive.relaxed.aligned;" ::: "memory"); }
__device__ __forceinline__ void cluster_wait() { asm volatile("barrier.cluster.wait.aligned;" ::: "memory"); }
__device__ __forceinline__ void cluster_sync() { cluster_arrive(); cluster_wait(); }
__device__ __forceinline__ void tma2d(uint32_t dst, const CUtensorMap* tm, int c0, int c1, uint32_t bar) {
  asm volatile("cp.async.bulk.tensor.2d.shared::cluster.global.mbarrier::complete_tx::bytes [%0], [%1, {%3, %4}], [%2];"
               ::"r"(dst), "l"(tm), "r"(bar), "r"(c0), "r"(c1) : "memory");
}
constexpr uint64_t POL_FIRST = 0x12F0000000000000ull;
__device__ __forceinline__ void tma4d_mc(uint32_t dst, const CUtensorMap* tm, int c2, int c3, uint32_t bar) {
  asm volatile("cp.async.bulk.tensor.4d.shared::cluster.global.mbarrier::complete_tx::bytes.multicast::cluster.L2::cache_hint [%0], [%1, {%3, %3, %4, %5}], [%2], %6, %7;"
               ::"r"(dst), "l"(tm), "r"(bar), "r"(0), "r"(c2), "r"(c3), "h"((uint16_t)3), "l"(POL_FIRST) : "memory");
}
__device__ __forceinline__ void tma5d_mc(uint32_t dst, const CUtensorMap* tm, int c2, int c4, uint32_t bar) {
  asm volatile("cp.async.bulk.tensor.5d.shared::cluster.global.mbarrier::complete_tx::bytes.multicast::cluster.L2::cache_hint [%0], [%1, {%3, %3, %4, %3, %5}], [%2], %6, %7;"
               ::"r"(dst), "l"(tm), "r"(bar), "r"(0), "r"(c2), "r"(c4), "h"((uint16_t)3), "l"(POL_FIRST) : "memory");
}
__device__ __forceinline__ void bulk_load(uint32_t dst, const void* src, uint32_t bytes, uint32_t bar) {
  asm volatile("cp.async.bulk.shared::cluster.global.mbarrier::complete_tx::bytes.L2::cache_hint [%0], [%1], %2, [%3], %4;" ::"r"(dst), "l"(src), "r"(bytes), "r"(bar), "l"(POL_FIRST) : "memory");
}
__device__ __forceinline__ void tma2d_store(const CUtensorMap* tm, uint32_t src, int c0, int c1) {
  asm volatile("cp.async.bulk.tensor.2d.global.shared::cta.bulk_group [%0, {%2, %3}], [%1];" ::"l"(tm), "r"(src), "r"(c0), "r"(c1) : "memory");
}
__device__ __forceinline__ uint32_t lds32(uint32_t a) { uint32_t v; asm volatile("ld.shared.u32 %0, [%1];" : "=r"(v) : "r"(a) : "memory"); return v; }
__device__ __forceinline__ uint2 lds64(uint32_t a) { uint2 v; asm volatile("ld.shared.v2.u32 {%0,%1}, [%2];" : "=r"(v.x), "=r"(v.y) : "r"(a) : "memory"); return v; }
__device__ __forceinline__ uint4 lds128(uint32_t a) { uint4 v; asm volatile("ld.shared.v4.u32 {%0,%1,%2,%3}, [%4];" : "=r"(v.x), "=r"(v.y), "=r"(v.z), "=r"(v.w) : "r"(a) : "memory"); return v; }
__device__ __forceinline__ void ldsm4(uint32_t a, uint32_t* v) {
  asm volatile("ldmatrix.sync.aligned.m8n8.x4.shared.b16 {%0,%1,%2,%3}, [%4];" : "=r"(v[0]), "=r"(v[1]), "=r"(v[2]), "=r"(v[3]) : "r"(a) : "memory");
}
__device__ __forceinline__ void stsm4(uint32_t a, const uint32_t* v) {
  asm volatile("stmatrix.sync.aligned.m8n8.x4.shared.b16 [%0], {%1,%2,%3,%4};" ::"r"(a), "r"(v[0]), "r"(v[1]), "r"(v[2]), "r"(v[3]) : "memory");
}
__device__ __forceinline__ void sts32(uint32_t a, uint32_t v) { asm volatile("st.shared.u32 [%0], %1;" ::"r"(a), "r"(v) : "memory"); }
__device__ __forceinline__ void st_pkt(uint4* p, uint32_t a, uint32_t b, uint32_t c, uint32_t d) {
  asm volatile("st.relaxed.gpu.global.v4.b32 [%0], {%1, %2, %3, %4};" ::"l"(p), "r"(a), "r"(b), "r"(c), "r"(d) : "memory");
}
__device__ __forceinline__ void st_pkt8(void* p, uint32_t a, uint32_t b) {
  asm volatile("{\n.reg .b64 v;\nmov.b64 v, {%1, %2};\nst.relaxed.gpu.global.b64 [%0], v;\n}\n" ::"l"(p), "r"(a), "r"(b) : "memory");
}
__device__ __forceinline__ uint4 ld_pkt(const uint4* p) {
  uint4 v;
  asm volatile("{\n.reg .b128 v;\nld.relaxed.gpu.global.b128 v, [%4];\nmov.b128 {%0, %1, %2, %3}, v;\n}\n" : "=r"(v.x), "=r"(v.y), "=r"(v.z), "=r"(v.w) : "l"(p) : "memory");
  return v;
}
__device__ __forceinline__ uint4 ldg_nc(const void* p) {
  uint4 v;
  asm volatile("ld.global.nc.v4.u32 {%0,%1,%2,%3}, [%4];" : "=r"(v.x), "=r"(v.y), "=r"(v.z), "=r"(v.w) : "l"(p));
  return v;
}
#define WG_FENCE() asm volatile("wgmma.fence.sync.aligned;" ::: "memory")
#define WG_COMMIT() asm volatile("wgmma.commit_group.sync.aligned;" ::: "memory")
#define WG_WAIT(n) asm volatile("wgmma.wait_group.sync.aligned " #n ";" ::: "memory")
template <int N> __device__ __forceinline__ void reg_fence(float (&d)[N]) {
#pragma unroll
  for (int i = 0; i < N; i++) asm volatile("" : "+f"(d[i])::"memory");
}
template <int N> __device__ __forceinline__ void reg_fence(uint32_t (&d)[N]) {
#pragma unroll
  for (int i = 0; i < N; i++) asm volatile("" : "+r"(d[i])::"memory");
}
__device__ __forceinline__ constexpr uint64_t desc_hi(uint32_t lbo, uint32_t sbo, uint64_t sw) {
  return ((uint64_t)(lbo >> 4) << 16) | ((uint64_t)(sbo >> 4) << 32) | (sw << 62);
}
__device__ __forceinline__ uint64_t mkdesc(uint32_t addr, uint64_t hi) { return hi | (uint64_t)((addr & 0x3FFFF) >> 4); }
__device__ __forceinline__ uint32_t pack_bf16(float lo, float hi) { uint32_t r; asm("cvt.rn.bf16x2.f32 %0, %1, %2;" : "=r"(r) : "f"(hi), "f"(lo)); return r; }
__device__ __forceinline__ float bf_lo(uint32_t v) { return __uint_as_float(v << 16); }
__device__ __forceinline__ float bf_hi(uint32_t v) { return __uint_as_float(v & 0xffff0000u); }
__device__ __forceinline__ uint32_t hadd2(uint32_t a, uint32_t b) { uint32_t r; asm("add.rn.bf16x2 %0, %1, %2;" : "=r"(r) : "r"(a), "r"(b)); return r; }
__device__ __forceinline__ uint32_t hsub2(uint32_t a, uint32_t b) { uint32_t r; asm("sub.rn.bf16x2 %0, %1, %2;" : "=r"(r) : "r"(a), "r"(b)); return r; }
__device__ __forceinline__ uint32_t hmul2(uint32_t a, uint32_t b) { uint32_t r; asm("mul.rn.bf16x2 %0, %1, %2;" : "=r"(r) : "r"(a), "r"(b)); return r; }
__device__ __forceinline__ float rbf(float x) { return __bfloat162float(__float2bfloat16_rn(x)); }
__device__ __forceinline__ float ex2(float x) { float y; asm("ex2.approx.ftz.f32 %0, %1;" : "=f"(y) : "f"(x)); return y; }
__device__ __forceinline__ float rcp(float x) { float y; asm("rcp.approx.ftz.f32 %0, %1;" : "=f"(y) : "f"(x)); return y; }
__device__ __forceinline__ float sigmoid_f(float x) { return rcp(1.f + ex2(x * -1.4426950408889634f)); }
__device__ __forceinline__ float silu_f(float x) { return x * sigmoid_f(x); }

__device__ __forceinline__ void wg_ss192t(float (&d)[96], uint64_t da, uint64_t db, int sd) {
  asm volatile("{\n.reg .pred p;\nsetp.ne.b32 p, %98, 0;\n"
    "wgmma.mma_async.sync.aligned.m64n192k16.f32.bf16.bf16 {%0,%1,%2,%3,%4,%5,%6,%7,%8,%9,%10,%11,%12,%13,%14,%15,%16,%17,%18,%19,%20,%21,%22,%23,%24,%25,%26,%27,%28,%29,%30,%31,%32,%33,%34,%35,%36,%37,%38,%39,%40,%41,%42,%43,%44,%45,%46,%47,%48,%49,%50,%51,%52,%53,%54,%55,%56,%57,%58,%59,%60,%61,%62,%63,%64,%65,%66,%67,%68,%69,%70,%71,%72,%73,%74,%75,%76,%77,%78,%79,%80,%81,%82,%83,%84,%85,%86,%87,%88,%89,%90,%91,%92,%93,%94,%95}, %96, %97, p, 1, 1, 0, 1;\n}\n"
    : "+f"(d[0]),"+f"(d[1]),"+f"(d[2]),"+f"(d[3]),"+f"(d[4]),"+f"(d[5]),"+f"(d[6]),"+f"(d[7]),"+f"(d[8]),"+f"(d[9]),"+f"(d[10]),"+f"(d[11]),"+f"(d[12]),"+f"(d[13]),"+f"(d[14]),"+f"(d[15]),"+f"(d[16]),"+f"(d[17]),"+f"(d[18]),"+f"(d[19]),"+f"(d[20]),"+f"(d[21]),"+f"(d[22]),"+f"(d[23]),"+f"(d[24]),"+f"(d[25]),"+f"(d[26]),"+f"(d[27]),"+f"(d[28]),"+f"(d[29]),"+f"(d[30]),"+f"(d[31]),"+f"(d[32]),"+f"(d[33]),"+f"(d[34]),"+f"(d[35]),"+f"(d[36]),"+f"(d[37]),"+f"(d[38]),"+f"(d[39]),"+f"(d[40]),"+f"(d[41]),"+f"(d[42]),"+f"(d[43]),"+f"(d[44]),"+f"(d[45]),"+f"(d[46]),"+f"(d[47]),"+f"(d[48]),"+f"(d[49]),"+f"(d[50]),"+f"(d[51]),"+f"(d[52]),"+f"(d[53]),"+f"(d[54]),"+f"(d[55]),"+f"(d[56]),"+f"(d[57]),"+f"(d[58]),"+f"(d[59]),"+f"(d[60]),"+f"(d[61]),"+f"(d[62]),"+f"(d[63]),"+f"(d[64]),"+f"(d[65]),"+f"(d[66]),"+f"(d[67]),"+f"(d[68]),"+f"(d[69]),"+f"(d[70]),"+f"(d[71]),"+f"(d[72]),"+f"(d[73]),"+f"(d[74]),"+f"(d[75]),"+f"(d[76]),"+f"(d[77]),"+f"(d[78]),"+f"(d[79]),"+f"(d[80]),"+f"(d[81]),"+f"(d[82]),"+f"(d[83]),"+f"(d[84]),"+f"(d[85]),"+f"(d[86]),"+f"(d[87]),"+f"(d[88]),"+f"(d[89]),"+f"(d[90]),"+f"(d[91]),"+f"(d[92]),"+f"(d[93]),"+f"(d[94]),"+f"(d[95])
    : "l"(da), "l"(db), "r"(sd));
}
__device__ __forceinline__ void wg_rs64(float (&d)[32], uint32_t a0, uint32_t a1, uint32_t a2, uint32_t a3, uint64_t db, int sd) {
  asm volatile("{\n.reg .pred p;\nsetp.ne.b32 p, %37, 0;\n"
    "wgmma.mma_async.sync.aligned.m64n64k16.f32.bf16.bf16 {%0,%1,%2,%3,%4,%5,%6,%7,%8,%9,%10,%11,%12,%13,%14,%15,%16,%17,%18,%19,%20,%21,%22,%23,%24,%25,%26,%27,%28,%29,%30,%31}, {%32,%33,%34,%35}, %36, p, 1, 1, 0;\n}\n"
    : "+f"(d[0]),"+f"(d[1]),"+f"(d[2]),"+f"(d[3]),"+f"(d[4]),"+f"(d[5]),"+f"(d[6]),"+f"(d[7]),"+f"(d[8]),"+f"(d[9]),"+f"(d[10]),"+f"(d[11]),"+f"(d[12]),"+f"(d[13]),"+f"(d[14]),"+f"(d[15]),"+f"(d[16]),"+f"(d[17]),"+f"(d[18]),"+f"(d[19]),"+f"(d[20]),"+f"(d[21]),"+f"(d[22]),"+f"(d[23]),"+f"(d[24]),"+f"(d[25]),"+f"(d[26]),"+f"(d[27]),"+f"(d[28]),"+f"(d[29]),"+f"(d[30]),"+f"(d[31])
    : "r"(a0), "r"(a1), "r"(a2), "r"(a3), "l"(db), "r"(sd));
}
__device__ __forceinline__ void wg_rs192t(float (&d)[96], uint32_t a0, uint32_t a1, uint32_t a2, uint32_t a3, uint64_t db, int sd) {
  asm volatile("{\n.reg .pred p;\nsetp.ne.b32 p, %101, 0;\n"
    "wgmma.mma_async.sync.aligned.m64n192k16.f32.bf16.bf16 {%0,%1,%2,%3,%4,%5,%6,%7,%8,%9,%10,%11,%12,%13,%14,%15,%16,%17,%18,%19,%20,%21,%22,%23,%24,%25,%26,%27,%28,%29,%30,%31,%32,%33,%34,%35,%36,%37,%38,%39,%40,%41,%42,%43,%44,%45,%46,%47,%48,%49,%50,%51,%52,%53,%54,%55,%56,%57,%58,%59,%60,%61,%62,%63,%64,%65,%66,%67,%68,%69,%70,%71,%72,%73,%74,%75,%76,%77,%78,%79,%80,%81,%82,%83,%84,%85,%86,%87,%88,%89,%90,%91,%92,%93,%94,%95}, {%96,%97,%98,%99}, %100, p, 1, 1, 1;\n}\n"
    : "+f"(d[0]),"+f"(d[1]),"+f"(d[2]),"+f"(d[3]),"+f"(d[4]),"+f"(d[5]),"+f"(d[6]),"+f"(d[7]),"+f"(d[8]),"+f"(d[9]),"+f"(d[10]),"+f"(d[11]),"+f"(d[12]),"+f"(d[13]),"+f"(d[14]),"+f"(d[15]),"+f"(d[16]),"+f"(d[17]),"+f"(d[18]),"+f"(d[19]),"+f"(d[20]),"+f"(d[21]),"+f"(d[22]),"+f"(d[23]),"+f"(d[24]),"+f"(d[25]),"+f"(d[26]),"+f"(d[27]),"+f"(d[28]),"+f"(d[29]),"+f"(d[30]),"+f"(d[31]),"+f"(d[32]),"+f"(d[33]),"+f"(d[34]),"+f"(d[35]),"+f"(d[36]),"+f"(d[37]),"+f"(d[38]),"+f"(d[39]),"+f"(d[40]),"+f"(d[41]),"+f"(d[42]),"+f"(d[43]),"+f"(d[44]),"+f"(d[45]),"+f"(d[46]),"+f"(d[47]),"+f"(d[48]),"+f"(d[49]),"+f"(d[50]),"+f"(d[51]),"+f"(d[52]),"+f"(d[53]),"+f"(d[54]),"+f"(d[55]),"+f"(d[56]),"+f"(d[57]),"+f"(d[58]),"+f"(d[59]),"+f"(d[60]),"+f"(d[61]),"+f"(d[62]),"+f"(d[63]),"+f"(d[64]),"+f"(d[65]),"+f"(d[66]),"+f"(d[67]),"+f"(d[68]),"+f"(d[69]),"+f"(d[70]),"+f"(d[71]),"+f"(d[72]),"+f"(d[73]),"+f"(d[74]),"+f"(d[75]),"+f"(d[76]),"+f"(d[77]),"+f"(d[78]),"+f"(d[79]),"+f"(d[80]),"+f"(d[81]),"+f"(d[82]),"+f"(d[83]),"+f"(d[84]),"+f"(d[85]),"+f"(d[86]),"+f"(d[87]),"+f"(d[88]),"+f"(d[89]),"+f"(d[90]),"+f"(d[91]),"+f"(d[92]),"+f"(d[93]),"+f"(d[94]),"+f"(d[95])
    : "r"(a0), "r"(a1), "r"(a2), "r"(a3), "l"(db), "r"(sd));
}
__device__ __forceinline__ void wg_ss160t(float (&d)[80], uint64_t da, uint64_t db, int sd) {
  asm volatile("{\n.reg .pred p;\nsetp.ne.b32 p, %82, 0;\n"
    "wgmma.mma_async.sync.aligned.m64n160k16.f32.bf16.bf16 {%0,%1,%2,%3,%4,%5,%6,%7,%8,%9,%10,%11,%12,%13,%14,%15,%16,%17,%18,%19,%20,%21,%22,%23,%24,%25,%26,%27,%28,%29,%30,%31,%32,%33,%34,%35,%36,%37,%38,%39,%40,%41,%42,%43,%44,%45,%46,%47,%48,%49,%50,%51,%52,%53,%54,%55,%56,%57,%58,%59,%60,%61,%62,%63,%64,%65,%66,%67,%68,%69,%70,%71,%72,%73,%74,%75,%76,%77,%78,%79}, %80, %81, p, 1, 1, 0, 1;\n}\n"
    : "+f"(d[0]),"+f"(d[1]),"+f"(d[2]),"+f"(d[3]),"+f"(d[4]),"+f"(d[5]),"+f"(d[6]),"+f"(d[7]),"+f"(d[8]),"+f"(d[9]),"+f"(d[10]),"+f"(d[11]),"+f"(d[12]),"+f"(d[13]),"+f"(d[14]),"+f"(d[15]),"+f"(d[16]),"+f"(d[17]),"+f"(d[18]),"+f"(d[19]),"+f"(d[20]),"+f"(d[21]),"+f"(d[22]),"+f"(d[23]),"+f"(d[24]),"+f"(d[25]),"+f"(d[26]),"+f"(d[27]),"+f"(d[28]),"+f"(d[29]),"+f"(d[30]),"+f"(d[31]),"+f"(d[32]),"+f"(d[33]),"+f"(d[34]),"+f"(d[35]),"+f"(d[36]),"+f"(d[37]),"+f"(d[38]),"+f"(d[39]),"+f"(d[40]),"+f"(d[41]),"+f"(d[42]),"+f"(d[43]),"+f"(d[44]),"+f"(d[45]),"+f"(d[46]),"+f"(d[47]),"+f"(d[48]),"+f"(d[49]),"+f"(d[50]),"+f"(d[51]),"+f"(d[52]),"+f"(d[53]),"+f"(d[54]),"+f"(d[55]),"+f"(d[56]),"+f"(d[57]),"+f"(d[58]),"+f"(d[59]),"+f"(d[60]),"+f"(d[61]),"+f"(d[62]),"+f"(d[63]),"+f"(d[64]),"+f"(d[65]),"+f"(d[66]),"+f"(d[67]),"+f"(d[68]),"+f"(d[69]),"+f"(d[70]),"+f"(d[71]),"+f"(d[72]),"+f"(d[73]),"+f"(d[74]),"+f"(d[75]),"+f"(d[76]),"+f"(d[77]),"+f"(d[78]),"+f"(d[79])
    : "l"(da), "l"(db), "r"(sd));
}
__device__ __forceinline__ void wg_ss80t(float (&d)[40], uint64_t da, uint64_t db, int sd) {
  asm volatile("{\n.reg .pred p;\nsetp.ne.b32 p, %42, 0;\n"
    "wgmma.mma_async.sync.aligned.m64n80k16.f32.bf16.bf16 {%0,%1,%2,%3,%4,%5,%6,%7,%8,%9,%10,%11,%12,%13,%14,%15,%16,%17,%18,%19,%20,%21,%22,%23,%24,%25,%26,%27,%28,%29,%30,%31,%32,%33,%34,%35,%36,%37,%38,%39}, %40, %41, p, 1, 1, 0, 1;\n}\n"
    : "+f"(d[0]),"+f"(d[1]),"+f"(d[2]),"+f"(d[3]),"+f"(d[4]),"+f"(d[5]),"+f"(d[6]),"+f"(d[7]),"+f"(d[8]),"+f"(d[9]),"+f"(d[10]),"+f"(d[11]),"+f"(d[12]),"+f"(d[13]),"+f"(d[14]),"+f"(d[15]),"+f"(d[16]),"+f"(d[17]),"+f"(d[18]),"+f"(d[19]),"+f"(d[20]),"+f"(d[21]),"+f"(d[22]),"+f"(d[23]),"+f"(d[24]),"+f"(d[25]),"+f"(d[26]),"+f"(d[27]),"+f"(d[28]),"+f"(d[29]),"+f"(d[30]),"+f"(d[31]),"+f"(d[32]),"+f"(d[33]),"+f"(d[34]),"+f"(d[35]),"+f"(d[36]),"+f"(d[37]),"+f"(d[38]),"+f"(d[39])
    : "l"(da), "l"(db), "r"(sd));
}

struct Maps { CUtensorMap x, xn, wq, k, v, wo, w3[2], xg, xe, out; };
struct Params {
  const __nv_bfloat16 *x, *wr, *wg, *wu, *wd, *k, *v;
  Scratch* s;
};

__device__ __forceinline__ void side_cta(const Params& p, int sc, unsigned epoch, float* sm) {
  const int tid = threadIdx.x, lane = tid & 31, warp = tid >> 5;
  int budget = WAIT_BUDGET;
  float* s_x = sm;
  float* s_red = sm + 1280;
  float* s_h = s_red + 6144;
  uint4* s_c = (uint4*)(s_h + 768);
  uint2* s_st = (uint2*)(s_c + 16);
  constexpr int DEPTH = 7, STEP = 4 * 6144;
  const uint32_t ring = smem_u32(s_st + 512) + tid * 16;
  const int cg = tid % 96, ks = tid / 96, cd = tid % 80, kd = tid / 80;
  const __nv_bfloat16* wp = (cg < 48 ? p.wg : p.wu) + (size_t)(ks * 160) * FF + sc * 384 + (cg % 48) * 8;
  int kf = 0, pitch = FF;
  uint32_t slot = ring;
  auto refill = [&]() {
    if (kf == 40) { wp = p.wd + (size_t)(sc * 384 + kd * 96) * DM + cd * 8; pitch = DM; }
    if (kf < (tid < 320 ? 64 : 40)) {
#pragma unroll
      for (int j = 0; j < 4; j++) asm volatile("cp.async.cg.shared.global.L2::cache_hint [%0], [%1], 16, %2;" ::"r"(slot + j * 6144), "l"(wp + j * pitch), "l"(POL_FIRST) : "memory");
    }
    asm volatile("cp.async.commit_group;" ::: "memory");
    wp += 4 * pitch; kf++;
    slot += STEP; if (slot == ring + DEPTH * STEP) slot = ring;
  };
  auto gemv = [&](int n, const float* x0, const float* x1, float* out) {
    float a[2][8] = {};
#pragma unroll 1
    for (int k = 0; k < n; k += 4) {
      refill();
      asm volatile("cp.async.wait_group %0;" ::"n"(DEPTH - 1) : "memory");
      const float4 f0 = *(const float4*)(x0 + k), f1 = *(const float4*)(x1 + k);
      const float y0[4] = {f0.x, f0.y, f0.z, f0.w}, y1[4] = {f1.x, f1.y, f1.z, f1.w};
#pragma unroll
      for (int j = 0; j < 4; j++) {
        const uint4 v = lds128(slot + j * 6144);
        const uint32_t u[4] = {v.x, v.y, v.z, v.w};
#pragma unroll
        for (int i = 0; i < 4; i++) {
          a[0][2 * i] += y0[j] * bf_lo(u[i]); a[0][2 * i + 1] += y0[j] * bf_hi(u[i]);
          a[1][2 * i] += y1[j] * bf_lo(u[i]); a[1][2 * i + 1] += y1[j] * bf_hi(u[i]);
        }
      }
    }
#pragma unroll
    for (int i = 0; i < 16; i++) out[(i >> 3) * 768 + (i & 7)] = a[i >> 3][i & 7];
  };
  auto load_row = [&](const __nv_bfloat16* r, uint32_t (&v)[10]) {
    const uint4 a = __ldg((const uint4*)r + lane), b = __ldg((const uint4*)r + 32 + lane);
    const uint2 c = __ldg((const uint2*)r + 128 + lane);
    v[0] = a.x; v[1] = a.y; v[2] = a.z; v[3] = a.w; v[4] = b.x; v[5] = b.y; v[6] = b.z; v[7] = b.w; v[8] = c.x; v[9] = c.y;
  };
  uint32_t wr[10], xb[3][10];
  load_row(p.wr, wr);
  auto stat2 = [&](int pair) {
    uint4 v;
    do v = ld_pkt((const uint4*)p.s->stat + pair); while ((((v.x ^ (epoch + 1)) | (v.z ^ (epoch + 1))) & 0xffff) && --budget >= 0);
    return make_uint4(__byte_perm(v.x, 0, 0x3232), v.y, __byte_perm(v.z, 0, 0x3232), v.w);
  };
  if (tid < 256) ((uint4*)s_st)[tid] = stat2(sc * 256 + tid);
  __syncthreads();
#pragma unroll
  for (int b = 0; b < 3; b++) load_row(p.x + (size_t)(sc * 512 + warp + 12 * b) * DM, xb[b]);
#pragma unroll 1
  for (int k = 0; k < DEPTH - 1; k++) refill();
  float v0 = -INFINITY, v1 = -INFINITY; int i0 = 0xfff, i1 = 0xfff;
  auto better = [](float a, int ia, float b, int ib) { return a > b || (a == b && ia < ib); };
  auto push = [&](float v, int i) {
    if (better(v, i, v0, i0)) { v1 = v0; i1 = i0; v0 = v; i0 = i; }
    else if (better(v, i, v1, i1)) { v1 = v; i1 = i; }
  };
  auto push2 = [&](uint4 c) { push(__uint_as_float(c.x), c.y & 0xfff); push(__uint_as_float(c.z), c.w & 0xfff); };
#pragma unroll 1
  for (int l3 = warp; l3 < 512; l3 += 36) {
#pragma unroll
    for (int b = 0; b < 3; b++) {
      const int lr = l3 + 12 * b;
      if (lr >= 512) break;
      const uint2 st = s_st[lr];
      uint32_t v[10];
#pragma unroll
      for (int i = 0; i < 10; i++) v[i] = hsub2(xb[b][i], st.x);
      if (lr + 36 < 512) load_row(p.x + (size_t)(sc * 512 + lr + 36) * DM, xb[b]);
      float r0 = 0.f, r1 = 0.f;
#pragma unroll
      for (int i = 0; i < 10; i++) {
        const uint32_t xn = pack_bf16(bf_lo(v[i]) * __uint_as_float(st.y), bf_hi(v[i]) * __uint_as_float(st.y));
        r0 = fmaf(bf_lo(xn), bf_lo(wr[i]), r0); r1 = fmaf(bf_hi(xn), bf_hi(wr[i]), r1);
      }
      r0 += r1;
#pragma unroll
      for (int o = 16; o > 0; o >>= 1) r0 += __shfl_xor_sync(~0u, r0, o);
      push(rbf(r0), sc * 512 + lr);
    }
  }
  if (lane == 0) s_c[warp] = make_uint4(__float_as_uint(v0), i0, __float_as_uint(v1), i1);
  __syncthreads();
#pragma unroll 1
  for (int w = 1; w < 12; w++) push2(s_c[(warp + w) % 12]);
  const uint32_t tag = (epoch + 1) << 12;
  if (tid == 0) st_pkt(p.s->cand + sc, __float_as_uint(v0), i0 | tag, __float_as_uint(v1), i1);
  {
    uint4 c;
    do c = ld_pkt(p.s->cand + (lane & 3)); while (((c.y ^ tag) >> 12) && --budget >= 0);
#pragma unroll 1
    for (int w = 1; w < 4; w++) { const int o = (sc + w) & 3; push2(make_uint4(__shfl_sync(~0u, c.x, o), __shfl_sync(~0u, c.y, o), __shfl_sync(~0u, c.z, o), __shfl_sync(~0u, c.w, o))); }
  }
  if (i0 >= SQ) i0 = 0;
  if (i1 >= SQ) i1 = (i0 == 0) ? 1 : 0;
  if (tid < 320) {
    const int row = tid < 160 ? i0 : i1;
    const uint2 u = __ldg((const uint2*)(p.x + (size_t)row * DM) + tid % 160);
    const uint4 st = stat2(row >> 1);
    const uint32_t mean2 = row & 1 ? st.z : st.x, d0 = hsub2(u.x, mean2), d1 = hsub2(u.y, mean2);
    const float inv = __uint_as_float(row & 1 ? st.w : st.y);
    ((float4*)s_x)[tid] = make_float4(rbf(bf_lo(d0) * inv), rbf(bf_hi(d0) * inv), rbf(bf_lo(d1) * inv), rbf(bf_hi(d1) * inv));
  }
  __syncthreads();
  gemv(160, s_x + ks * 160, s_x + DM + ks * 160, s_red + ks * 1536 + cg * 8);
  __syncthreads();
#pragma unroll
  for (int t = 0; t < 2; t++) {
    float g = 0.f, u = 0.f;
#pragma unroll
    for (int k = 0; k < 4; k++) { g += s_red[(k * 2 + t) * 768 + tid]; u += s_red[(k * 2 + t) * 768 + 384 + tid]; }
    s_h[t * 384 + tid] = rbf(rbf(silu_f(rbf(g))) * rbf(u));
  }
  __syncthreads();
  if (tid < 320) gemv(96, s_h + kd * 96, s_h + 384 + kd * 96, s_red + kd * 1536 + cd * 8);
  __syncthreads();
  const int o4 = tid + (tid < 160 ? 0 : 32);
  if (tid < 320) {
    const float4 *r = (const float4*)s_red + o4, a = r[0], b = r[384], c = r[768], d = r[1152];
    ((float4*)p.s->ffn)[sc * 320 + tid] = make_float4(a.x + b.x + c.x + d.x, a.y + b.y + c.y + d.y, a.z + b.z + c.z + d.z, a.w + b.w + c.w + d.w);
  }
  __syncthreads();
  if (tid == 0) { __threadfence(); s_c[0].x = (atomicAdd(&p.s->flag[FL_SIDE], 1u) & 3u) == 3u; __threadfence(); }
  __syncthreads();
  if (s_c[0].x) {
    if (tid < 320) {
      const float4 *r = (const float4*)p.s->ffn + tid, a = __ldcg(r), b = __ldcg(r + 320), c = __ldcg(r + 640), d = __ldcg(r + 960), x = ((float4*)s_x)[tid];
      const float rs = rbf(sigmoid_f(tid < 160 ? v0 : v1));
      auto gate = [&](float xn, float y) { return silu_f(rbf(xn + rbf(rbf(y) * rs))); };
      if (tid == 0) { p.s->sel[0] = i0; p.s->sel[1] = i1; }
      ((uint2*)p.s->gsel)[tid] =
          make_uint2(pack_bf16(gate(x.x, a.x + b.x + c.x + d.x), gate(x.y, a.y + b.y + c.y + d.y)), pack_bf16(gate(x.z, a.z + b.z + c.z + d.z), gate(x.w, a.w + b.w + c.w + d.w)));
    }
    __syncthreads();
    if (tid == 0) red_release(&p.s->flag[FL_FFN]);
  }
}

constexpr float SM_C = 0.07216878364870322f * 1.4426950408889634f;

#define LD 0
#define LS 3
__device__ __forceinline__ void ln_piece(const Params& p, uint32_t (&r)[48], int k, int row, int l16) {
  auto f = [&](int i) { return __uint_as_float(r[i]); };
  if (k == LD) {
#pragma unroll
    for (int i = 0; i < 5; i++) {
      const uint4 v = ldg_nc((const uint4*)(p.x + (size_t)row * DM) + i * 16 + l16);
      r[4 * i] = v.x; r[4 * i + 1] = v.y; r[4 * i + 2] = v.z; r[4 * i + 3] = v.w;
    }
    asm volatile("ld.relaxed.gpu.global.v2.u32 {%0,%1}, [%2];" : "=r"(r[20]), "=r"(r[21]) : "l"(&p.s->done));
  } else if (k == LS || k == LS + 1) {
    if (k == LS) { r[22] = __shfl_sync(~0u, r[0], 0, 16) << 16; r[23] = r[24] = 0; }
    float s0 = f(23), s1 = 0.f, q0 = f(24), q1 = 0.f;
#pragma unroll
    for (int i = 10 * (k - LS); i < 10 * (k - LS) + 10; i++) {
      const float a = bf_lo(r[i]) - f(22), b = bf_hi(r[i]) - f(22);
      s0 += a; s1 += b; q0 = fmaf(a, a, q0); q1 = fmaf(b, b, q1);
    }
    r[23] = __float_as_uint(s0 + s1); r[24] = __float_as_uint(q0 + q1);
  } else if (k == LS + 2) {
    float s0 = f(23), q0 = f(24);
#pragma unroll
    for (int o = 8; o > 0; o >>= 1) { s0 += __shfl_xor_sync(~0u, s0, o); q0 += __shfl_xor_sync(~0u, q0, o); }
    s0 *= 1.f / DM;
    const float mean = f(22) + s0, var = rbf(fmaxf(fmaf(q0, 1.f / DM, -s0 * s0), 0.f));
    float sd; asm("sqrt.approx.ftz.f32 %0, %1;" : "=f"(sd) : "f"(rbf(var + 1e-5f)));
    const float inv = rcp(rbf(sd));
    r[22] = pack_bf16(mean, mean); r[23] = __float_as_uint(inv * SM_C);
    const uint32_t tag = __funnelshift_r(r[20], r[21], 7) + 1;
    if (l16 == 0) st_pkt8(&p.s->stat[row], __byte_perm(tag, r[22], 0x7610), __float_as_uint(inv));
  } else if (k > LS + 2 && k <= LS + 5) {
#pragma unroll
    for (int j = 2 * (k - LS - 3); j < 2 * (k - LS - 3) + 2 && j < 5; j++) {
#pragma unroll
      for (int i = 4 * j; i < 4 * j + 4; i++) { const uint32_t d = hsub2(r[i], r[22]); r[i] = pack_bf16(bf_lo(d) * f(23), bf_hi(d) * f(23)); }
      *((uint4*)(p.s->xn + (size_t)row * DM) + j * 16 + l16) = make_uint4(r[4 * j], r[4 * j + 1], r[4 * j + 2], r[4 * j + 3]);
    }
  }
}

constexpr float SM_HI = 0x1p64f, SM_LO = 0x1p-64f;
__device__ __forceinline__ void exp_block(float (&s)[32], float& l0, float& l1, int from = 0, int to = 32) {
#pragma unroll
  for (int i = from; i < to; i++) { s[i] = ex2(s[i]); if (i & 2) l1 += s[i]; else l0 += s[i]; }
}
__device__ __forceinline__ float quad_sum(float v) { v += __shfl_xor_sync(~0u, v, 1); return v + __shfl_xor_sync(~0u, v, 2); }
__device__ __forceinline__ float quad_max(float v) { v = fmaxf(v, __shfl_xor_sync(~0u, v, 1)); return fmaxf(v, __shfl_xor_sync(~0u, v, 2)); }
__device__ __noinline__ void safe_head(const uint32_t* kp, const uint32_t* vp, uint4* io) {
  uint32_t fq[48];
#pragma unroll
  for (int i = 0; i < 12; i++) { const uint4 v = io[(i >> 1) * 512 + (i & 1) * 32]; fq[4 * i] = v.x; fq[4 * i + 1] = v.y; fq[4 * i + 2] = v.z; fq[4 * i + 3] = v.w; }
  float m0 = -INFINITY, m1 = -INFINITY;
#pragma unroll 1
  for (int pass = 0; pass < 3; pass++) {
    float o[48] = {}, l0 = 0.f, l1 = 0.f;
#pragma unroll 1
    for (int n = 0; n < 64; n++) {
      const uint32_t *kr = kp + n * (8 * DH / 2), *vr = vp + n * (8 * DH / 2) + (pass - 1) * 48;
      float d[4] = {};
#pragma unroll
      for (int t = 0; t < 12; t++)
        asm volatile("mma.sync.aligned.m16n8k16.row.col.f32.bf16.bf16.f32 {%0,%1,%2,%3}, {%4,%5,%6,%7}, {%8,%9}, {%0,%1,%2,%3};"
                     : "+f"(d[0]), "+f"(d[1]), "+f"(d[2]), "+f"(d[3])
                     : "r"(fq[4 * t]), "r"(fq[4 * t + 1]), "r"(fq[4 * t + 2]), "r"(fq[4 * t + 3]), "r"(__ldg(kr + 8 * t)), "r"(__ldg(kr + 8 * t + 4)));
      if (pass == 0) { m0 = fmaxf(m0, fmaxf(d[0], d[1])); m1 = fmaxf(m1, fmaxf(d[2], d[3])); continue; }
      d[0] = ex2(d[0] - m0); d[1] = ex2(d[1] - m0); d[2] = ex2(d[2] - m1); d[3] = ex2(d[3] - m1);
      l0 += d[0] + d[1]; l1 += d[2] + d[3];
      const uint32_t p0 = pack_bf16(d[0], d[1]), p1 = pack_bf16(d[2], d[3]);
#pragma unroll
      for (int c = 0; c < 12; c++)
        asm volatile("{\n.reg .b32 t;\nmovmatrix.sync.aligned.m8n8.trans.b16 t, %6;\n"
                     "mma.sync.aligned.m16n8k8.row.col.f32.bf16.bf16.f32 {%0,%1,%2,%3}, {%4,%5}, {t}, {%0,%1,%2,%3};\n}\n"
                     : "+f"(o[4 * c]), "+f"(o[4 * c + 1]), "+f"(o[4 * c + 2]), "+f"(o[4 * c + 3]) : "r"(p0), "r"(p1), "r"(__ldg(vr + 4 * c)));
    }
    if (pass == 0) { m0 = quad_max(m0); m1 = quad_max(m1); continue; }
    l0 = rcp(quad_sum(l0)); l1 = rcp(quad_sum(l1));
#pragma unroll
    for (int i = 0; i < 6; i++) {
      const float* v = o + 16 * (i >> 1) + 2 * (i & 1);
      const float r = i & 1 ? l1 : l0;
      io[(3 * (pass - 1) + (i >> 1)) * 512 + (i & 1) * 32] =
          make_uint4(pack_bf16(v[0] * r, v[1] * r), pack_bf16(v[4] * r, v[5] * r), pack_bf16(v[8] * r, v[9] * r), pack_bf16(v[12] * r, v[13] * r));
    }
  }
}

#define CVG 48
#define NE 8
#define PS1 8
#define CSW 0
#define D0 2
#define ROT 2
#define PW 0
#define TURN 0x1f8
#define TK 3
#define COR 1
#define LQ 6
__device__ __forceinline__ constexpr int end_stage(int n) { return n < 4 ? n : n < LQ ? n - 4 : n == LQ ? 4 : n % 5; }
#define Q2N 1
#define SWN 12
#define SCH 0
__device__ __forceinline__ constexpr int sent(int n) {
  constexpr int t[4][15] = {{0, 2, 4, 5, 5, 6, 7, 8,  9, 10, 11, 12, 13, 14, 15},
                            {0, 2, 4, 5, 5, 6, 7, 8,  9, 10, 12, 13, 14, 15, 15},
                            {0, 2, 4, 5, 5, 7, 8, 9, 10, 10, 12, 14, 15, 15, 15},
                            {0, 2, 4, 5, 5, 7, 8, 9, 10, 10, 13, 15, 15, 15, 15}};
  return n < LQ + 2 ? 0 : LQ == 6 && n == 8 ? 3 : t[SCH][n - 6];
}
template <int N> struct IntC { static constexpr int value = N; };
template <int N, int I = 0, class F> __device__ __forceinline__ void static_for(F&& f) { if constexpr (I < N) { f(IntC<I>{}); static_for<N, I + 1>(f); } }

extern __shared__ __align__(1024) uint8_t smem_raw[];
constexpr uint32_t EA = 160, EB = 184;
#define SMEM_LAYOUT                                                                                                          \
  [[maybe_unused]] const uint32_t sb = smem_u32(smem_raw), bar_a = sb + OFF_M, bar_b = bar_a + 40, bar_x = bar_a + 88,      \
      bar_u = bar_a + 96, bar_e = bar_a + 104, bar_o = bar_a + 200, bar_w = bar_a + 208, bar_z = bar_a + 288,                \
      bar_s = bar_a + 296, bar_d = bar_a + 304, s_stat = bar_a + 512, s_sel = s_stat + 1024;

__device__ __forceinline__ int cluster_role() {
  uint32_t t, n;
  asm("mov.u32 %0, %%smid;" : "=r"(t)); asm("mov.u32 %0, %%nsmid;" : "=r"(n));
  t >>= 1;
  return n != 132 ? blockIdx.x >> 1 : t < 32 ? t : t < 60 ? t + 1 + (((t - 32) * 37) >> 8) : t < 62 ? t + 4 : (t - 58) * 8;
}

__device__ __forceinline__ int k_block(int t, int hg) {
  const int i = (t * 11) >> 5;
  return ((i < 6 ? (hg & 6) + (i & 1) : hg ^ (i & 1)) * 4 + (i >> 1)) * 6 + (t == 3 * i ? 4 : 2 * (t - 3 * i) - 2);
}

__device__ __noinline__ int errands(Scratch* s, const Maps& m, int qt, int hg, int warp, uint32_t tag, int budget) {
  SMEM_LAYOUT
  const int lane = threadIdx.x & 31, kq = hg >> 1, nh = hg & 1;
  if (warp == 1) {
#pragma unroll 1
    for (int u = 0; u < 5; u++) {
      mbar_wait(bar_o, u & 1);
      if (lane == 0) red_release(&s->flag[u ? FL_O + (qt * 8 + hg) * 8 : FL_XN + qt * 32]);
      __syncwarp();
    }
  } else if (warp == 2) {
    mbar_wait(bar_x, 0, budget);
    while ((int)(ld_acquire(&s->flag[FL_FFN]) - tag) < 0 && --budget >= 0) {}
    if (lane < 21) {
      const uint4 v = __ldcg(lane ? (const uint4*)(s->gsel + (lane > 10 ? DM - 80 : 0) + nh * 320 + kq * 80) + lane - 1 : (const uint4*)s->sel);
      asm volatile("st.shared.v4.u32 [%0], {%1,%2,%3,%4};" ::"r"(s_sel + 16 * lane), "r"(v.x), "r"(v.y), "r"(v.z), "r"(v.w) : "memory");
    }
    __syncwarp();
    if (lane == 0) { mbar_arrive(bar_u); asm volatile("red.relaxed.gpu.global.add.u64 [%0], 1;" ::"l"(&s->done) : "memory"); }
    while ((int)(ld_acquire(&s->flag[FL_RD + (qt * 8 + (hg ^ 1)) * 8]) - tag) < 0 && --budget >= 0) {}
    if (lane < 3) mbar_arrive(bar_z);
  } else {
    wait_flag(&s->flag[FL_XN + qt * 32], tag * 8);
    fence_proxy_async();
    mbar_wait(bar_a + EA + 32, 1);
    uint32_t a8 = 0, pha = 1;
    const int kb = (qt * 192 + k_block(lane, hg)) * 512;
#pragma unroll 1
    for (int n = 0; n < 54; n++) {
      const int t = n - 30, ko = __shfl_sync(~0u, kb, t);
      if (t == 0 || t == 18) {
        wait_flag(&s->flag[FL_O + (qt * 8 + (t ? 2 * kq + (lane & 1) : lane & 7)) * 8], tag * 4 - (t ? 0 : 1));
        fence_proxy_async();
      }
      mbar_wait(bar_a + EA + a8, pha);
      const uint32_t fb = bar_a + a8, dst = sb + a8 * (TA >> 3);
      if (elect()) {
        if (t >= 0) {
          mbar_expect_tx(fb, TA);
          bulk_load(dst, s->o + ko, TA, fb);
          if (t == 8) {
            mbar_expect_tx(bar_x, 6 * 3840);
#pragma unroll 1
            for (int e = 0; e < 6; e++) tma2d(sb + OFF_B + TW + e * TB, &m.xg, nh * 320 + kq * 80, qt * 128 + e * 24, bar_x);
            asm volatile("prefetch.tensormap [%0];\nprefetch.tensormap [%1];\nprefetch.tensormap [%2];\nprefetch.tensormap [%3];"
                         ::"l"(m.w3), "l"(m.w3 + 1), "l"(&m.xe), "l"(&m.out) : "memory");
          }
          if (t == 22) asm volatile("red.relaxed.gpu.global.add.u32 [%0], 1;" ::"l"(&s->flag[FL_RD + (qt * 8 + hg) * 8]) : "memory");
        } else if (n >= 10 && pha) mbar_arrive(fb);
        else { mbar_expect_tx(fb, TA); tma2d(dst, &m.xn, 8 * a8 + (pha || (n >= 15 && n < 20) ? 0 : 320), qt * 128, fb); }
      }
      a8 += 8; if (a8 == 40) { a8 = 0; pha ^= 1; }
    }
    if (lane < 3) mbar_arrive(bar_z);
  }
  return budget;
}

__global__ void __launch_bounds__(384, 1) __cluster_dims__(2, 1, 1)
fused_kernel(const Params p, const __grid_constant__ Maps m) {
  SMEM_LAYOUT
  const int wi = __shfl_sync(~0u, threadIdx.x >> 5, 0), wg = wi >> 2;
  const int lane = threadIdx.x & 31;
  const int cl = cluster_role();
  const int rank = blockIdx.x & 1;

  if (cl >= 64) {
    const unsigned epoch = (unsigned)(__ldcg(&p.s->done) >> 7);
    side_cta(p, 2 * cl + rank - 128, epoch, (float*)smem_raw);
    return;
  }
  const int qt = (cl & 7) * 2 + rank, hg = cl >> 3;
  const int kq = hg >> 1, nh = hg & 1;

  const int s0 = (5 * ((qt >> 1) & ~(8 / ROT - 1))) >> 2, kg0 = 10 * (qt >> 1) - 8 * s0;
  if (elect()) {
    const int c = (int)(0x5ff7700000ull >> (4 * wi) & 15) + 1;
    for (int i = 0; i < 4; i++) mbar_init(bar_a + 32 * wi + 8 * i, c);
    asm volatile("fence.mbarrier_init.release.cluster;" ::: "memory");
  }
  __syncwarp();
  cluster_arrive();
  if (wi < 2 && elect()) {
    if (wi) {
      if (!PW) asm volatile("prefetch.tensormap [%0];" ::"l"(&m.wq) : "memory");
      mbar_expect_tx(bar_b, TB); mbar_expect_tx(bar_b + 8, TB);
      for (int i = 0; i < 2 * PW; i++)
        asm volatile("cp.async.bulk.tensor.4d.shared::cluster.global.mbarrier::complete_tx::bytes.L2::cache_hint [%0], [%1, {%3, %3, %4, %5}], [%2], %6;"
                     ::"r"(sb + OFF_B + i * (TB / 2)), "l"(&m.wq), "r"(bar_b + 8 * (i >> 1)), "r"(0), "r"(12 * hg), "r"(8 * s0 + 4 * i), "l"(POL_FIRST) : "memory");
    }
    else for (int i = 0; i < 2; i++) { mbar_expect_tx(bar_a + 8 * i, TA); tma2d(sb + i * TA, &m.x, 64 * (s0 + i), qt * 128, bar_a + 8 * i); }
  }
  __syncwarp();
  cluster_wait();
  if (wi == 1 && elect())
    for (int i = PW; i < 2; i++) tma4d_mc(sb + OFF_B + i * TB + rank * (TB / 2), &m.wq, 12 * hg, 8 * (s0 + i) + 4 * rank, bar_b + 8 * i);
  if (wg > 0) {
    const int w = wg - 1;
    const int cw = wi - 4;
    asm volatile("setmaxnreg.inc.sync.aligned.u32 232;");
    uint32_t fr[48];
    reg_fence(fr);
    auto ln_row = [&]() { int v = qt * 128 + hg * 16 + cw * 2 + (lane >> 4); asm volatile("" : "+r"(v)); return v; };
    uint32_t rel_addr;
    asm volatile("mapa.shared::cluster.u32 %0, %1, %2;" : "=r"(rel_addr) : "r"(bar_b + EB), "r"(lane & 1));
    auto rel_a = [&](uint32_t o8) { if (lane == 0) mbar_arrive(bar_a + EA + o8); };
    auto rel_b = [&](uint32_t o8) { if (lane < 2) mbar_arrive_cluster(rel_addr + o8); };
    uint32_t b8 = 0, phb = 0;
    auto next_pair = [&]() { b8 += 16; if (b8 == 48) { b8 = 0; phb ^= 1; } };
    const int g = lane >> 2, q = lane & 3;
    constexpr uint64_t HI_A = desc_hi(16, 1024, 1);
    constexpr uint64_t HI_W = desc_hi(1024, 3072, 1);
    constexpr uint64_t HI_O = desc_hi(2048, 512, 2);
    if (w == 1) asm volatile("bar.arrive 1, 256;" ::: "memory");

    uint32_t zero; asm volatile("mov.u32 %0, %%tid.y;" : "=r"(zero));
    float acc[96];
    uint4* optr = p.s->o + (size_t)(qt * 192 + hg * 24) * 512 + (cw * 16 + g) * 4 + (q ^ ((g >> 1) & 3));
    uint32_t rl[4];
    auto store_o = [&](int pp) {
#pragma unroll
      for (int i = (12 * pp + 8) / 9; i < (12 * (pp + 1) + 8) / 9; i++) {
#pragma unroll
        for (int k = 4 * i; k < 4 * i + 4; k++)
          asm volatile("{\n.reg .b32 t;\nmul.rn.bf16x2 t, %0, %2;\nfma.rn.bf16x2 %0, %0, %1, t;\n}\n" : "+r"(fr[k]) : "r"(rl[i & 1]), "r"(rl[2 + (i & 1)]));
        fr[4 * i] &= ~1u;
        optr[(i >> 1) * 512 + (i & 1) * 32] = make_uint4(fr[4 * i], fr[4 * i + 1], fr[4 * i + 2], fr[4 * i + 3]);
      }
      if (pp == 8) optr += 6 * 512;
    };
    auto fresh = [&]() { uint32_t v = sb; asm volatile("" : "+r"(v)); return v; };
    reg_fence(rl);

#pragma unroll 1
    for (int u = 0; u < 4; u++) {
      const uint32_t sq = fresh();
      const uint64_t dA = mkdesc(sq + w * 8192, HI_A), dB0 = mkdesc(sq + OFF_B, HI_W);
      uint32_t pb8 = 0;
#pragma unroll
      for (int s = 0; s < 10; s++) {
        const uint32_t o8 = b8 + 8 * (s & 1);
        const uint64_t dW = dB0 + o8 * (TB >> 7);
        mbar_wait(bar_a + 8 * (s % 5), s / 5);
        mbar_wait(bar_b + o8, phb);
        if (s == 9 || ((TURN >> s & 1) && u == 0)) asm volatile("bar.sync %0, 256;" ::"r"(1 + w) : "memory");
        WG_FENCE();
#pragma unroll
        for (int kk = 0; kk < 4; kk++) {
          wg_ss192t(acc, dA + ((s % 5) * (TA >> 4) + kk * 2), dW + kk * 384, kk != 0 || s != 0);
          if (kk == TK && (TURN >> s & 1) && u == 0) asm volatile("bar.arrive %0, 256;" ::"r"(2 - w) : "memory");
        }
        WG_COMMIT();
        if (s == 9 && (!COR || u > 0)) asm volatile("bar.arrive %0, 256;" ::"r"(2 - w) : "memory");
        if (s > 0) { WG_WAIT(1); rel_a(8 * ((s - 1) % 5)); rel_b(pb8); }
        if (s < 9) { if (u > 0) store_o(s); else ln_piece(p, fr, s, ln_row(), lane & 15); }
        if (s == 8) { __syncwarp(); if (lane == 0) mbar_arrive(bar_o); }
        pb8 = o8;
        if (s & 1) next_pair();
      }
      if (u == 0) {
        mbar_wait(bar_s, 0);
        const uint2 s0 = lds64(s_stat + (cw * 16 + g) * 8), s1 = lds64(s_stat + 64 + (cw * 16 + g) * 8);
        const uint32_t msk = q == 0 ? 0xffffffffu : q == 1 ? 0xffffu : 0u;
        const float c0 = SM_C * __uint_as_float(s0.y), c1 = SM_C * __uint_as_float(s1.y);
        uint32_t am[4] = {(s0.x ^ 0x80008000u) & msk, (s1.x ^ 0x80008000u) & msk, 0, 0};
        reg_fence(am);
        WG_FENCE();
        wg_rs192t(acc, am[0], am[1], am[2], am[3], mkdesc(sb, desc_hi(1024, 0, 1)), 1);
        WG_COMMIT();
        if (COR) asm volatile("bar.arrive %0, 256;" ::"r"(2 - w) : "memory");
        WG_WAIT(0);
        reg_fence(acc);
#pragma unroll
        for (int i = 0; i < 24; i++) { acc[4 * i] *= c0; acc[4 * i + 1] *= c0; acc[4 * i + 2] *= c1; acc[4 * i + 3] *= c1; }
      } else { WG_WAIT(0); reg_fence(acc); }
      rel_b(pb8);
      rel_a(32);
      auto pack_q = [&](int from, int to) {
#pragma unroll
        for (int i = from; i < to; i++) { fr[i] = pack_bf16(acc[2 * i], acc[2 * i + 1]); asm volatile("" : "+r"(fr[i])::"memory"); }
      };
      pack_q(0, CVG);
      float sc[32], l0 = 0.f, l1 = 0.f;
      uint32_t pf[16], k8;
      auto pack_p = [&](const float (&s_)[32], int from = 0, int to = 16) {
#pragma unroll
        for (int i = from; i < to; i++) pf[i] = pack_bf16(s_[2 * i], s_[2 * i + 1]);
      };
      auto scores = [&](int j, int pass = 11) {
        k8 = b8 + 8;
        mbar_wait(bar_b + k8, phb);
        next_pair();
        mbar_wait(bar_b + b8, phb);
        const uint64_t dk = mkdesc(sb + OFF_B, HI_W) + k8 * (TB >> 7);
        asm volatile("bar.sync %0, 256;" ::"r"(1 + w) : "memory");
        WG_FENCE();
#pragma unroll
        for (int t = 0; t < 12; t++) {
          wg_rs64(sc, fr[4 * t], fr[4 * t + 1], fr[4 * t + 2], fr[4 * t + 3], dk + (t >> 2) * 64 + (t & 3) * 2, t != 0);
          if (t == 11) WG_COMMIT();
          if (t == pass) asm volatile("bar.arrive %0, 256;" ::"r"(2 - w) : "memory");
        }
      };
      auto pv = [&](int add) {
        const uint64_t dv = mkdesc(sb + OFF_B, HI_W) + b8 * (TB >> 7);
#pragma unroll
        for (int kk = 0; kk < 4; kk++) wg_rs192t(acc, pf[4 * kk], pf[4 * kk + 1], pf[4 * kk + 2], pf[4 * kk + 3], dv + kk * 384, kk != 0 || add);
        WG_COMMIT();
      };
      auto finish = [&]() {
        WG_WAIT(1);
        reg_fence(sc);
        exp_block(sc, l0, l1);
        rel_b(k8 + (__float_as_uint(l0) & __float_as_uint(l1) & zero));
        WG_WAIT(0);
        reg_fence(acc); reg_fence(pf);
        rel_b(b8);
        pack_p(sc);
      };
      {
        mbar_wait(bar_b + b8, phb);
        const uint64_t dk = mkdesc(sb + OFF_B, HI_W) + b8 * (TB >> 7);
        asm volatile("bar.sync %0, 256;" ::"r"(1 + w) : "memory");
#pragma unroll
        for (int t = 0; t < 12; t++) {
          if (t && (4 * t) % CVG == 0) pack_q(4 * t, 4 * t + CVG);
          if ((4 * t) % CVG == 0) WG_FENCE();
          wg_rs64(sc, fr[4 * t], fr[4 * t + 1], fr[4 * t + 2], fr[4 * t + 3], dk + (t >> 2) * 64 + (t & 3) * 2, t != 0);
          if (t == 7) asm volatile("bar.arrive %0, 256;" ::"r"(2 - w) : "memory");
        }
        WG_COMMIT();
        WG_WAIT(0);
        reg_fence(sc);
        float s0[32];
#pragma unroll
        for (int i = 0; i < 32; i++) s0[i] = i < NE ? sc[i] : __uint_as_float(__float_as_uint(sc[i]) ^ zero);
        exp_block(s0, l0, l1, 0, NE);
        pack_p(s0, 0, NE / 2);
#pragma unroll
        for (int i = NE; i < 32; i++) asm volatile("" : "+f"(s0[i])::"memory");
#pragma unroll
        for (int i = 0; i < NE / 2; i++) asm volatile("" : "+r"(pf[i])::"memory");
        rel_b(b8);
        scores(1, PS1);
        const uint32_t z = lds32(s_stat) & zero;
#pragma unroll
        for (int i = NE; i < 32; i++) {
          asm("{\n.reg .pred p;\nsetp.eq.u32 p, %1, 0;\n@p ex2.approx.ftz.f32 %0, %0;\n}\n" : "+f"(s0[i]) : "r"(z));
          if (i & 2) l1 += s0[i]; else l0 += s0[i];
        }
        pack_p(s0, NE / 2, 16);
        reg_fence(pf);
        WG_FENCE();
        pv(0);
        finish();
      }
#pragma unroll 1
      for (int j = NE < 32 ? 2 : 1; j < 8; j++) { scores(j); pv(j > 1); finish(); }
      const uint32_t v8 = b8 + 8;
      mbar_wait(bar_b + v8, phb);
      next_pair();
      {
        const uint64_t dv = mkdesc(sb + OFF_B, HI_W) + v8 * (TB >> 7);
        asm volatile("bar.sync %0, 256;" ::"r"(1 + w) : "memory");
        WG_FENCE();
#pragma unroll
        for (int kk = 0; kk < 4; kk++) {
          wg_rs192t(acc, pf[4 * kk], pf[4 * kk + 1], pf[4 * kk + 2], pf[4 * kk + 3], dv + kk * 384, 1);
          if (kk == 1 && (u < 3 || w == 0)) asm volatile("bar.arrive %0, 256;" ::"r"(2 - w) : "memory");
        }
        WG_COMMIT();
      }
      l0 = quad_sum(l0); l1 = quad_sum(l1);
      const bool unsafe = __any_sync(~0u, !(l0 >= SM_LO && l1 >= SM_LO && l0 + l1 <= SM_HI));
      l0 = rcp(l0); l1 = rcp(l1);
      rl[0] = pack_bf16(l0, l0); rl[1] = pack_bf16(l1, l1);
      l0 -= bf_lo(rl[0]); l1 -= bf_lo(rl[1]);
      rl[2] = pack_bf16(l0, l0); rl[3] = pack_bf16(l1, l1);
      WG_WAIT(0);
      reg_fence(acc);
      rel_b(v8);
      if (__builtin_expect(unsafe, 0)) {
        int o = hg * 4 + u; asm volatile("" : "+r"(o));
        o = (o * SKC + (SKC - WIN) + g) * (DH / 2) + q;
#pragma unroll
        for (int i = 0; i < 12; i++) optr[(i >> 1) * 512 + (i & 1) * 32] = make_uint4(fr[4 * i], fr[4 * i + 1], fr[4 * i + 2], fr[4 * i + 3]);
        safe_head((const uint32_t*)p.k + o, (const uint32_t*)p.v + o, optr);
#pragma unroll
        for (int i = 0; i < 12; i++) { const uint4 v = optr[(i >> 1) * 512 + (i & 1) * 32]; fr[4 * i] = v.x; fr[4 * i + 1] = v.y; fr[4 * i + 2] = v.z; fr[4 * i + 3] = v.w; }
        rl[0] = rl[1] = 0x3f803f80u; rl[2] = rl[3] = 0;
      } else {
#pragma unroll
        for (int i = 0; i < 24; i++) {
          fr[8 * (i >> 2) + (i & 3)] = pack_bf16(acc[4 * i], acc[4 * i + 1]);
          fr[8 * (i >> 2) + 4 + (i & 3)] = pack_bf16(acc[4 * i + 2], acc[4 * i + 3]);
        }
      }
    }

    float aF[80], aS[80];
    uint32_t pha = 0, a8 = 0, pa8 = 0, pb8 = 0;
#pragma unroll 1
    for (int s = 0; s < 19; s++) {
      const uint64_t d0 = mkdesc(sb, HI_O), dO = d0 + (a8 * (TA >> 7) + w * 256), dB = d0 + ((OFF_B >> 4) + b8 * (TB >> 7));
      mbar_wait(bar_a + a8, pha);
      mbar_wait(bar_b + b8, phb);
      WG_FENCE();
#pragma unroll
      for (int kk = 0; kk < 4; kk++) wg_ss160t(aF, dO + ((kk >> 1) * 512 + (kk & 1) * 2), dB + ((kk >> 1) * 640 + (kk & 1) * 64), kk != 0 || s != 0);
      WG_COMMIT();
      mbar_wait(bar_b + b8 + 8, phb);
      WG_WAIT(1);
      if (s > 0) { rel_a(pa8); rel_b(pb8 + 8); }
      WG_FENCE();
#pragma unroll
      for (int kk = 0; kk < 4; kk++) wg_ss160t(aS, dO + ((kk >> 1) * 512 + (kk & 1) * 2), dB + ((TB >> 4) + (kk >> 1) * 640 + (kk & 1) * 64), kk != 0 || s != 0);
      WG_COMMIT();
      if (s < 9) {
#pragma unroll
        for (int pp = 0; pp < 9; pp++) if (s == pp) store_o(pp);
        if (s == 8) { __syncwarp(); if (lane == 0) mbar_arrive(bar_o); }
      } else if (s < 15) {
        const int b = 2 * cw + ((lane >> 3) & 1);
        uint32_t ga = sb + OFF_B + TW + ((b * 11) >> 5) * (TB - 3840) + b * 1280 + (lane & 7) * 160 + (lane >> 4) * 16;
        if (s < 14) {
          mbar_wait(bar_x, 0);
          ga += 32 * (s - 9);
          ldsm4(ga, fr);
#pragma unroll
          for (int i = 0; i < 4; i++) {
            const uint2 st = lds64(s_stat + (cw * 16 + g + 8 * (i & 1)) * 8);
            const uint32_t d = hsub2(fr[i], st.x), xn = pack_bf16(bf_lo(d) * __uint_as_float(st.y), bf_hi(d) * __uint_as_float(st.y));
            fr[i] = pack_bf16(silu_f(bf_lo(xn)), silu_f(bf_hi(xn)));
          }
          stsm4(ga, fr);
        } else {
          mbar_wait(bar_u, 0);
          const uint2 sel = lds64(s_sel);
          const uint32_t row = qt * 128 + cw * 16 + (lane & 15);
          if (row == sel.x || row == sel.y) ga = s_sel + 16 + (row == sel.y ? 160 : 0) + (lane >> 4) * 16;
#pragma unroll
          for (int k = 0; k < 5; k++) ldsm4(ga + 32 * k, fr + 4 * k);
        }
      }
      WG_WAIT(1);
      rel_b(b8);
      pa8 = a8; a8 += 8; if (a8 == 40) { a8 = 0; pha ^= 1; }
      pb8 = b8; next_pair();
    }
    const int t128 = threadIdx.x & 127;
    uint4* const xbase = p.s->o + (size_t)(qt * 192 + nh * 24 + 10) * 512 + w * 640 + t128;
    uint4* const dst = xbase + kq * (48 * 512);
    float q1[40], q2[40], oth[40], own[40];
    auto take = [&](float (&x)[40], const float* a) {
#pragma unroll
      for (int k = 0; k < 40; k++) x[k] = __uint_as_float(__float_as_uint(a[k]) ^ zero);
      reg_fence(x);
    };
    reg_fence(aF);
    take(q1, aF);
    auto fa = [&](int i) { return mbar_try(bar_a + 8 * ((4 + i) % 5), i == 0); };
    auto fb = [&](int e) { return mbar_try(bar_b + 8 * (e % 6), (e / 6) & 1); };
    auto send = [&](int m) {
      const float* v = (m < 5 ? q1 : m < 10 ? q2 : oth) + 8 * (m % 5);
      st_pkt(dst + (m / 5) * 1280 + (m % 5) * 128, pack_bf16(v[0], v[1]) | 1, pack_bf16(v[2], v[3]), pack_bf16(v[4], v[5]), pack_bf16(v[6], v[7]));
    };
    static_for<20>([&](auto n_) {
      constexpr int n = n_.value, i = end_stage(n), e = 142 + n / 2, qi = n == 4 ? 1 : n == LQ ? 0 : n / 5;
      float (&acc_)[40] = qi == 0 ? q1 : qi == 1 ? q2 : qi == 2 ? oth : own;
      if (n == 0) while (!(fa(0) & fa(1) & fb(142) & fb(143))) {}
      if (n == 2) while (!(fa(2) & fa(3) & fb(144))) {}
      if (n == LQ) while (!(fa(4) & fb(145) & fb(146) & mbar_try(bar_z, 0))) {}
      if (n == 10) while (!(fb(147) & fb(148) & fb(149))) {}
      const uint64_t d0 = mkdesc(fresh(), HI_O);
      WG_FENCE();
#pragma unroll
      for (int kk = 0; kk < 4; kk++)
        wg_ss80t(acc_, d0 + w * 256 + (((4 + i) % 5) * (TA >> 4) + (kk >> 1) * 512 + (kk & 1) * 2),
                 d0 + ((OFF_B >> 4) + (e % 6) * (TB >> 4) + (n & 1) * 768 + (kk >> 1) * 384 + (kk & 1) * 64), 1);
      WG_COMMIT();
      if ((!(n & 1) && n <= 16) || n == 15 || n == LQ + 1) WG_WAIT(1);
      if (n == 0) rel_a(24);
      if (!(n & 1) && n <= 10) rel_b(8 * ((e - 1) % 6));
      if (n == Q2N) take(q2, aF + 40);
      if (n == 10) cluster_arrive();
      if (n == 12 || n == 14 || n == 16) rel_a(4u * n - 48);
      if (n == LQ + 1) reg_fence(q1);
      if (n == 10) reg_fence(q2);
      if (n == 15) reg_fence(oth);
      if (n == 15) while (!(fb(150) & fb(151))) {}
      static_for<sent(n + 1) - sent(n)>([&](auto k_) { send(sent(n) + k_.value); });
      if (n == 8) {
        reg_fence(aS);
#pragma unroll
        for (int k = 0; k < 40; k++) oth[k] = kq & 1 ? aS[k] : aS[40 + k];
        reg_fence(oth);
      }
      if (n == SWN) {
        reg_fence(aS);
#pragma unroll
        for (int k = 0; k < 40; k++) own[k] = kq & 1 ? aS[40 + k] : aS[k];
        reg_fence(own);
      }
    });
    uint32_t xr[20];
    const uint32_t xs = sb + OFF_B + 2 * TB + cw * 2560, xa = xs + (lane & 15) * 160 + (lane >> 4) * 16;
    mbar_wait(bar_b + 16, 1);
#pragma unroll
    for (int k = 0; k < 5; k++) ldsm4(xa + 32 * k, xr + 4 * k);
    {
      auto fetch = [&](int e, uint4 (&v)[5]) {
        mbar_wait(bar_e + 16 * e + 8 * w, 0);
#pragma unroll
        for (int i = 0; i < 5; i++) v[i] = lds128(sb + OFF_B + (3 + e) * TB + (w * 640 + i * 128 + t128) * 16);
      };
      auto add = [&](int e, uint4 (&v)[5]) {
        while (!(v[0].x & v[1].x & v[2].x & v[3].x & v[4].x & 1)) {
#pragma unroll
          for (int i = 0; i < 5; i++) v[i] = ld_pkt(xbase + (kq ^ ((0x132 >> (4 * e)) & 3)) * (48 * 512) + (e < 2 ? kq & 1 : 2) * 1280 + i * 128);
        }
#pragma unroll
        for (int i = 0; i < 5; i++) {
          float* o = own + 8 * i;
          o[0] += bf_lo(v[i].x); o[1] += bf_hi(v[i].x); o[2] += bf_lo(v[i].y); o[3] += bf_hi(v[i].y);
          o[4] += bf_lo(v[i].z); o[5] += bf_hi(v[i].z); o[6] += bf_lo(v[i].w); o[7] += bf_hi(v[i].w);
        }
      };
      WG_WAIT(0);
      reg_fence(own);
#pragma unroll 1
      for (int e = 0; e < 3; e++) { uint4 v[5]; fetch(e, v); add(e, v); }
      if (lane == 0) mbar_arrive(bar_w);
#pragma unroll
      for (int i = 0; i < 20; i++) xr[i] = hadd2(xr[i], hmul2(pack_bf16(own[2 * i], own[2 * i + 1]), fr[i]));
#pragma unroll
      for (int k = 0; k < 5; k++) stsm4(xa + 32 * k, xr + 4 * k);
      asm volatile("fence.proxy.async.shared::cta;" ::: "memory");
      __syncwarp();
      if (elect()) {
        tma2d_store(&m.out, xs, nh * 320 + kq * 80, qt * 128 + cw * 16);
        asm volatile("cp.async.bulk.commit_group;\ncp.async.bulk.wait_group.read 0;" ::: "memory");
      }
      __syncwarp();
    }
    cluster_wait();
  } else {
    asm volatile("setmaxnreg.dec.sync.aligned.u32 40;");
    uint32_t tid_; asm volatile("mov.u32 %0, %%tid.x;" : "=r"(tid_));
    const int warp = __shfl_sync(~0u, tid_ >> 5, 0);
    auto is_warp = [&](int k) { uint32_t e; asm volatile("{\n.reg .pred q;\nsetp.eq.u32 q, %1, %2;\nselp.u32 %0, 1, 0, q;\n}" : "=r"(e) : "r"(warp), "r"(k)); return e != 0; };
    if (warp > 0) {
      const unsigned epoch = (unsigned)(__ldcg(&p.s->done) >> 7);
      int budget = WAIT_BUDGET;
      const uint32_t tag = epoch + 1;
      mbar_wait(bar_a + EA, 0, budget);
      mbar_wait(bar_b + (kg0 & ~7), 0, budget); mbar_wait(bar_b + (kg0 & ~7) + 8, 0, budget);
      float cs0 = 0.f, cs1 = 0.f;
      const int n = rank * 96 + (warp - 1) * 32;
#pragma unroll 1
      for (int kg = kg0 + (lane >> 4) * 5, e = kg + 5; kg < e; kg++) {
        const uint32_t ad = sb + OFF_B + kg * 3072 + (n >> 6) * 1024 + (n & 63) * 2 + (lane & 15) * 4;
#pragma unroll
        for (int k = 0; k < 8; k++) { const uint32_t v = lds32(ad ^ (k * 0x90)); cs0 += bf_lo(v); cs1 += bf_hi(v); }
      }
      cs0 += __shfl_xor_sync(~0u, cs0, 16); cs1 += __shfl_xor_sync(~0u, cs1, 16);
      if (lane < 16) st_pkt8((uint2*)(p.s->cs + (hg * 4 + (qt >> 2)) * 96 + (n >> 1) + lane) + ((qt >> 1) & 1), (__float_as_uint(cs0) & ~3u) | (tag & 3), __float_as_uint(cs1));
      if (lane < 2) { uint32_t a; asm volatile("mapa.shared::cluster.u32 %0, %1, %2;" : "=r"(a) : "r"(bar_d), "r"(lane)); mbar_arrive_cluster(a); }
      mbar_wait(bar_a + EA, 1, budget);
      for (const uint32_t c0 = clock(); clock() - c0 < CSW;) {}
      uint4 v[5];
      while (true) {
        uint32_t bad = 0;
#pragma unroll
        for (int i = 0; i < 5; i++) v[i] = ld_pkt(i < 4 ? p.s->cs + (hg * 4 + i) * 96 + (tid_ - 32) : (const uint4*)p.s->stat + qt * 64 + (tid_ & 63));
#pragma unroll
        for (int i = 0; i < 5; i++) bad |= (v[i].x ^ tag) | (v[i].z ^ tag);
        if (!__any_sync(~0u, bad & 3) || --budget < 0) break;
      }
      asm volatile("st.shared.v4.u32 [%0], {%1,%2,%3,%4};" ::"r"(s_stat + (tid_ & 63) * 16), "r"(__byte_perm(v[4].x, 0, 0x3232)), "r"(v[4].y), "r"(__byte_perm(v[4].z, 0, 0x3232)), "r"(v[4].w) : "memory");
      cs0 = cs1 = 0.f;
#pragma unroll
      for (int i = 0; i < 4; i++) { cs0 += __uint_as_float(v[i].x & ~3u) + __uint_as_float(v[i].z & ~3u); cs1 += __uint_as_float(v[i].y) + __uint_as_float(v[i].w); }
#pragma unroll
      for (int k = 0; k < 8; k++) {
        const uint32_t t = k < 3 ? pack_bf16(cs0, cs1) : 0;
        sts32((sb + (warp - 1) * 1024 + lane * 4) ^ (k * 0x90), t);
        cs0 -= bf_lo(t); cs1 -= bf_hi(t);
      }
      asm volatile("fence.proxy.async.shared::cta;" ::: "memory");
      __syncwarp();
      if (lane < 2) mbar_arrive(bar_s);
      budget = errands(p.s, m, qt, hg, warp, tag, budget);
      if (is_warp(2)) {
        mbar_wait(bar_w, 0, budget);
        if (budget < 0) asm volatile("st.global.u32 [%0], %1;" ::"l"(0ull), "r"(budget) : "memory");
      }
    } else {
      uint32_t fb = bar_b + 16, dst = sb + OFF_B + 2 * TB, ph = 1;
      auto next = [&]() { fb += 8; dst += TB; if (fb == bar_b + 48) { fb = bar_b; dst = sb + OFF_B; ph ^= 1; } };
#pragma unroll 1
      for (int u = 0; u < 4; u++) {
        const int h = hg * 4 + u;
        int s = u ? (u == 2 ? 5 : 0) : (s0 + 2) % 10;
#pragma unroll 1
        for (int i = u ? 0 : 2; i < 10; i++) {
          if (u == 0) {
            const uint32_t a8 = 8 * (i < 5 ? i : i - 5);
            if (D0 && i >= D0) { const int j = i - D0; mbar_wait(bar_a + 8 * (j < 5 ? j : j - 5), j >= 5); }
            mbar_wait(bar_a + EA + a8, i < 5);
            if (elect()) { mbar_expect_tx(bar_a + a8, TA); tma2d(sb + a8 * (TA >> 3), &m.x, 64 * s, qt * 128, bar_a + a8); }
            if (i == 6 + (kg0 >> 3)) mbar_wait(bar_d, 0);
          }
          mbar_wait(fb + EB, ph);
          if (elect()) { mbar_expect_tx(fb, TB); tma4d_mc(dst + rank * (TB / 2), &m.wq, 3 * h, 8 * s + 4 * rank, fb); }
          next();
          if (++s == 10) s = 0;
        }
        const int kv0 = (h * SKC + (SKC - WIN)) / 8 + 4 * rank;
#pragma unroll 1
        for (int i = 0; i < 16; i++) {
          const bool isk = (0x2AAB >> i) & 1;
          mbar_wait(fb + EB, ph);
          if (elect()) { mbar_expect_tx(fb, TB); tma4d_mc(dst + rank * (TB / 2), isk ? &m.k : &m.v, 0, kv0 + 8 * (isk ? (i + 1) >> 1 : (i - 1) >> 1), fb); }
          next();
        }
      }
      const int cF = 10 * nh + 5 - 5 * (kq >> 1), cS = 10 * nh + 5 * (kq >> 1);
      const int kb = 4 * (k_block(lane, hg) + rank);
#pragma unroll 1
      for (int n = 0; n < 38; n++) {
        const int c2 = __shfl_sync(~0u, kb, n >> 1);
        mbar_wait(fb + EB, ph);
        if (elect()) { mbar_expect_tx(fb, TW); tma5d_mc(dst + rank * (TW / 2), &m.wo, c2, n & 1 ? cS : cF, fb); }
        next();
      }
      const int odd = (((0x7ff0 ^ 1 << LQ) ^ (kq & 1 ? 0xffc00 : 0)) >> lane) & 1;
      const int tq = __shfl_sync(~0u, kb, 19 + end_stage(lane)) << 16 | odd << 7 | ((lane < 10 ? cF : cS) + 2 * odd);
#pragma unroll 1
      for (int n = 0; n < 20; n += 2) {
        const int t0 = __shfl_sync(~0u, tq, n), t1 = __shfl_sync(~0u, tq, n + 1);
        mbar_wait(fb + EB, ph);
        if (elect()) {
          mbar_expect_tx(fb, TB);
          tma5d_mc(dst + rank * (TB / 4), (const CUtensorMap*)((const char*)m.w3 + (t0 & 128)), t0 >> 16, t0 & 31, fb);
          tma5d_mc(dst + TB / 2 + rank * (TB / 4), (const CUtensorMap*)((const char*)m.w3 + (t1 & 128)), t1 >> 16, t1 & 31, fb);
        }
        next();
      }
      mbar_wait(fb + EB, ph);
      if (elect()) { mbar_expect_tx(fb, TW); tma2d(dst, &m.xe, nh * 320 + kq * 80, qt * 128, fb); }
    }
    if (!is_warp(2)) {
      const int e = warp - (warp >> 1), ms = 2 * e + ((lane >> 2) & 1);
      const uint4* src = p.s->o + (size_t)(qt * 192 + nh * 24 + 10 + (kq ^ ((0x132 >> (4 * e)) & 3)) * 48) * 512 + (e < 2 ? kq & 1 : 2) * 1280 + (ms & 1) * 640;
      uint32_t todo = 0xff;
      bool ok = lane >= 8;
      mbar_wait(bar_z, 0);
#pragma unroll 1
      while (todo) {
        if (!ok) ok = ld_pkt(src + 4 * 128 + (lane & 3) * 32 + 31).x & 1;
        const uint32_t got = __ballot_sync(~0u, ok) & todo, go = __ballot_sync(~0u, ((got >> (lane & 28)) & 15) == 15);
        if (go) mbar_wait(bar_a + EA + 8 * e, 0);
        if ((go & 0x11) >> lane & 1) {
          mbar_expect_tx(bar_e + 8 * ms, TW / 2); bulk_load(sb + OFF_B + (3 + e) * TB + (ms & 1) * (TW / 2), src, TW / 2, bar_e + 8 * ms);
        }
        todo &= ~go;
      }
    }
    cluster_sync();
  }
}

typedef CUresult (*EncodeFn)(CUtensorMap*, CUtensorMapDataType, cuuint32_t, void*, const cuuint64_t*, const cuuint64_t*,
                             const cuuint32_t*, const cuuint32_t*, CUtensorMapInterleave, CUtensorMapSwizzle,
                             CUtensorMapL2promotion, CUtensorMapFloatOOBfill);

void encode(EncodeFn fn, CUtensorMap* tm, void* base, int rank, const cuuint64_t* dims, const cuuint64_t* strides,
            const cuuint32_t* box, CUtensorMapSwizzle sw) {
  const cuuint32_t es[5] = {1, 1, 1, 1, 1};
  fn(tm, CU_TENSOR_MAP_DATA_TYPE_BFLOAT16, rank, base, dims, strides, box, es, CU_TENSOR_MAP_INTERLEAVE_NONE, sw,
     CU_TENSOR_MAP_L2_PROMOTION_L2_128B, CU_TENSOR_MAP_FLOAT_OOB_FILL_NONE);
}

}

extern "C" void kernel_launch(void* const* d_in, const int* in_sizes, int n_in, void* d_out, int out_size) {
  static EncodeFn fn = nullptr;
  static Scratch* scr = nullptr;
  if (!fn) {
    void* f = nullptr;
    cudaDriverEntryPointQueryResult st;
    cudaGetDriverEntryPoint("cuTensorMapEncodeTiled", &f, cudaEnableDefault, &st);
    fn = (EncodeFn)f;
    cudaGetSymbolAddress((void**)&scr, g_scratch);
    cudaFuncSetAttribute(fused_kernel, cudaFuncAttributeMaxDynamicSharedMemorySize, SMEM_BYTES);
  }
  Maps m;
  { const cuuint64_t d[2] = {DM, SQ}, s[1] = {DM * 2}; const cuuint32_t b[2] = {64, 128};
    encode(fn, &m.x, d_in[0], 2, d, s, b, CU_TENSOR_MAP_SWIZZLE_128B);
    encode(fn, &m.xn, scr->xn, 2, d, s, b, CU_TENSOR_MAP_SWIZZLE_128B); }
  { const cuuint64_t d[4] = {64, 8, QD / 64, DM / 8}, s[3] = {QD * 2, 128, 8 * QD * 2}; const cuuint32_t b[4] = {64, 8, 3, 4};
    encode(fn, &m.wq, d_in[3], 4, d, s, b, CU_TENSOR_MAP_SWIZZLE_128B); }
  { const cuuint64_t d[4] = {64, 8, 3, NH * SKC / 8}, s[3] = {DH * 2, 128, 8 * DH * 2}; const cuuint32_t b[4] = {64, 8, 3, 4};
    encode(fn, &m.k, d_in[1], 4, d, s, b, CU_TENSOR_MAP_SWIZZLE_128B);
    encode(fn, &m.v, d_in[2], 4, d, s, b, CU_TENSOR_MAP_SWIZZLE_128B); }
  {
    const cuuint64_t d[5] = {32, 2, QD / 8, 4, DM / 32}, s[4] = {DM * 2, 8 * DM * 2, 2 * DM * 2, 64}; const cuuint32_t b[5] = {32, 2, 4, 4, 5};
    encode(fn, &m.wo, d_in[4], 5, d, s, b, CU_TENSOR_MAP_SWIZZLE_64B);
    const cuuint32_t b3[5] = {32, 2, 4, 4, 3};
    encode(fn, &m.w3[0], d_in[4], 5, d, s, b3, CU_TENSOR_MAP_SWIZZLE_64B);
    encode(fn, &m.w3[1], (char*)d_in[4] + 32, 5, d, s, b3, CU_TENSOR_MAP_SWIZZLE_64B); }
  { const cuuint64_t d[2] = {DM, SQ}, s[1] = {DM * 2}; const cuuint32_t bg[2] = {80, 24}, bx[2] = {80, 128}, bo[2] = {80, 16};
    encode(fn, &m.xg, d_in[0], 2, d, s, bg, CU_TENSOR_MAP_SWIZZLE_NONE);
    encode(fn, &m.xe, d_in[0], 2, d, s, bx, CU_TENSOR_MAP_SWIZZLE_NONE);
    encode(fn, &m.out, d_out, 2, d, s, bo, CU_TENSOR_MAP_SWIZZLE_NONE); }
  Params p;
  p.x = (const __nv_bfloat16*)d_in[0]; p.wr = (const __nv_bfloat16*)d_in[6]; p.wg = (const __nv_bfloat16*)d_in[7];
  p.wu = (const __nv_bfloat16*)d_in[8]; p.wd = (const __nv_bfloat16*)d_in[9];

  p.k = (const __nv_bfloat16*)d_in[1]; p.v = (const __nv_bfloat16*)d_in[2]; p.s = scr;
  cudaLaunchConfig_t cfg = {};
  cfg.gridDim = dim3(132); cfg.blockDim = dim3(384); cfg.dynamicSmemBytes = SMEM_BYTES; cfg.stream = cudaStreamPerThread;
  cudaLaunchKernelEx(&cfg, fused_kernel, p, m);
}
```

```cpp
#include <cuda_runtime.h>
#include <cuda_bf16.h>
#include <cuda.h>
#include <stdint.h>

namespace {

constexpr int SQ = 2048, DM = 640, NH = 32, DH = 192, SKC = 2048, WIN = 512, FF = 1536;
constexpr int QD = NH * DH;
constexpr uint32_t TA = 16384, TB = 24576, TW = 20480, OFF_B = 5 * TA, OFF_M = OFF_B + 6 * TB, SMEM_BYTES = OFF_M + 3072;
constexpr int WAIT_BUDGET = 1 << 20;

constexpr int FL_XN = 0;
constexpr int FL_O = 512;
constexpr int FL_RD = FL_O + 1024;
constexpr int FL_FFN = FL_RD + 1024;
constexpr int FL_SIDE = FL_FFN + 32;
struct __align__(1024) Scratch {
  unsigned long long done, pad0[15];
  unsigned flag[FL_SIDE + 32];
  uint4 cand[8];
  float ffn[4 * 2 * DM];
  int sel[4];
  __nv_bfloat16 gsel[2 * DM];
  uint4 cs[8 * 4 * DH / 2];
  uint2 stat[SQ];
  __align__(1024) __nv_bfloat16 xn[SQ * DM];
  __align__(1024) uint4 o[SQ * QD / 8];
};
__device__ Scratch g_scratch;

__device__ __forceinline__ uint32_t smem_u32(const void* p) { return (uint32_t)__cvta_generic_to_shared(p); }
__device__ __forceinline__ void mbar_init(uint32_t bar, int cnt) { asm volatile("mbarrier.init.shared::cta.b64 [%0], %1;" ::"r"(bar), "r"(cnt)); }
__device__ __forceinline__ void mbar_expect_tx(uint32_t bar, uint32_t bytes) {
  asm volatile("mbarrier.arrive.expect_tx.shared::cta.b64 _, [%0], %1;" ::"r"(bar), "r"(bytes) : "memory");
}
__device__ __forceinline__ void mbar_arrive(uint32_t bar) { asm volatile("mbarrier.arrive.shared::cta.b64 _, [%0];" ::"r"(bar) : "memory"); }
__device__ __forceinline__ void mbar_arrive_cluster(uint32_t addr) { asm volatile("mbarrier.arrive.shared::cluster.b64 _, [%0];" ::"r"(addr) : "memory"); }
__device__ __forceinline__ bool mbar_try(uint32_t bar, uint32_t parity) {
  uint32_t ok;
  asm volatile("{\n.reg .pred p;\nmbarrier.try_wait.parity.shared::cta.b64 p, [%1], %2;\nselp.u32 %0, 1, 0, p;\n}\n" : "=r"(ok) : "r"(bar), "r"(parity) : "memory");
  return ok;
}
__device__ __forceinline__ void mbar_wait(uint32_t bar, uint32_t parity, int& budget) {
#pragma unroll 1
  while (!mbar_try(bar, parity)) { if (--budget < 0) break; }
}
__device__ __forceinline__ void mbar_wait(uint32_t bar, uint32_t parity) {
#pragma unroll 1
  while (!mbar_try(bar, parity)) {}
}
__device__ __forceinline__ unsigned ld_acquire(const unsigned* p) { unsigned v; asm volatile("ld.acquire.gpu.global.u32 %0, [%1];" : "=r"(v) : "l"(p) : "memory"); return v; }
__device__ __forceinline__ void wait_flag(const unsigned* p, unsigned target) {
#pragma unroll 1
  while (__any_sync(~0u, (int)(ld_acquire(p) - target) < 0)) {}
}
__device__ __forceinline__ void red_release(unsigned* p) { asm volatile("red.release.gpu.global.add.u32 [%0], 1;" ::"l"(p) : "memory"); }
__device__ __forceinline__ void fence_proxy_async() { asm volatile("fence.proxy.async.global;" ::: "memory"); }
__device__ __forceinline__ bool elect() {
  uint32_t p;
  asm volatile("{\n.reg .pred P;\nelect.sync _|P, 0xffffffff;\nselp.u32 %0, 1, 0, P;\n}\n" : "=r"(p));
  return p;
}
__device__ __forceinline__ void cluster_arrive() { asm volatile("barrier.cluster.arrive.relaxed.aligned;" ::: "memory"); }
__device__ __forceinline__ void cluster_wait() { asm volatile("barrier.cluster.wait.aligned;" ::: "memory"); }
__device__ __forceinline__ void cluster_sync() { cluster_arrive(); cluster_wait(); }
__device__ __forceinline__ void tma2d(uint32_t dst, const CUtensorMap* tm, int c0, int c1, uint32_t bar) {
  asm volatile("cp.async.bulk.tensor.2d.shared::cluster.global.mbarrier::complete_tx::bytes [%0], [%1, {%3, %4}], [%2];"
               ::"r"(dst), "l"(tm), "r"(bar), "r"(c0), "r"(c1) : "memory");
}
constexpr uint64_t POL_FIRST = 0x12F0000000000000ull;
__device__ __forceinline__ void tma4d_mc(uint32_t dst, const CUtensorMap* tm, int c2, int c3, uint32_t bar) {
  asm volatile("cp.async.bulk.tensor.4d.shared::cluster.global.mbarrier::complete_tx::bytes.multicast::cluster.L2::cache_hint [%0], [%1, {%3, %3, %4, %5}], [%2], %6, %7;"
               ::"r"(dst), "l"(tm), "r"(bar), "r"(0), "r"(c2), "r"(c3), "h"((uint16_t)3), "l"(POL_FIRST) : "memory");
}
__device__ __forceinline__ void tma5d_mc(uint32_t dst, const CUtensorMap* tm, int c2, int c4, uint32_t bar) {
  asm volatile("cp.async.bulk.tensor.5d.shared::cluster.global.mbarrier::complete_tx::bytes.multicast::cluster.L2::cache_hint [%0], [%1, {%3, %3, %4, %3, %5}], [%2], %6, %7;"
               ::"r"(dst), "l"(tm), "r"(bar), "r"(0), "r"(c2), "r"(c4), "h"((uint16_t)3), "l"(POL_FIRST) : "memory");
}
__device__ __forceinline__ void bulk_load(uint32_t dst, const void* src, uint32_t bytes, uint32_t bar) {
  asm volatile("cp.async.bulk.shared::cluster.global.mbarrier::complete_tx::bytes.L2::cache_hint [%0], [%1], %2, [%3], %4;" ::"r"(dst), "l"(src), "r"(bytes), "r"(bar), "l"(POL_FIRST) : "memory");
}
__device__ __forceinline__ void tma2d_store(const CUtensorMap* tm, uint32_t src, int c0, int c1) {
  asm volatile("cp.async.bulk.tensor.2d.global.shared::cta.bulk_group [%0, {%2, %3}], [%1];" ::"l"(tm), "r"(src), "r"(c0), "r"(c1) : "memory");
}
__device__ __forceinline__ uint32_t lds32(uint32_t a) { uint32_t v; asm volatile("ld.shared.u32 %0, [%1];" : "=r"(v) : "r"(a) : "memory"); return v; }
__device__ __forceinline__ uint2 lds64(uint32_t a) { uint2 v; asm volatile("ld.shared.v2.u32 {%0,%1}, [%2];" : "=r"(v.x), "=r"(v.y) : "r"(a) : "memory"); return v; }
__device__ __forceinline__ uint4 lds128(uint32_t a) { uint4 v; asm volatile("ld.shared.v4.u32 {%0,%1,%2,%3}, [%4];" : "=r"(v.x), "=r"(v.y), "=r"(v.z), "=r"(v.w) : "r"(a) : "memory"); return v; }
__device__ __forceinline__ void ldsm4(uint32_t a, uint32_t* v) {
  asm volatile("ldmatrix.sync.aligned.m8n8.x4.shared.b16 {%0,%1,%2,%3}, [%4];" : "=r"(v[0]), "=r"(v[1]), "=r"(v[2]), "=r"(v[3]) : "r"(a) : "memory");
}
__device__ __forceinline__ void stsm4(uint32_t a, const uint32_t* v) {
  asm volatile("stmatrix.sync.aligned.m8n8.x4.shared.b16 [%0], {%1,%2,%3,%4};" ::"r"(a), "r"(v[0]), "r"(v[1]), "r"(v[2]), "r"(v[3]) : "memory");
}
__device__ __forceinline__ void sts32(uint32_t a, uint32_t v) { asm volatile("st.shared.u32 [%0], %1;" ::"r"(a), "r"(v) : "memory"); }
__device__ __forceinline__ void st_pkt(uint4* p, uint32_t a, uint32_t b, uint32_t c, uint32_t d) {
  asm volatile("st.relaxed.gpu.global.v4.b32 [%0], {%1, %2, %3, %4};" ::"l"(p), "r"(a), "r"(b), "r"(c), "r"(d) : "memory");
}
__device__ __forceinline__ void st_pkt8(void* p, uint32_t a, uint32_t b) {
  asm volatile("{\n.reg .b64 v;\nmov.b64 v, {%1, %2};\nst.relaxed.gpu.global.b64 [%0], v;\n}\n" ::"l"(p), "r"(a), "r"(b) : "memory");
}
__device__ __forceinline__ uint4 ld_pkt(const uint4* p) {
  uint4 v;
  asm volatile("{\n.reg .b128 v;\nld.relaxed.gpu.global.b128 v, [%4];\nmov.b128 {%0, %1, %2, %3}, v;\n}\n" : "=r"(v.x), "=r"(v.y), "=r"(v.z), "=r"(v.w) : "l"(p) : "memory");
  return v;
}
__device__ __forceinline__ uint4 ldg_nc(const void* p) {
  uint4 v;
  asm volatile("ld.global.nc.v4.u32 {%0,%1,%2,%3}, [%4];" : "=r"(v.x), "=r"(v.y), "=r"(v.z), "=r"(v.w) : "l"(p));
  return v;
}
#define WG_FENCE() asm volatile("wgmma.fence.sync.aligned;" ::: "memory")
#define WG_COMMIT() asm volatile("wgmma.commit_group.sync.aligned;" ::: "memory")
#define WG_WAIT(n) asm volatile("wgmma.wait_group.sync.aligned " #n ";" ::: "memory")
template <int N> __device__ __forceinline__ void reg_fence(float (&d)[N]) {
#pragma unroll
  for (int i = 0; i < N; i++) asm volatile("" : "+f"(d[i])::"memory");
}
template <int N> __device__ __forceinline__ void reg_fence(uint32_t (&d)[N]) {
#pragma unroll
  for (int i = 0; i < N; i++) asm volatile("" : "+r"(d[i])::"memory");
}
__device__ __forceinline__ constexpr uint64_t desc_hi(uint32_t lbo, uint32_t sbo, uint64_t sw) {
  return ((uint64_t)(lbo >> 4) << 16) | ((uint64_t)(sbo >> 4) << 32) | (sw << 62);
}
__device__ __forceinline__ uint64_t mkdesc(uint32_t addr, uint64_t hi) { return hi | (uint64_t)((addr & 0x3FFFF) >> 4); }
__device__ __forceinline__ uint32_t pack_bf16(float lo, float hi) { uint32_t r; asm("cvt.rn.bf16x2.f32 %0, %1, %2;" : "=r"(r) : "f"(hi), "f"(lo)); return r; }
__device__ __forceinline__ float bf_lo(uint32_t v) { return __uint_as_float(v << 16); }
__device__ __forceinline__ float bf_hi(uint32_t v) { return __uint_as_float(v & 0xffff0000u); }
__device__ __forceinline__ uint32_t hadd2(uint32_t a, uint32_t b) { uint32_t r; asm("add.rn.bf16x2 %0, %1, %2;" : "=r"(r) : "r"(a), "r"(b)); return r; }
__device__ __forceinline__ uint32_t hsub2(uint32_t a, uint32_t b) { uint32_t r; asm("sub.rn.bf16x2 %0, %1, %2;" : "=r"(r) : "r"(a), "r"(b)); return r; }
__device__ __forceinline__ uint32_t hmul2(uint32_t a, uint32_t b) { uint32_t r; asm("mul.rn.bf16x2 %0, %1, %2;" : "=r"(r) : "r"(a), "r"(b)); return r; }
__device__ __forceinline__ float rbf(float x) { return __bfloat162float(__float2bfloat16_rn(x)); }
__device__ __forceinline__ float ex2(float x) { float y; asm("ex2.approx.ftz.f32 %0, %1;" : "=f"(y) : "f"(x)); return y; }
__device__ __forceinline__ float rcp(float x) { float y; asm("rcp.approx.ftz.f32 %0, %1;" : "=f"(y) : "f"(x)); return y; }
__device__ __forceinline__ float sigmoid_f(float x) { return rcp(1.f + ex2(x * -1.4426950408889634f)); }
__device__ __forceinline__ float silu_f(float x) { return x * sigmoid_f(x); }

__device__ __forceinline__ void wg_ss192t(float (&d)[96], uint64_t da, uint64_t db, int sd) {
  asm volatile("{\n.reg .pred p;\nsetp.ne.b32 p, %98, 0;\n"
    "wgmma.mma_async.sync.aligned.m64n192k16.f32.bf16.bf16 {%0,%1,%2,%3,%4,%5,%6,%7,%8,%9,%10,%11,%12,%13,%14,%15,%16,%17,%18,%19,%20,%21,%22,%23,%24,%25,%26,%27,%28,%29,%30,%31,%32,%33,%34,%35,%36,%37,%38,%39,%40,%41,%42,%43,%44,%45,%46,%47,%48,%49,%50,%51,%52,%53,%54,%55,%56,%57,%58,%59,%60,%61,%62,%63,%64,%65,%66,%67,%68,%69,%70,%71,%72,%73,%74,%75,%76,%77,%78,%79,%80,%81,%82,%83,%84,%85,%86,%87,%88,%89,%90,%91,%92,%93,%94,%95}, %96, %97, p, 1, 1, 0, 1;\n}\n"
    : "+f"(d[0]),"+f"(d[1]),"+f"(d[2]),"+f"(d[3]),"+f"(d[4]),"+f"(d[5]),"+f"(d[6]),"+f"(d[7]),"+f"(d[8]),"+f"(d[9]),"+f"(d[10]),"+f"(d[11]),"+f"(d[12]),"+f"(d[13]),"+f"(d[14]),"+f"(d[15]),"+f"(d[16]),"+f"(d[17]),"+f"(d[18]),"+f"(d[19]),"+f"(d[20]),"+f"(d[21]),"+f"(d[22]),"+f"(d[23]),"+f"(d[24]),"+f"(d[25]),"+f"(d[26]),"+f"(d[27]),"+f"(d[28]),"+f"(d[29]),"+f"(d[30]),"+f"(d[31]),"+f"(d[32]),"+f"(d[33]),"+f"(d[34]),"+f"(d[35]),"+f"(d[36]),"+f"(d[37]),"+f"(d[38]),"+f"(d[39]),"+f"(d[40]),"+f"(d[41]),"+f"(d[42]),"+f"(d[43]),"+f"(d[44]),"+f"(d[45]),"+f"(d[46]),"+f"(d[47]),"+f"(d[48]),"+f"(d[49]),"+f"(d[50]),"+f"(d[51]),"+f"(d[52]),"+f"(d[53]),"+f"(d[54]),"+f"(d[55]),"+f"(d[56]),"+f"(d[57]),"+f"(d[58]),"+f"(d[59]),"+f"(d[60]),"+f"(d[61]),"+f"(d[62]),"+f"(d[63]),"+f"(d[64]),"+f"(d[65]),"+f"(d[66]),"+f"(d[67]),"+f"(d[68]),"+f"(d[69]),"+f"(d[70]),"+f"(d[71]),"+f"(d[72]),"+f"(d[73]),"+f"(d[74]),"+f"(d[75]),"+f"(d[76]),"+f"(d[77]),"+f"(d[78]),"+f"(d[79]),"+f"(d[80]),"+f"(d[81]),"+f"(d[82]),"+f"(d[83]),"+f"(d[84]),"+f"(d[85]),"+f"(d[86]),"+f"(d[87]),"+f"(d[88]),"+f"(d[89]),"+f"(d[90]),"+f"(d[91]),"+f"(d[92]),"+f"(d[93]),"+f"(d[94]),"+f"(d[95])
    : "l"(da), "l"(db), "r"(sd));
}
__device__ __forceinline__ void wg_rs64(float (&d)[32], uint32_t a0, uint32_t a1, uint32_t a2, uint32_t a3, uint64_t db, int sd) {
  asm volatile("{\n.reg .pred p;\nsetp.ne.b32 p, %37, 0;\n"
    "wgmma.mma_async.sync.aligned.m64n64k16.f32.bf16.bf16 {%0,%1,%2,%3,%4,%5,%6,%7,%8,%9,%10,%11,%12,%13,%14,%15,%16,%17,%18,%19,%20,%21,%22,%23,%24,%25,%26,%27,%28,%29,%30,%31}, {%32,%33,%34,%35}, %36, p, 1, 1, 0;\n}\n"
    : "+f"(d[0]),"+f"(d[1]),"+f"(d[2]),"+f"(d[3]),"+f"(d[4]),"+f"(d[5]),"+f"(d[6]),"+f"(d[7]),"+f"(d[8]),"+f"(d[9]),"+f"(d[10]),"+f"(d[11]),"+f"(d[12]),"+f"(d[13]),"+f"(d[14]),"+f"(d[15]),"+f"(d[16]),"+f"(d[17]),"+f"(d[18]),"+f"(d[19]),"+f"(d[20]),"+f"(d[21]),"+f"(d[22]),"+f"(d[23]),"+f"(d[24]),"+f"(d[25]),"+f"(d[26]),"+f"(d[27]),"+f"(d[28]),"+f"(d[29]),"+f"(d[30]),"+f"(d[31])
    : "r"(a0), "r"(a1), "r"(a2), "r"(a3), "l"(db), "r"(sd));
}
__device__ __forceinline__ void wg_rs192t(float (&d)[96], uint32_t a0, uint32_t a1, uint32_t a2, uint32_t a3, uint64_t db, int sd) {
  asm volatile("{\n.reg .pred p;\nsetp.ne.b32 p, %101, 0;\n"
    "wgmma.mma_async.sync.aligned.m64n192k16.f32.bf16.bf16 {%0,%1,%2,%3,%4,%5,%6,%7,%8,%9,%10,%11,%12,%13,%14,%15,%16,%17,%18,%19,%20,%21,%22,%23,%24,%25,%26,%27,%28,%29,%30,%31,%32,%33,%34,%35,%36,%37,%38,%39,%40,%41,%42,%43,%44,%45,%46,%47,%48,%49,%50,%51,%52,%53,%54,%55,%56,%57,%58,%59,%60,%61,%62,%63,%64,%65,%66,%67,%68,%69,%70,%71,%72,%73,%74,%75,%76,%77,%78,%79,%80,%81,%82,%83,%84,%85,%86,%87,%88,%89,%90,%91,%92,%93,%94,%95}, {%96,%97,%98,%99}, %100, p, 1, 1, 1;\n}\n"
    : "+f"(d[0]),"+f"(d[1]),"+f"(d[2]),"+f"(d[3]),"+f"(d[4]),"+f"(d[5]),"+f"(d[6]),"+f"(d[7]),"+f"(d[8]),"+f"(d[9]),"+f"(d[10]),"+f"(d[11]),"+f"(d[12]),"+f"(d[13]),"+f"(d[14]),"+f"(d[15]),"+f"(d[16]),"+f"(d[17]),"+f"(d[18]),"+f"(d[19]),"+f"(d[20]),"+f"(d[21]),"+f"(d[22]),"+f"(d[23]),"+f"(d[24]),"+f"(d[25]),"+f"(d[26]),"+f"(d[27]),"+f"(d[28]),"+f"(d[29]),"+f"(d[30]),"+f"(d[31]),"+f"(d[32]),"+f"(d[33]),"+f"(d[34]),"+f"(d[35]),"+f"(d[36]),"+f"(d[37]),"+f"(d[38]),"+f"(d[39]),"+f"(d[40]),"+f"(d[41]),"+f"(d[42]),"+f"(d[43]),"+f"(d[44]),"+f"(d[45]),"+f"(d[46]),"+f"(d[47]),"+f"(d[48]),"+f"(d[49]),"+f"(d[50]),"+f"(d[51]),"+f"(d[52]),"+f"(d[53]),"+f"(d[54]),"+f"(d[55]),"+f"(d[56]),"+f"(d[57]),"+f"(d[58]),"+f"(d[59]),"+f"(d[60]),"+f"(d[61]),"+f"(d[62]),"+f"(d[63]),"+f"(d[64]),"+f"(d[65]),"+f"(d[66]),"+f"(d[67]),"+f"(d[68]),"+f"(d[69]),"+f"(d[70]),"+f"(d[71]),"+f"(d[72]),"+f"(d[73]),"+f"(d[74]),"+f"(d[75]),"+f"(d[76]),"+f"(d[77]),"+f"(d[78]),"+f"(d[79]),"+f"(d[80]),"+f"(d[81]),"+f"(d[82]),"+f"(d[83]),"+f"(d[84]),"+f"(d[85]),"+f"(d[86]),"+f"(d[87]),"+f"(d[88]),"+f"(d[89]),"+f"(d[90]),"+f"(d[91]),"+f"(d[92]),"+f"(d[93]),"+f"(d[94]),"+f"(d[95])
    : "r"(a0), "r"(a1), "r"(a2), "r"(a3), "l"(db), "r"(sd));
}
__device__ __forceinline__ void wg_ss160t(float (&d)[80], uint64_t da, uint64_t db, int sd) {
  asm volatile("{\n.reg .pred p;\nsetp.ne.b32 p, %82, 0;\n"
    "wgmma.mma_async.sync.aligned.m64n160k16.f32.bf16.bf16 {%0,%1,%2,%3,%4,%5,%6,%7,%8,%9,%10,%11,%12,%13,%14,%15,%16,%17,%18,%19,%20,%21,%22,%23,%24,%25,%26,%27,%28,%29,%30,%31,%32,%33,%34,%35,%36,%37,%38,%39,%40,%41,%42,%43,%44,%45,%46,%47,%48,%49,%50,%51,%52,%53,%54,%55,%56,%57,%58,%59,%60,%61,%62,%63,%64,%65,%66,%67,%68,%69,%70,%71,%72,%73,%74,%75,%76,%77,%78,%79}, %80, %81, p, 1, 1, 0, 1;\n}\n"
    : "+f"(d[0]),"+f"(d[1]),"+f"(d[2]),"+f"(d[3]),"+f"(d[4]),"+f"(d[5]),"+f"(d[6]),"+f"(d[7]),"+f"(d[8]),"+f"(d[9]),"+f"(d[10]),"+f"(d[11]),"+f"(d[12]),"+f"(d[13]),"+f"(d[14]),"+f"(d[15]),"+f"(d[16]),"+f"(d[17]),"+f"(d[18]),"+f"(d[19]),"+f"(d[20]),"+f"(d[21]),"+f"(d[22]),"+f"(d[23]),"+f"(d[24]),"+f"(d[25]),"+f"(d[26]),"+f"(d[27]),"+f"(d[28]),"+f"(d[29]),"+f"(d[30]),"+f"(d[31]),"+f"(d[32]),"+f"(d[33]),"+f"(d[34]),"+f"(d[35]),"+f"(d[36]),"+f"(d[37]),"+f"(d[38]),"+f"(d[39]),"+f"(d[40]),"+f"(d[41]),"+f"(d[42]),"+f"(d[43]),"+f"(d[44]),"+f"(d[45]),"+f"(d[46]),"+f"(d[47]),"+f"(d[48]),"+f"(d[49]),"+f"(d[50]),"+f"(d[51]),"+f"(d[52]),"+f"(d[53]),"+f"(d[54]),"+f"(d[55]),"+f"(d[56]),"+f"(d[57]),"+f"(d[58]),"+f"(d[59]),"+f"(d[60]),"+f"(d[61]),"+f"(d[62]),"+f"(d[63]),"+f"(d[64]),"+f"(d[65]),"+f"(d[66]),"+f"(d[67]),"+f"(d[68]),"+f"(d[69]),"+f"(d[70]),"+f"(d[71]),"+f"(d[72]),"+f"(d[73]),"+f"(d[74]),"+f"(d[75]),"+f"(d[76]),"+f"(d[77]),"+f"(d[78]),"+f"(d[79])
    : "l"(da), "l"(db), "r"(sd));
}
__device__ __forceinline__ void wg_ss80t(float (&d)[40], uint64_t da, uint64_t db, int sd) {
  asm volatile("{\n.reg .pred p;\nsetp.ne.b32 p, %42, 0;\n"
    "wgmma.mma_async.sync.aligned.m64n80k16.f32.bf16.bf16 {%0,%1,%2,%3,%4,%5,%6,%7,%8,%9,%10,%11,%12,%13,%14,%15,%16,%17,%18,%19,%20,%21,%22,%23,%24,%25,%26,%27,%28,%29,%30,%31,%32,%33,%34,%35,%36,%37,%38,%39}, %40, %41, p, 1, 1, 0, 1;\n}\n"
    : "+f"(d[0]),"+f"(d[1]),"+f"(d[2]),"+f"(d[3]),"+f"(d[4]),"+f"(d[5]),"+f"(d[6]),"+f"(d[7]),"+f"(d[8]),"+f"(d[9]),"+f"(d[10]),"+f"(d[11]),"+f"(d[12]),"+f"(d[13]),"+f"(d[14]),"+f"(d[15]),"+f"(d[16]),"+f"(d[17]),"+f"(d[18]),"+f"(d[19]),"+f"(d[20]),"+f"(d[21]),"+f"(d[22]),"+f"(d[23]),"+f"(d[24]),"+f"(d[25]),"+f"(d[26]),"+f"(d[27]),"+f"(d[28]),"+f"(d[29]),"+f"(d[30]),"+f"(d[31]),"+f"(d[32]),"+f"(d[33]),"+f"(d[34]),"+f"(d[35]),"+f"(d[36]),"+f"(d[37]),"+f"(d[38]),"+f"(d[39])
    : "l"(da), "l"(db), "r"(sd));
}

struct Maps { CUtensorMap x, xn, wq, k, v, wo, w3[2], xg, xe, out; };
struct Params {
  const __nv_bfloat16 *x, *wr, *wg, *wu, *wd, *k, *v;
  Scratch* s;
};

__device__ __forceinline__ void side_cta(const Params& p, int sc, unsigned epoch, float* sm) {
  const int tid = threadIdx.x, lane = tid & 31, warp = tid >> 5;
  int budget = WAIT_BUDGET;
  float* s_x = sm;
  float* s_red = sm + 1280;
  float* s_h = s_red + 6144;
  uint4* s_c = (uint4*)(s_h + 768);
  uint2* s_st = (uint2*)(s_c + 16);
  constexpr int DEPTH = 7, STEP = 4 * 6144;
  const uint32_t ring = smem_u32(s_st + 512) + tid * 16;
  const int cg = tid % 96, ks = tid / 96, cd = tid % 80, kd = tid / 80;
  const __nv_bfloat16* wp = (cg < 48 ? p.wg : p.wu) + (size_t)(ks * 160) * FF + sc * 384 + (cg % 48) * 8;
  int kf = 0, pitch = FF;
  uint32_t slot = ring;
  auto refill = [&]() {
    if (kf == 40) { wp = p.wd + (size_t)(sc * 384 + kd * 96) * DM + cd * 8; pitch = DM; }
    if (kf < (tid < 320 ? 64 : 40)) {
#pragma unroll
      for (int j = 0; j < 4; j++) asm volatile("cp.async.cg.shared.global.L2::cache_hint [%0], [%1], 16, %2;" ::"r"(slot + j * 6144), "l"(wp + j * pitch), "l"(POL_FIRST) : "memory");
    }
    asm volatile("cp.async.commit_group;" ::: "memory");
    wp += 4 * pitch; kf++;
    slot += STEP; if (slot == ring + DEPTH * STEP) slot = ring;
  };
  auto gemv = [&](int n, const float* x0, const float* x1, float* out) {
    float a[2][8] = {};
#pragma unroll 1
    for (int k = 0; k < n; k += 4) {
      refill();
      asm volatile("cp.async.wait_group %0;" ::"n"(DEPTH - 1) : "memory");
      const float4 f0 = *(const float4*)(x0 + k), f1 = *(const float4*)(x1 + k);
      const float y0[4] = {f0.x, f0.y, f0.z, f0.w}, y1[4] = {f1.x, f1.y, f1.z, f1.w};
#pragma unroll
      for (int j = 0; j < 4; j++) {
        const uint4 v = lds128(slot + j * 6144);
        const uint32_t u[4] = {v.x, v.y, v.z, v.w};
#pragma unroll
        for (int i = 0; i < 4; i++) {
          a[0][2 * i] += y0[j] * bf_lo(u[i]); a[0][2 * i + 1] += y0[j] * bf_hi(u[i]);
          a[1][2 * i] += y1[j] * bf_lo(u[i]); a[1][2 * i + 1] += y1[j] * bf_hi(u[i]);
        }
      }
    }
#pragma unroll
    for (int i = 0; i < 16; i++) out[(i >> 3) * 768 + (i & 7)] = a[i >> 3][i & 7];
  };
  auto load_row = [&](const __nv_bfloat16* r, uint32_t (&v)[10]) {
    const uint4 a = __ldg((const uint4*)r + lane), b = __ldg((const uint4*)r + 32 + lane);
    const uint2 c = __ldg((const uint2*)r + 128 + lane);
    v[0] = a.x; v[1] = a.y; v[2] = a.z; v[3] = a.w; v[4] = b.x; v[5] = b.y; v[6] = b.z; v[7] = b.w; v[8] = c.x; v[9] = c.y;
  };
  uint32_t wr[10], xb[3][10];
  load_row(p.wr, wr);
  auto stat2 = [&](int pair) {
    uint4 v;
    do v = ld_pkt((const uint4*)p.s->stat + pair); while ((((v.x ^ (epoch + 1)) | (v.z ^ (epoch + 1))) & 0xffff) && --budget >= 0);
    return make_uint4(__byte_perm(v.x, 0, 0x3232), v.y, __byte_perm(v.z, 0, 0x3232), v.w);
  };
  if (tid < 256) ((uint4*)s_st)[tid] = stat2(sc * 256 + tid);
  __syncthreads();
#pragma unroll
  for (int b = 0; b < 3; b++) load_row(p.x + (size_t)(sc * 512 + warp + 12 * b) * DM, xb[b]);
#pragma unroll 1
  for (int k = 0; k < DEPTH - 1; k++) refill();
  float v0 = -INFINITY, v1 = -INFINITY; int i0 = 0xfff, i1 = 0xfff;
  auto better = [](float a, int ia, float b, int ib) { return a > b || (a == b && ia < ib); };
  auto push = [&](float v, int i) {
    if (better(v, i, v0, i0)) { v1 = v0; i1 = i0; v0 = v; i0 = i; }
    else if (better(v, i, v1, i1)) { v1 = v; i1 = i; }
  };
  auto push2 = [&](uint4 c) { push(__uint_as_float(c.x), c.y & 0xfff); push(__uint_as_float(c.z), c.w & 0xfff); };
#pragma unroll 1
  for (int l3 = warp; l3 < 512; l3 += 36) {
#pragma unroll
    for (int b = 0; b < 3; b++) {
      const int lr = l3 + 12 * b;
      if (lr >= 512) break;
      const uint2 st = s_st[lr];
      uint32_t v[10];
#pragma unroll
      for (int i = 0; i < 10; i++) v[i] = hsub2(xb[b][i], st.x);
      if (lr + 36 < 512) load_row(p.x + (size_t)(sc * 512 + lr + 36) * DM, xb[b]);
      float r0 = 0.f, r1 = 0.f;
#pragma unroll
      for (int i = 0; i < 10; i++) {
        const uint32_t xn = pack_bf16(bf_lo(v[i]) * __uint_as_float(st.y), bf_hi(v[i]) * __uint_as_float(st.y));
        r0 = fmaf(bf_lo(xn), bf_lo(wr[i]), r0); r1 = fmaf(bf_hi(xn), bf_hi(wr[i]), r1);
      }
      r0 += r1;
#pragma unroll
      for (int o = 16; o > 0; o >>= 1) r0 += __shfl_xor_sync(~0u, r0, o);
      push(rbf(r0), sc * 512 + lr);
    }
  }
  if (lane == 0) s_c[warp] = make_uint4(__float_as_uint(v0), i0, __float_as_uint(v1), i1);
  __syncthreads();
#pragma unroll 1
  for (int w = 1; w < 12; w++) push2(s_c[(warp + w) % 12]);
  const uint32_t tag = (epoch + 1) << 12;
  if (tid == 0) st_pkt(p.s->cand + sc, __float_as_uint(v0), i0 | tag, __float_as_uint(v1), i1);
  {
    uint4 c;
    do c = ld_pkt(p.s->cand + (lane & 3)); while (((c.y ^ tag) >> 12) && --budget >= 0);
#pragma unroll 1
    for (int w = 1; w < 4; w++) { const int o = (sc + w) & 3; push2(make_uint4(__shfl_sync(~0u, c.x, o), __shfl_sync(~0u, c.y, o), __shfl_sync(~0u, c.z, o), __shfl_sync(~0u, c.w, o))); }
  }
  if (i0 >= SQ) i0 = 0;
  if (i1 >= SQ) i1 = (i0 == 0) ? 1 : 0;
  if (tid < 320) {
    const int row = tid < 160 ? i0 : i1;
    const uint2 u = __ldg((const uint2*)(p.x + (size_t)row * DM) + tid % 160);
    const uint4 st = stat2(row >> 1);
    const uint32_t mean2 = row & 1 ? st.z : st.x, d0 = hsub2(u.x, mean2), d1 = hsub2(u.y, mean2);
    const float inv = __uint_as_float(row & 1 ? st.w : st.y);
    ((float4*)s_x)[tid] = make_float4(rbf(bf_lo(d0) * inv), rbf(bf_hi(d0) * inv), rbf(bf_lo(d1) * inv), rbf(bf_hi(d1) * inv));
  }
  __syncthreads();
  gemv(160, s_x + ks * 160, s_x + DM + ks * 160, s_red + ks * 1536 + cg * 8);
  __syncthreads();
#pragma unroll
  for (int t = 0; t < 2; t++) {
    float g = 0.f, u = 0.f;
#pragma unroll
    for (int k = 0; k < 4; k++) { g += s_red[(k * 2 + t) * 768 + tid]; u += s_red[(k * 2 + t) * 768 + 384 + tid]; }
    s_h[t * 384 + tid] = rbf(rbf(silu_f(rbf(g))) * rbf(u));
  }
  __syncthreads();
  if (tid < 320) gemv(96, s_h + kd * 96, s_h + 384 + kd * 96, s_red + kd * 1536 + cd * 8);
  __syncthreads();
  const int o4 = tid + (tid < 160 ? 0 : 32);
  if (tid < 320) {
    const float4 *r = (const float4*)s_red + o4, a = r[0], b = r[384], c = r[768], d = r[1152];
    ((float4*)p.s->ffn)[sc * 320 + tid] = make_float4(a.x + b.x + c.x + d.x, a.y + b.y + c.y + d.y, a.z + b.z + c.z + d.z, a.w + b.w + c.w + d.w);
  }
  __syncthreads();
  if (tid == 0) { __threadfence(); s_c[0].x = (atomicAdd(&p.s->flag[FL_SIDE], 1u) & 3u) == 3u; __threadfence(); }
  __syncthreads();
  if (s_c[0].x) {
    if (tid < 320) {
      const float4 *r = (const float4*)p.s->ffn + tid, a = __ldcg(r), b = __ldcg(r + 320), c = __ldcg(r + 640), d = __ldcg(r + 960), x = ((float4*)s_x)[tid];
      const float rs = rbf(sigmoid_f(tid < 160 ? v0 : v1));
      auto gate = [&](float xn, float y) { return silu_f(rbf(xn + rbf(rbf(y) * rs))); };
      if (tid == 0) { p.s->sel[0] = i0; p.s->sel[1] = i1; }
      ((uint2*)p.s->gsel)[tid] =
          make_uint2(pack_bf16(gate(x.x, a.x + b.x + c.x + d.x), gate(x.y, a.y + b.y + c.y + d.y)), pack_bf16(gate(x.z, a.z + b.z + c.z + d.z), gate(x.w, a.w + b.w + c.w + d.w)));
    }
    __syncthreads();
    if (tid == 0) red_release(&p.s->flag[FL_FFN]);
  }
}

constexpr float SM_C = 0.07216878364870322f * 1.4426950408889634f;

constexpr int LD = 0, LS = 3;
__device__ __forceinline__ void ln_piece(const Params& p, uint32_t (&r)[48], int k, int row, int l16) {
  auto f = [&](int i) { return __uint_as_float(r[i]); };
  if (k == LD) {
#pragma unroll
    for (int i = 0; i < 5; i++) {
      const uint4 v = ldg_nc((const uint4*)(p.x + (size_t)row * DM) + i * 16 + l16);
      r[4 * i] = v.x; r[4 * i + 1] = v.y; r[4 * i + 2] = v.z; r[4 * i + 3] = v.w;
    }
    asm volatile("ld.relaxed.gpu.global.v2.u32 {%0,%1}, [%2];" : "=r"(r[20]), "=r"(r[21]) : "l"(&p.s->done));
  } else if (k == LS || k == LS + 1) {
    if (k == LS) { r[22] = __shfl_sync(~0u, r[0], 0, 16) << 16; r[23] = r[24] = 0; }
    float s0 = f(23), s1 = 0.f, q0 = f(24), q1 = 0.f;
#pragma unroll
    for (int i = 10 * (k - LS); i < 10 * (k - LS) + 10; i++) {
      const float a = bf_lo(r[i]) - f(22), b = bf_hi(r[i]) - f(22);
      s0 += a; s1 += b; q0 = fmaf(a, a, q0); q1 = fmaf(b, b, q1);
    }
    r[23] = __float_as_uint(s0 + s1); r[24] = __float_as_uint(q0 + q1);
  } else if (k == LS + 2) {
    float s0 = f(23), q0 = f(24);
#pragma unroll
    for (int o = 8; o > 0; o >>= 1) { s0 += __shfl_xor_sync(~0u, s0, o); q0 += __shfl_xor_sync(~0u, q0, o); }
    s0 *= 1.f / DM;
    const float mean = f(22) + s0, var = rbf(fmaxf(fmaf(q0, 1.f / DM, -s0 * s0), 0.f));
    float sd; asm("sqrt.approx.ftz.f32 %0, %1;" : "=f"(sd) : "f"(rbf(var + 1e-5f)));
    const float inv = rcp(rbf(sd));
    r[22] = pack_bf16(mean, mean); r[23] = __float_as_uint(inv * SM_C);
    const uint32_t tag = __funnelshift_r(r[20], r[21], 7) + 1;
    if (l16 == 0) st_pkt8(&p.s->stat[row], __byte_perm(tag, r[22], 0x7610), __float_as_uint(inv));
  } else if (k > LS + 2 && k <= LS + 5) {
#pragma unroll
    for (int j = 2 * (k - LS - 3); j < 2 * (k - LS - 3) + 2 && j < 5; j++) {
#pragma unroll
      for (int i = 4 * j; i < 4 * j + 4; i++) { const uint32_t d = hsub2(r[i], r[22]); r[i] = pack_bf16(bf_lo(d) * f(23), bf_hi(d) * f(23)); }
      *((uint4*)(p.s->xn + (size_t)row * DM) + j * 16 + l16) = make_uint4(r[4 * j], r[4 * j + 1], r[4 * j + 2], r[4 * j + 3]);
    }
  }
}

constexpr float SM_HI = 0x1p64f, SM_LO = 0x1p-64f;
__device__ __forceinline__ void exp_block(float (&s)[32], float& l0, float& l1, int from = 0, int to = 32) {
#pragma unroll
  for (int i = from; i < to; i++) { s[i] = ex2(s[i]); if (i & 2) l1 += s[i]; else l0 += s[i]; }
}
__device__ __forceinline__ float quad_sum(float v) { v += __shfl_xor_sync(~0u, v, 1); return v + __shfl_xor_sync(~0u, v, 2); }
__device__ __forceinline__ float quad_max(float v) { v = fmaxf(v, __shfl_xor_sync(~0u, v, 1)); return fmaxf(v, __shfl_xor_sync(~0u, v, 2)); }
__device__ __noinline__ void safe_head(const uint32_t* kp, const uint32_t* vp, uint4* io) {
  uint32_t fq[48];
#pragma unroll
  for (int i = 0; i < 12; i++) { const uint4 v = io[(i >> 1) * 512 + (i & 1) * 32]; fq[4 * i] = v.x; fq[4 * i + 1] = v.y; fq[4 * i + 2] = v.z; fq[4 * i + 3] = v.w; }
  float m0 = -INFINITY, m1 = -INFINITY;
#pragma unroll 1
  for (int pass = 0; pass < 3; pass++) {
    float o[48] = {}, l0 = 0.f, l1 = 0.f;
#pragma unroll 1
    for (int n = 0; n < 64; n++) {
      const uint32_t *kr = kp + n * (8 * DH / 2), *vr = vp + n * (8 * DH / 2) + (pass - 1) * 48;
      float d[4] = {};
#pragma unroll
      for (int t = 0; t < 12; t++)
        asm volatile("mma.sync.aligned.m16n8k16.row.col.f32.bf16.bf16.f32 {%0,%1,%2,%3}, {%4,%5,%6,%7}, {%8,%9}, {%0,%1,%2,%3};"
                     : "+f"(d[0]), "+f"(d[1]), "+f"(d[2]), "+f"(d[3])
                     : "r"(fq[4 * t]), "r"(fq[4 * t + 1]), "r"(fq[4 * t + 2]), "r"(fq[4 * t + 3]), "r"(__ldg(kr + 8 * t)), "r"(__ldg(kr + 8 * t + 4)));
      if (pass == 0) { m0 = fmaxf(m0, fmaxf(d[0], d[1])); m1 = fmaxf(m1, fmaxf(d[2], d[3])); continue; }
      d[0] = ex2(d[0] - m0); d[1] = ex2(d[1] - m0); d[2] = ex2(d[2] - m1); d[3] = ex2(d[3] - m1);
      l0 += d[0] + d[1]; l1 += d[2] + d[3];
      const uint32_t p0 = pack_bf16(d[0], d[1]), p1 = pack_bf16(d[2], d[3]);
#pragma unroll
      for (int c = 0; c < 12; c++)
        asm volatile("{\n.reg .b32 t;\nmovmatrix.sync.aligned.m8n8.trans.b16 t, %6;\n"
                     "mma.sync.aligned.m16n8k8.row.col.f32.bf16.bf16.f32 {%0,%1,%2,%3}, {%4,%5}, {t}, {%0,%1,%2,%3};\n}\n"
                     : "+f"(o[4 * c]), "+f"(o[4 * c + 1]), "+f"(o[4 * c + 2]), "+f"(o[4 * c + 3]) : "r"(p0), "r"(p1), "r"(__ldg(vr + 4 * c)));
    }
    if (pass == 0) { m0 = quad_max(m0); m1 = quad_max(m1); continue; }
    l0 = rcp(quad_sum(l0)); l1 = rcp(quad_sum(l1));
#pragma unroll
    for (int i = 0; i < 6; i++) {
      const float* v = o + 16 * (i >> 1) + 2 * (i & 1);
      const float r = i & 1 ? l1 : l0;
      io[(3 * (pass - 1) + (i >> 1)) * 512 + (i & 1) * 32] =
          make_uint4(pack_bf16(v[0] * r, v[1] * r), pack_bf16(v[4] * r, v[5] * r), pack_bf16(v[8] * r, v[9] * r), pack_bf16(v[12] * r, v[13] * r));
    }
  }
}

__device__ __forceinline__ constexpr int end_stage(int n) { return n < 4 ? n : n < 6 ? n - 4 : n == 6 ? 4 : n % 5; }
__device__ __forceinline__ constexpr int sent(int n) { return n < 8 ? 0 : n < 9 ? 3 : n < 11 ? 5 : n < 13 ? 8 : n < 16 ? 10 : n < 17 ? 14 : 15; }
template <int N> struct IntC { static constexpr int value = N; };
template <int N, int I = 0, class F> __device__ __forceinline__ void static_for(F&& f) { if constexpr (I < N) { f(IntC<I>{}); static_for<N, I + 1>(f); } }

extern __shared__ __align__(1024) uint8_t smem_raw[];
constexpr uint32_t EA = 160, EB = 184;
#define SMEM_LAYOUT                                                                                                          \
  [[maybe_unused]] const uint32_t sb = smem_u32(smem_raw), bar_a = sb + OFF_M, bar_b = bar_a + 40, bar_x = bar_a + 88,      \
      bar_u = bar_a + 96, bar_e = bar_a + 104, bar_o = bar_a + 200, bar_w = bar_a + 208, bar_z = bar_a + 288,                \
      bar_s = bar_a + 296, bar_d = bar_a + 304, s_stat = bar_a + 512, s_sel = s_stat + 1024;

__device__ __forceinline__ int cluster_role() {
  uint32_t t, n;
  asm("mov.u32 %0, %%smid;" : "=r"(t)); asm("mov.u32 %0, %%nsmid;" : "=r"(n));
  t >>= 1;
  return n != 132 ? blockIdx.x >> 1 : t < 32 ? t : t < 60 ? t + 1 + (((t - 32) * 37) >> 8) : t < 62 ? t + 4 : (t - 58) * 8;
}

__device__ __forceinline__ int k_block(int t, int hg) {
  const int i = (t * 11) >> 5;
  return ((i < 6 ? (hg & 6) + (i & 1) : hg ^ (i & 1)) * 4 + (i >> 1)) * 6 + (t == 3 * i ? 4 : 2 * (t - 3 * i) - 2);
}

__device__ __noinline__ int errands(Scratch* s, const Maps& m, int qt, int hg, int warp, uint32_t tag, int budget) {
  SMEM_LAYOUT
  const int lane = threadIdx.x & 31, kq = hg >> 1, nh = hg & 1;
  if (warp == 1) {
#pragma unroll 1
    for (int u = 0; u < 5; u++) {
      mbar_wait(bar_o, u & 1);
      if (lane == 0) red_release(&s->flag[u ? FL_O + (qt * 8 + hg) * 8 : FL_XN + qt * 32]);
      __syncwarp();
    }
  } else if (warp == 2) {
    mbar_wait(bar_x, 0, budget);
    while ((int)(ld_acquire(&s->flag[FL_FFN]) - tag) < 0 && --budget >= 0) {}
    if (lane < 21) {
      const uint4 v = __ldcg(lane ? (const uint4*)(s->gsel + (lane > 10 ? DM - 80 : 0) + nh * 320 + kq * 80) + lane - 1 : (const uint4*)s->sel);
      asm volatile("st.shared.v4.u32 [%0], {%1,%2,%3,%4};" ::"r"(s_sel + 16 * lane), "r"(v.x), "r"(v.y), "r"(v.z), "r"(v.w) : "memory");
    }
    __syncwarp();
    if (lane == 0) { mbar_arrive(bar_u); asm volatile("red.relaxed.gpu.global.add.u64 [%0], 1;" ::"l"(&s->done) : "memory"); }
    while ((int)(ld_acquire(&s->flag[FL_RD + (qt * 8 + (hg ^ 1)) * 8]) - tag) < 0 && --budget >= 0) {}
    if (lane < 3) mbar_arrive(bar_z);
  } else {
    wait_flag(&s->flag[FL_XN + qt * 32], tag * 8);
    fence_proxy_async();
    mbar_wait(bar_a + EA + 32, 1);
    uint32_t a8 = 0, pha = 1;
    const int kb = (qt * 192 + k_block(lane, hg)) * 512;
#pragma unroll 1
    for (int n = 0; n < 54; n++) {
      const int t = n - 30, ko = __shfl_sync(~0u, kb, t);
      if (t == 0 || t == 18) {
        wait_flag(&s->flag[FL_O + (qt * 8 + (t ? 2 * kq + (lane & 1) : lane & 7)) * 8], tag * 4 - (t ? 0 : 1));
        fence_proxy_async();
      }
      mbar_wait(bar_a + EA + a8, pha);
      const uint32_t fb = bar_a + a8, dst = sb + a8 * (TA >> 3);
      if (elect()) {
        if (t >= 0) {
          mbar_expect_tx(fb, TA);
          bulk_load(dst, s->o + ko, TA, fb);
          if (t == 8) {
            mbar_expect_tx(bar_x, 6 * 3840);
#pragma unroll 1
            for (int e = 0; e < 6; e++) tma2d(sb + OFF_B + TW + e * TB, &m.xg, nh * 320 + kq * 80, qt * 128 + e * 24, bar_x);
            asm volatile("prefetch.tensormap [%0];\nprefetch.tensormap [%1];\nprefetch.tensormap [%2];\nprefetch.tensormap [%3];"
                         ::"l"(m.w3), "l"(m.w3 + 1), "l"(&m.xe), "l"(&m.out) : "memory");
          }
          if (t == 22) asm volatile("red.relaxed.gpu.global.add.u32 [%0], 1;" ::"l"(&s->flag[FL_RD + (qt * 8 + hg) * 8]) : "memory");
        } else if (n >= 10 && pha) mbar_arrive(fb);
        else { mbar_expect_tx(fb, TA); tma2d(dst, &m.xn, 8 * a8 + (pha || (n >= 15 && n < 20) ? 0 : 320), qt * 128, fb); }
      }
      a8 += 8; if (a8 == 40) { a8 = 0; pha ^= 1; }
    }
    if (lane < 3) mbar_arrive(bar_z);
  }
  return budget;
}

__global__ void __launch_bounds__(384, 1) __cluster_dims__(2, 1, 1)
fused_kernel(const Params p, const __grid_constant__ Maps m) {
  SMEM_LAYOUT
  const int wi = __shfl_sync(~0u, threadIdx.x >> 5, 0), wg = wi >> 2;
  const int lane = threadIdx.x & 31;
  const int cl = cluster_role();
  const int rank = blockIdx.x & 1;

  if (cl >= 64) {
    const unsigned epoch = (unsigned)(__ldcg(&p.s->done) >> 7);
    side_cta(p, 2 * cl + rank - 128, epoch, (float*)smem_raw);
    return;
  }
  const int qt = (cl & 7) * 2 + rank, hg = cl >> 3;
  const int kq = hg >> 1, nh = hg & 1;

  const int s0 = qt < 8 ? 0 : 5, kg0 = 10 * ((qt >> 1) & 3);
  if (elect()) {
    const int c = (int)(0x5ff7700000ull >> (4 * wi) & 15) + 1;
    for (int i = 0; i < 4; i++) mbar_init(bar_a + 32 * wi + 8 * i, c);
    asm volatile("fence.mbarrier_init.release.cluster;" ::: "memory");
  }
  __syncwarp();
  cluster_arrive();
  if (wi < 2 && elect()) {
    if (wi) { asm volatile("prefetch.tensormap [%0];" ::"l"(&m.wq) : "memory"); mbar_expect_tx(bar_b, TB); mbar_expect_tx(bar_b + 8, TB); }
    else for (int i = 0; i < 2; i++) { mbar_expect_tx(bar_a + 8 * i, TA); tma2d(sb + i * TA, &m.x, 64 * (s0 + i), qt * 128, bar_a + 8 * i); }
  }
  __syncwarp();
  cluster_wait();
  if (wi == 1 && elect())
    for (int i = 0; i < 2; i++) tma4d_mc(sb + OFF_B + i * TB + rank * (TB / 2), &m.wq, 12 * hg, 8 * (s0 + i) + 4 * rank, bar_b + 8 * i);
  if (wg > 0) {
    const int w = wg - 1;
    const int cw = wi - 4;
    asm volatile("setmaxnreg.inc.sync.aligned.u32 232;");
    uint32_t fr[48];
    reg_fence(fr);
    auto ln_row = [&]() { int v = qt * 128 + hg * 16 + cw * 2 + (lane >> 4); asm volatile("" : "+r"(v)); return v; };
    uint32_t rel_addr;
    asm volatile("mapa.shared::cluster.u32 %0, %1, %2;" : "=r"(rel_addr) : "r"(bar_b + EB), "r"(lane & 1));
    auto rel_a = [&](uint32_t o8) { if (lane == 0) mbar_arrive(bar_a + EA + o8); };
    auto rel_b = [&](uint32_t o8) { if (lane < 2) mbar_arrive_cluster(rel_addr + o8); };
    uint32_t b8 = 0, phb = 0;
    auto next_pair = [&]() { b8 += 16; if (b8 == 48) { b8 = 0; phb ^= 1; } };
    const int g = lane >> 2, q = lane & 3;
    constexpr uint64_t HI_A = desc_hi(16, 1024, 1);
    constexpr uint64_t HI_W = desc_hi(1024, 3072, 1);
    constexpr uint64_t HI_O = desc_hi(2048, 512, 2);
    if (w == 1) asm volatile("bar.arrive 1, 256;" ::: "memory");

    uint32_t zero; asm volatile("mov.u32 %0, %%tid.y;" : "=r"(zero));
    float acc[96];
    uint4* optr = p.s->o + (size_t)(qt * 192 + hg * 24) * 512 + (cw * 16 + g) * 4 + (q ^ ((g >> 1) & 3));
    uint32_t rl[4];
    auto store_o = [&](int pp) {
#pragma unroll
      for (int i = (12 * pp + 8) / 9; i < (12 * (pp + 1) + 8) / 9; i++) {
#pragma unroll
        for (int k = 4 * i; k < 4 * i + 4; k++)
          asm volatile("{\n.reg .b32 t;\nmul.rn.bf16x2 t, %0, %2;\nfma.rn.bf16x2 %0, %0, %1, t;\n}\n" : "+r"(fr[k]) : "r"(rl[i & 1]), "r"(rl[2 + (i & 1)]));
        fr[4 * i] &= ~1u;
        optr[(i >> 1) * 512 + (i & 1) * 32] = make_uint4(fr[4 * i], fr[4 * i + 1], fr[4 * i + 2], fr[4 * i + 3]);
      }
      if (pp == 8) optr += 6 * 512;
    };
    auto fresh = [&]() { uint32_t v = sb; asm volatile("" : "+r"(v)); return v; };
    reg_fence(rl);

#pragma unroll 1
    for (int u = 0; u < 4; u++) {
      const uint32_t sq = fresh();
      const uint64_t dA = mkdesc(sq + w * 8192, HI_A), dB0 = mkdesc(sq + OFF_B, HI_W);
      uint32_t pb8 = 0;
#pragma unroll
      for (int s = 0; s < 10; s++) {
        const uint32_t o8 = b8 + 8 * (s & 1);
        const uint64_t dW = dB0 + o8 * (TB >> 7);
        mbar_wait(bar_a + 8 * (s % 5), s / 5);
        mbar_wait(bar_b + o8, phb);
        if (s == 9 || (s >= LS && u == 0)) asm volatile("bar.sync %0, 256;" ::"r"(1 + w) : "memory");
        WG_FENCE();
#pragma unroll
        for (int kk = 0; kk < 4; kk++) wg_ss192t(acc, dA + ((s % 5) * (TA >> 4) + kk * 2), dW + kk * 384, kk != 0 || s != 0);
        WG_COMMIT();
        if (s >= LS && (s == 9) == (u > 0)) asm volatile("bar.arrive %0, 256;" ::"r"(2 - w) : "memory");
        if (s > 0) { WG_WAIT(1); rel_a(8 * ((s - 1) % 5)); rel_b(pb8); }
        if (s < 9) { if (u > 0) store_o(s); else ln_piece(p, fr, s, ln_row(), lane & 15); }
        if (s == 8) { __syncwarp(); if (lane == 0) mbar_arrive(bar_o); }
        pb8 = o8;
        if (s & 1) next_pair();
      }
      if (u == 0) {
        mbar_wait(bar_s, 0);
        const uint2 s0 = lds64(s_stat + (cw * 16 + g) * 8), s1 = lds64(s_stat + 64 + (cw * 16 + g) * 8);
        const uint32_t msk = q == 0 ? 0xffffffffu : q == 1 ? 0xffffu : 0u;
        const float c0 = SM_C * __uint_as_float(s0.y), c1 = SM_C * __uint_as_float(s1.y);
        uint32_t am[4] = {(s0.x ^ 0x80008000u) & msk, (s1.x ^ 0x80008000u) & msk, 0, 0};
        reg_fence(am);
        WG_FENCE();
        wg_rs192t(acc, am[0], am[1], am[2], am[3], mkdesc(sb, desc_hi(1024, 0, 1)), 1);
        WG_COMMIT();
        asm volatile("bar.arrive %0, 256;" ::"r"(2 - w) : "memory");
        WG_WAIT(0);
        reg_fence(acc);
#pragma unroll
        for (int i = 0; i < 24; i++) { acc[4 * i] *= c0; acc[4 * i + 1] *= c0; acc[4 * i + 2] *= c1; acc[4 * i + 3] *= c1; }
      } else { WG_WAIT(0); reg_fence(acc); }
      rel_b(pb8);
      rel_a(32);
#pragma unroll
      for (int i = 0; i < 48; i++) fr[i] = pack_bf16(acc[2 * i], acc[2 * i + 1]);
      reg_fence(fr);
      float sc[32], l0 = 0.f, l1 = 0.f;
      uint32_t pf[16], k8;
      auto pack_p = [&](const float (&s_)[32], int from = 0, int to = 16) {
#pragma unroll
        for (int i = from; i < to; i++) pf[i] = pack_bf16(s_[2 * i], s_[2 * i + 1]);
      };
      auto scores = [&](int j, int pass = 11) {
        k8 = b8 + 8;
        mbar_wait(bar_b + k8, phb);
        next_pair();
        mbar_wait(bar_b + b8, phb);
        const uint64_t dk = mkdesc(sb + OFF_B, HI_W) + k8 * (TB >> 7);
        asm volatile("bar.sync %0, 256;" ::"r"(1 + w) : "memory");
        WG_FENCE();
#pragma unroll
        for (int t = 0; t < 12; t++) {
          wg_rs64(sc, fr[4 * t], fr[4 * t + 1], fr[4 * t + 2], fr[4 * t + 3], dk + (t >> 2) * 64 + (t & 3) * 2, t != 0);
          if (t == 11) WG_COMMIT();
          if (t == pass) asm volatile("bar.arrive %0, 256;" ::"r"(2 - w) : "memory");
        }
      };
      auto pv = [&](int add) {
        const uint64_t dv = mkdesc(sb + OFF_B, HI_W) + b8 * (TB >> 7);
#pragma unroll
        for (int kk = 0; kk < 4; kk++) wg_rs192t(acc, pf[4 * kk], pf[4 * kk + 1], pf[4 * kk + 2], pf[4 * kk + 3], dv + kk * 384, kk != 0 || add);
        WG_COMMIT();
      };
      auto finish = [&]() {
        WG_WAIT(1);
        reg_fence(sc);
        exp_block(sc, l0, l1);
        rel_b(k8 + (__float_as_uint(l0) & __float_as_uint(l1) & zero));
        WG_WAIT(0);
        reg_fence(acc); reg_fence(pf);
        rel_b(b8);
        pack_p(sc);
      };
      {
        mbar_wait(bar_b + b8, phb);
        const uint64_t dk = mkdesc(sb + OFF_B, HI_W) + b8 * (TB >> 7);
        asm volatile("bar.sync %0, 256;" ::"r"(1 + w) : "memory");
#pragma unroll
        for (int t = 0; t < 12; t++) {
          if (t == 0) WG_FENCE();
          wg_rs64(sc, fr[4 * t], fr[4 * t + 1], fr[4 * t + 2], fr[4 * t + 3], dk + (t >> 2) * 64 + (t & 3) * 2, t != 0);
          if (t == 7) asm volatile("bar.arrive %0, 256;" ::"r"(2 - w) : "memory");
        }
        WG_COMMIT();
        WG_WAIT(0);
        reg_fence(sc);
        constexpr int NE = 8;
        float s0[32];
#pragma unroll
        for (int i = 0; i < 32; i++) s0[i] = i < NE ? sc[i] : __uint_as_float(__float_as_uint(sc[i]) ^ zero);
        exp_block(s0, l0, l1, 0, NE);
        pack_p(s0, 0, NE / 2);
#pragma unroll
        for (int i = NE; i < 32; i++) asm volatile("" : "+f"(s0[i])::"memory");
#pragma unroll
        for (int i = 0; i < NE / 2; i++) asm volatile("" : "+r"(pf[i])::"memory");
        rel_b(b8);
        scores(1, 8);
        const uint32_t z = lds32(s_stat) & zero;
#pragma unroll
        for (int i = NE; i < 32; i++) {
          asm("{\n.reg .pred p;\nsetp.eq.u32 p, %1, 0;\n@p ex2.approx.ftz.f32 %0, %0;\n}\n" : "+f"(s0[i]) : "r"(z));
          if (i & 2) l1 += s0[i]; else l0 += s0[i];
        }
        pack_p(s0, NE / 2, 16);
        reg_fence(pf);
        WG_FENCE();
        pv(0);
        finish();
      }
#pragma unroll 1
      for (int j = 2; j < 8; j++) { scores(j); pv(1); finish(); }
      const uint32_t v8 = b8 + 8;
      mbar_wait(bar_b + v8, phb);
      next_pair();
      {
        const uint64_t dv = mkdesc(sb + OFF_B, HI_W) + v8 * (TB >> 7);
        asm volatile("bar.sync %0, 256;" ::"r"(1 + w) : "memory");
        WG_FENCE();
#pragma unroll
        for (int kk = 0; kk < 4; kk++) {
          wg_rs192t(acc, pf[4 * kk], pf[4 * kk + 1], pf[4 * kk + 2], pf[4 * kk + 3], dv + kk * 384, 1);
          if (kk == 1 && (u < 3 || w == 0)) asm volatile("bar.arrive %0, 256;" ::"r"(2 - w) : "memory");
        }
        WG_COMMIT();
      }
      l0 = quad_sum(l0); l1 = quad_sum(l1);
      const bool unsafe = __any_sync(~0u, !(l0 >= SM_LO && l1 >= SM_LO && l0 + l1 <= SM_HI));
      l0 = rcp(l0); l1 = rcp(l1);
      rl[0] = pack_bf16(l0, l0); rl[1] = pack_bf16(l1, l1);
      l0 -= bf_lo(rl[0]); l1 -= bf_lo(rl[1]);
      rl[2] = pack_bf16(l0, l0); rl[3] = pack_bf16(l1, l1);
      WG_WAIT(0);
      reg_fence(acc);
      rel_b(v8);
      if (__builtin_expect(unsafe, 0)) {
        int o = hg * 4 + u; asm volatile("" : "+r"(o));
        o = (o * SKC + (SKC - WIN) + g) * (DH / 2) + q;
#pragma unroll
        for (int i = 0; i < 12; i++) optr[(i >> 1) * 512 + (i & 1) * 32] = make_uint4(fr[4 * i], fr[4 * i + 1], fr[4 * i + 2], fr[4 * i + 3]);
        safe_head((const uint32_t*)p.k + o, (const uint32_t*)p.v + o, optr);
#pragma unroll
        for (int i = 0; i < 12; i++) { const uint4 v = optr[(i >> 1) * 512 + (i & 1) * 32]; fr[4 * i] = v.x; fr[4 * i + 1] = v.y; fr[4 * i + 2] = v.z; fr[4 * i + 3] = v.w; }
        rl[0] = rl[1] = 0x3f803f80u; rl[2] = rl[3] = 0;
      } else {
#pragma unroll
        for (int i = 0; i < 24; i++) {
          fr[8 * (i >> 2) + (i & 3)] = pack_bf16(acc[4 * i], acc[4 * i + 1]);
          fr[8 * (i >> 2) + 4 + (i & 3)] = pack_bf16(acc[4 * i + 2], acc[4 * i + 3]);
        }
      }
    }

    float aF[80], aS[80];
    uint32_t pha = 0, a8 = 0, pa8 = 0, pb8 = 0;
#pragma unroll 1
    for (int s = 0; s < 19; s++) {
      const uint64_t d0 = mkdesc(sb, HI_O), dO = d0 + (a8 * (TA >> 7) + w * 256), dB = d0 + ((OFF_B >> 4) + b8 * (TB >> 7));
      mbar_wait(bar_a + a8, pha);
      mbar_wait(bar_b + b8, phb);
      WG_FENCE();
#pragma unroll
      for (int kk = 0; kk < 4; kk++) wg_ss160t(aF, dO + ((kk >> 1) * 512 + (kk & 1) * 2), dB + ((kk >> 1) * 640 + (kk & 1) * 64), kk != 0 || s != 0);
      WG_COMMIT();
      mbar_wait(bar_b + b8 + 8, phb);
      WG_WAIT(1);
      if (s > 0) { rel_a(pa8); rel_b(pb8 + 8); }
      WG_FENCE();
#pragma unroll
      for (int kk = 0; kk < 4; kk++) wg_ss160t(aS, dO + ((kk >> 1) * 512 + (kk & 1) * 2), dB + ((TB >> 4) + (kk >> 1) * 640 + (kk & 1) * 64), kk != 0 || s != 0);
      WG_COMMIT();
      if (s < 9) {
#pragma unroll
        for (int pp = 0; pp < 9; pp++) if (s == pp) store_o(pp);
        if (s == 8) { __syncwarp(); if (lane == 0) mbar_arrive(bar_o); }
      } else if (s < 15) {
        const int b = 2 * cw + ((lane >> 3) & 1);
        uint32_t ga = sb + OFF_B + TW + ((b * 11) >> 5) * (TB - 3840) + b * 1280 + (lane & 7) * 160 + (lane >> 4) * 16;
        if (s < 14) {
          mbar_wait(bar_x, 0);
          ga += 32 * (s - 9);
          ldsm4(ga, fr);
#pragma unroll
          for (int i = 0; i < 4; i++) {
            const uint2 st = lds64(s_stat + (cw * 16 + g + 8 * (i & 1)) * 8);
            const uint32_t d = hsub2(fr[i], st.x), xn = pack_bf16(bf_lo(d) * __uint_as_float(st.y), bf_hi(d) * __uint_as_float(st.y));
            fr[i] = pack_bf16(silu_f(bf_lo(xn)), silu_f(bf_hi(xn)));
          }
          stsm4(ga, fr);
        } else {
          mbar_wait(bar_u, 0);
          const uint2 sel = lds64(s_sel);
          const uint32_t row = qt * 128 + cw * 16 + (lane & 15);
          if (row == sel.x || row == sel.y) ga = s_sel + 16 + (row == sel.y ? 160 : 0) + (lane >> 4) * 16;
#pragma unroll
          for (int k = 0; k < 5; k++) ldsm4(ga + 32 * k, fr + 4 * k);
        }
      }
      WG_WAIT(1);
      rel_b(b8);
      pa8 = a8; a8 += 8; if (a8 == 40) { a8 = 0; pha ^= 1; }
      pb8 = b8; next_pair();
    }
    const int t128 = threadIdx.x & 127;
    uint4* const xbase = p.s->o + (size_t)(qt * 192 + nh * 24 + 10) * 512 + w * 640 + t128;
    uint4* const dst = xbase + kq * (48 * 512);
    float q1[40], q2[40], oth[40], own[40];
    auto take = [&](float (&x)[40], const float* a) {
#pragma unroll
      for (int k = 0; k < 40; k++) x[k] = __uint_as_float(__float_as_uint(a[k]) ^ zero);
      reg_fence(x);
    };
    reg_fence(aF);
    take(q1, aF);
    auto fa = [&](int i) { return mbar_try(bar_a + 8 * ((4 + i) % 5), i == 0); };
    auto fb = [&](int e) { return mbar_try(bar_b + 8 * (e % 6), (e / 6) & 1); };
    auto send = [&](int m) {
      const float* v = (m < 5 ? q1 : m < 10 ? q2 : oth) + 8 * (m % 5);
      st_pkt(dst + (m / 5) * 1280 + (m % 5) * 128, pack_bf16(v[0], v[1]) | 1, pack_bf16(v[2], v[3]), pack_bf16(v[4], v[5]), pack_bf16(v[6], v[7]));
    };
    static_for<20>([&](auto n_) {
      constexpr int n = n_.value, i = end_stage(n), e = 142 + n / 2, qi = n == 4 ? 1 : n == 6 ? 0 : n / 5;
      float (&acc_)[40] = qi == 0 ? q1 : qi == 1 ? q2 : qi == 2 ? oth : own;
      if (n == 0) while (!(fa(0) & fa(1) & fb(142) & fb(143))) {}
      if (n == 2) while (!(fa(2) & fa(3) & fb(144))) {}
      if (n == 6) while (!(fa(4) & fb(145) & fb(146) & mbar_try(bar_z, 0))) {}
      if (n == 10) while (!(fb(147) & fb(148) & fb(149))) {}
      const uint64_t d0 = mkdesc(fresh(), HI_O), dw = d0 + w * 256;
      WG_FENCE();
#pragma unroll
      for (int kk = 0; kk < 4; kk++)
        wg_ss80t(acc_, dw + (((4 + i) % 5) * (TA >> 4) + (kk >> 1) * 512 + (kk & 1) * 2),
                 d0 + ((OFF_B >> 4) + (e % 6) * (TB >> 4) + (n & 1) * 768 + (kk >> 1) * 384 + (kk & 1) * 64), 1);
      WG_COMMIT();
      if ((!(n & 1) && n <= 16) || n == 15 || n == 7) WG_WAIT(1);
      if (n == 0) rel_a(24);
      if (!(n & 1) && n <= 10) rel_b(8 * ((e - 1) % 6));
      if (n == 1) take(q2, aF + 40);
      if (n == 10) cluster_arrive();
      if (n == 12 || n == 14 || n == 16) rel_a(4u * n - 48);
      if (n == 7) reg_fence(q1);
      if (n == 10) reg_fence(q2);
      if (n == 15) reg_fence(oth);
      if (n == 14 || n == 17) while (!fb(n == 14 ? 150 : 151)) {}
      static_for<sent(n + 1) - sent(n)>([&](auto k_) { send(sent(n) + k_.value); });
      if (n == 8) {
        reg_fence(aS);
#pragma unroll
        for (int k = 0; k < 40; k++) oth[k] = kq & 1 ? aS[k] : aS[40 + k];
        reg_fence(oth);
      }
      if (n == 12) {
        reg_fence(aS);
#pragma unroll
        for (int k = 0; k < 40; k++) own[k] = kq & 1 ? aS[40 + k] : aS[k];
        reg_fence(own);
      }
    });
    uint32_t xr[20];
    const uint32_t xs = sb + OFF_B + 2 * TB + cw * 2560, xa = xs + (lane & 15) * 160 + (lane >> 4) * 16;
    auto load_x = [&]() {
      mbar_wait(bar_b + 16, 1);
#pragma unroll
      for (int k = 0; k < 5; k++) ldsm4(xa + 32 * k, xr + 4 * k);
    };
    {
      auto fetch = [&](int e, uint4 (&v)[5]) {
        mbar_wait(bar_e + 16 * e + 8 * w, 0);
#pragma unroll
        for (int i = 0; i < 5; i++) v[i] = lds128(sb + OFF_B + (3 + e) * TB + (w * 640 + i * 128 + t128) * 16);
      };
      auto add = [&](int e, uint4 (&v)[5]) {
        auto tags = [&]() { uint32_t t; asm("{\n.reg .b32 t;\nlop3.b32 t, %1, %2, %3, 0x80;\nlop3.b32 %0, t, %4, %5, 0x80;\n}\n" : "=r"(t) : "r"(v[0].x), "r"(v[1].x), "r"(v[2].x), "r"(v[3].x), "r"(v[4].x)); return t & 1; };
        while (!__all_sync(~0u, tags())) {
#pragma unroll
          for (int i = 0; i < 5; i++) v[i] = ld_pkt(xbase + (kq ^ ((0x132 >> (4 * e)) & 3)) * (48 * 512) + (e < 2 ? kq & 1 : 2) * 1280 + i * 128);
        }
#pragma unroll
        for (int i = 0; i < 5; i++) {
          float* o = own + 8 * i;
          o[0] += bf_lo(v[i].x); o[1] += bf_hi(v[i].x); o[2] += bf_lo(v[i].y); o[3] += bf_hi(v[i].y);
          o[4] += bf_lo(v[i].z); o[5] += bf_hi(v[i].z); o[6] += bf_lo(v[i].w); o[7] += bf_hi(v[i].w);
        }
      };
      uint4 v2[5];
      WG_WAIT(0);
      reg_fence(own);
#pragma unroll 1
      for (int e = 0; e < 2; e++) {
        uint4 v[5];
        fetch(e, v);
        if (e) {
#pragma unroll
          for (int i = 0; i < 5; i++) v2[i] = ld_pkt(xbase + (kq ^ 1) * (48 * 512) + 2 * 1280 + i * 128);
        }
        add(e, v);
      }
      load_x();
      add(2, v2);
      if (lane == 0) mbar_arrive(bar_w);
#pragma unroll
      for (int i = 0; i < 20; i++) xr[i] = hadd2(xr[i], hmul2(pack_bf16(own[2 * i], own[2 * i + 1]), fr[i]));
#pragma unroll
      for (int k = 0; k < 5; k++) stsm4(xa + 32 * k, xr + 4 * k);
      asm volatile("fence.proxy.async.shared::cta;" ::: "memory");
      __syncwarp();
      if (elect()) {
        tma2d_store(&m.out, xs, nh * 320 + kq * 80, qt * 128 + cw * 16);
        asm volatile("cp.async.bulk.commit_group;\ncp.async.bulk.wait_group.read 0;" ::: "memory");
      }
      __syncwarp();
    }
    cluster_wait();
  } else {
    asm volatile("setmaxnreg.dec.sync.aligned.u32 40;");
    uint32_t tid_; asm volatile("mov.u32 %0, %%tid.x;" : "=r"(tid_));
    const int warp = __shfl_sync(~0u, tid_ >> 5, 0);
    auto is_warp = [&](int k) { uint32_t e; asm volatile("{\n.reg .pred q;\nsetp.eq.u32 q, %1, %2;\nselp.u32 %0, 1, 0, q;\n}" : "=r"(e) : "r"(warp), "r"(k)); return e != 0; };
    if (warp > 0) {
      const unsigned epoch = (unsigned)(__ldcg(&p.s->done) >> 7);
      int budget = WAIT_BUDGET;
      const uint32_t tag = epoch + 1;
      mbar_wait(bar_a + EA, 0, budget);
      mbar_wait(bar_b + (kg0 & ~7), 0, budget); mbar_wait(bar_b + (kg0 & ~7) + 8, 0, budget);
      float cs0 = 0.f, cs1 = 0.f;
      const int n = rank * 96 + (warp - 1) * 32;
#pragma unroll 1
      for (int kg = kg0 + (lane >> 4) * 5, e = kg + 5; kg < e; kg++) {
        const uint32_t ad = sb + OFF_B + kg * 3072 + (n >> 6) * 1024 + (n & 63) * 2 + (lane & 15) * 4;
#pragma unroll
        for (int k = 0; k < 8; k++) { const uint32_t v = lds32(ad ^ (k * 0x90)); cs0 += bf_lo(v); cs1 += bf_hi(v); }
      }
      cs0 += __shfl_xor_sync(~0u, cs0, 16); cs1 += __shfl_xor_sync(~0u, cs1, 16);
      if (lane < 16) st_pkt8((uint2*)(p.s->cs + (hg * 4 + (qt >> 2)) * 96 + (n >> 1) + lane) + ((qt >> 1) & 1), (__float_as_uint(cs0) & ~3u) | (tag & 3), __float_as_uint(cs1));
      if (lane < 2) { uint32_t a; asm volatile("mapa.shared::cluster.u32 %0, %1, %2;" : "=r"(a) : "r"(bar_d), "r"(lane)); mbar_arrive_cluster(a); }
      mbar_wait(bar_a + EA, 1, budget);
      uint4 v[5];
      while (true) {
        uint32_t bad = 0;
#pragma unroll
        for (int i = 0; i < 5; i++) v[i] = ld_pkt(i < 4 ? p.s->cs + (hg * 4 + i) * 96 + (tid_ - 32) : (const uint4*)p.s->stat + qt * 64 + (tid_ & 63));
#pragma unroll
        for (int i = 0; i < 5; i++) bad |= (v[i].x ^ tag) | (v[i].z ^ tag);
        if (!__any_sync(~0u, bad & 3) || --budget < 0) break;
      }
      asm volatile("st.shared.v4.u32 [%0], {%1,%2,%3,%4};" ::"r"(s_stat + (tid_ & 63) * 16), "r"(__byte_perm(v[4].x, 0, 0x3232)), "r"(v[4].y), "r"(__byte_perm(v[4].z, 0, 0x3232)), "r"(v[4].w) : "memory");
      cs0 = cs1 = 0.f;
#pragma unroll
      for (int i = 0; i < 4; i++) { cs0 += __uint_as_float(v[i].x & ~3u) + __uint_as_float(v[i].z & ~3u); cs1 += __uint_as_float(v[i].y) + __uint_as_float(v[i].w); }
#pragma unroll
      for (int k = 0; k < 8; k++) {
        const uint32_t t = k < 3 ? pack_bf16(cs0, cs1) : 0;
        sts32((sb + (warp - 1) * 1024 + lane * 4) ^ (k * 0x90), t);
        cs0 -= bf_lo(t); cs1 -= bf_hi(t);
      }
      asm volatile("fence.proxy.async.shared::cta;" ::: "memory");
      __syncwarp();
      if (lane < 2) mbar_arrive(bar_s);
      budget = errands(p.s, m, qt, hg, warp, tag, budget);
      if (is_warp(2)) {
        mbar_wait(bar_w, 0, budget);
        if (budget < 0) asm volatile("st.global.u32 [%0], %1;" ::"l"(0ull), "r"(budget) : "memory");
      }
    } else {
      uint32_t fb = bar_b + 16, dst = sb + OFF_B + 2 * TB, ph = 1;
      auto next = [&]() { fb += 8; dst += TB; if (fb == bar_b + 48) { fb = bar_b; dst = sb + OFF_B; ph ^= 1; } };
#pragma unroll 1
      for (int u = 0; u < 4; u++) {
        const int h = hg * 4 + u;
        int s = u ? (u == 2 ? 5 : 0) : s0 + 2;
#pragma unroll 1
        for (int i = u ? 0 : 2; i < 10; i++) {
          if (u == 0) {
            const uint32_t a8 = 8 * (i < 5 ? i : i - 5);
            mbar_wait(bar_a + 8 * (i < 7 ? i - 2 : i - 7), i >= 7);
            mbar_wait(bar_a + EA + a8, i < 5);
            if (elect()) { mbar_expect_tx(bar_a + a8, TA); tma2d(sb + a8 * (TA >> 3), &m.x, 64 * s, qt * 128, bar_a + a8); }
            if (i == 6 + (kg0 >> 3)) mbar_wait(bar_d, 0);
          }
          mbar_wait(fb + EB, ph);
          if (elect()) { mbar_expect_tx(fb, TB); tma4d_mc(dst + rank * (TB / 2), &m.wq, 3 * h, 8 * s + 4 * rank, fb); }
          next();
          if (++s == 10) s = 0;
        }
        const int kv0 = (h * SKC + (SKC - WIN)) / 8 + 4 * rank;
#pragma unroll 1
        for (int i = 0; i < 16; i++) {
          const bool isk = (0x2AAB >> i) & 1;
          mbar_wait(fb + EB, ph);
          if (elect()) { mbar_expect_tx(fb, TB); tma4d_mc(dst + rank * (TB / 2), isk ? &m.k : &m.v, 0, kv0 + 8 * (isk ? (i + 1) >> 1 : (i - 1) >> 1), fb); }
          next();
        }
      }
      const int cF = 10 * nh + 5 - 5 * (kq >> 1), cS = 10 * nh + 5 * (kq >> 1);
      const int kb = 4 * (k_block(lane, hg) + rank);
#pragma unroll 1
      for (int n = 0; n < 38; n++) {
        const int c2 = __shfl_sync(~0u, kb, n >> 1);
        mbar_wait(fb + EB, ph);
        if (elect()) { mbar_expect_tx(fb, TW); tma5d_mc(dst + rank * (TW / 2), &m.wo, c2, n & 1 ? cS : cF, fb); }
        next();
      }
      const int odd = ((0x7fb0 ^ (kq & 1 ? 0xffc00 : 0)) >> lane) & 1;
      const int tq = __shfl_sync(~0u, kb, 19 + end_stage(lane)) << 16 | odd << 7 | ((lane < 10 ? cF : cS) + 2 * odd);
#pragma unroll 1
      for (int n = 0; n < 20; n += 2) {
        const int t0 = __shfl_sync(~0u, tq, n), t1 = __shfl_sync(~0u, tq, n + 1);
        mbar_wait(fb + EB, ph);
        if (elect()) {
          mbar_expect_tx(fb, TB);
          tma5d_mc(dst + rank * (TB / 4), (const CUtensorMap*)((const char*)m.w3 + (t0 & 128)), t0 >> 16, t0 & 31, fb);
          tma5d_mc(dst + TB / 2 + rank * (TB / 4), (const CUtensorMap*)((const char*)m.w3 + (t1 & 128)), t1 >> 16, t1 & 31, fb);
        }
        next();
      }
      mbar_wait(fb + EB, ph);
      if (elect()) { mbar_expect_tx(fb, TW); tma2d(dst, &m.xe, nh * 320 + kq * 80, qt * 128, fb); }
    }
    if (warp & 1) {
      const int e = warp >> 1, ms = 2 * e + ((lane >> 2) & 1);
      const uint4* src = p.s->o + (size_t)(qt * 192 + nh * 24 + 10 + (kq ^ ((0x132 >> (4 * e)) & 3)) * 48) * 512 + (e < 2 ? kq & 1 : 2) * 1280 + (ms & 1) * 640;
      uint32_t todo = 0xff;
      bool ok = lane >= 8;
      mbar_wait(bar_z, 0);
#pragma unroll 1
      while (todo) {
        if (!ok) ok = ld_pkt(src + 4 * 128 + (lane & 3) * 32 + 31).x & 1;
        const uint32_t got = __ballot_sync(~0u, ok) & todo, go = __ballot_sync(~0u, ((got >> (lane & 28)) & 15) == 15);
        if (go) mbar_wait(bar_a + EA + 8 * e, 0);
        if ((go & 0x11) >> lane & 1) {
          mbar_expect_tx(bar_e + 8 * ms, TW / 2); bulk_load(sb + OFF_B + (3 + e) * TB + (ms & 1) * (TW / 2), src, TW / 2, bar_e + 8 * ms);
        }
        todo &= ~go;
      }
    }
    cluster_sync();
  }
}

typedef CUresult (*EncodeFn)(CUtensorMap*, CUtensorMapDataType, cuuint32_t, void*, const cuuint64_t*, const cuuint64_t*,
                             const cuuint32_t*, const cuuint32_t*, CUtensorMapInterleave, CUtensorMapSwizzle,
                             CUtensorMapL2promotion, CUtensorMapFloatOOBfill);

void encode(EncodeFn fn, CUtensorMap* tm, void* base, int rank, const cuuint64_t* dims, const cuuint64_t* strides,
            const cuuint32_t* box, CUtensorMapSwizzle sw) {
  const cuuint32_t es[5] = {1, 1, 1, 1, 1};
  fn(tm, CU_TENSOR_MAP_DATA_TYPE_BFLOAT16, rank, base, dims, strides, box, es, CU_TENSOR_MAP_INTERLEAVE_NONE, sw,
     CU_TENSOR_MAP_L2_PROMOTION_L2_128B, CU_TENSOR_MAP_FLOAT_OOB_FILL_NONE);
}

}

extern "C" void kernel_launch(void* const* d_in, const int* in_sizes, int n_in, void* d_out, int out_size) {
  static EncodeFn fn = nullptr;
  static Scratch* scr = nullptr;
  if (!fn) {
    void* f = nullptr;
    cudaDriverEntryPointQueryResult st;
    cudaGetDriverEntryPoint("cuTensorMapEncodeTiled", &f, cudaEnableDefault, &st);
    fn = (EncodeFn)f;
    cudaGetSymbolAddress((void**)&scr, g_scratch);
    cudaFuncSetAttribute(fused_kernel, cudaFuncAttributeMaxDynamicSharedMemorySize, SMEM_BYTES);
  }
  Maps m;
  { const cuuint64_t d[2] = {DM, SQ}, s[1] = {DM * 2}; const cuuint32_t b[2] = {64, 128};
    encode(fn, &m.x, d_in[0], 2, d, s, b, CU_TENSOR_MAP_SWIZZLE_128B);
    encode(fn, &m.xn, scr->xn, 2, d, s, b, CU_TENSOR_MAP_SWIZZLE_128B); }
  { const cuuint64_t d[4] = {64, 8, QD / 64, DM / 8}, s[3] = {QD * 2, 128, 8 * QD * 2}; const cuuint32_t b[4] = {64, 8, 3, 4};
    encode(fn, &m.wq, d_in[3], 4, d, s, b, CU_TENSOR_MAP_SWIZZLE_128B); }
  { const cuuint64_t d[4] = {64, 8, 3, NH * SKC / 8}, s[3] = {DH * 2, 128, 8 * DH * 2}; const cuuint32_t b[4] = {64, 8, 3, 4};
    encode(fn, &m.k, d_in[1], 4, d, s, b, CU_TENSOR_MAP_SWIZZLE_128B);
    encode(fn, &m.v, d_in[2], 4, d, s, b, CU_TENSOR_MAP_SWIZZLE_128B); }
  {
    const cuuint64_t d[5] = {32, 2, QD / 8, 4, DM / 32}, s[4] = {DM * 2, 8 * DM * 2, 2 * DM * 2, 64}; const cuuint32_t b[5] = {32, 2, 4, 4, 5};
    encode(fn, &m.wo, d_in[4], 5, d, s, b, CU_TENSOR_MAP_SWIZZLE_64B);
    const cuuint32_t b3[5] = {32, 2, 4, 4, 3};
    encode(fn, &m.w3[0], d_in[4], 5, d, s, b3, CU_TENSOR_MAP_SWIZZLE_64B);
    encode(fn, &m.w3[1], (char*)d_in[4] + 32, 5, d, s, b3, CU_TENSOR_MAP_SWIZZLE_64B); }
  { const cuuint64_t d[2] = {DM, SQ}, s[1] = {DM * 2}; const cuuint32_t bg[2] = {80, 24}, bx[2] = {80, 128}, bo[2] = {80, 16};
    encode(fn, &m.xg, d_in[0], 2, d, s, bg, CU_TENSOR_MAP_SWIZZLE_NONE);
    encode(fn, &m.xe, d_in[0], 2, d, s, bx, CU_TENSOR_MAP_SWIZZLE_NONE);
    encode(fn, &m.out, d_out, 2, d, s, bo, CU_TENSOR_MAP_SWIZZLE_NONE); }
  Params p;
  p.x = (const __nv_bfloat16*)d_in[0]; p.wr = (const __nv_bfloat16*)d_in[6]; p.wg = (const __nv_bfloat16*)d_in[7];
  p.wu = (const __nv_bfloat16*)d_in[8]; p.wd = (const __nv_bfloat16*)d_in[9];

  p.k = (const __nv_bfloat16*)d_in[1]; p.v = (const __nv_bfloat16*)d_in[2]; p.s = scr;
  cudaLaunchConfig_t cfg = {};
  cfg.gridDim = dim3(132); cfg.blockDim = dim3(384); cfg.dynamicSmemBytes = SMEM_BYTES; cfg.stream = cudaStreamPerThread;
  cudaLaunchKernelEx(&cfg, fused_kernel, p, m);
}
```

```cpp
#include <cuda_runtime.h>
#include <cuda_bf16.h>
#include <cuda.h>
#include <stdint.h>

namespace {

constexpr int SQ = 2048, DM = 640, NH = 32, DH = 192, SKC = 2048, WIN = 512, FF = 1536;
constexpr int QD = NH * DH;
constexpr uint32_t TA = 16384, TB = 24576, TW = 20480, OFF_B = 5 * TA, OFF_M = OFF_B + 6 * TB, SMEM_BYTES = OFF_M + 3072;
constexpr int WAIT_BUDGET = 1 << 20;

constexpr int FL_XN = 0;
constexpr int FL_O = 512;
constexpr int FL_RD = FL_O + 1024;
constexpr int FL_FFN = FL_RD + 1024;
constexpr int FL_SIDE = FL_FFN + 32;
struct __align__(1024) Scratch {
  unsigned long long done, pad0[15];
  unsigned flag[FL_SIDE + 32];
  uint4 cand[8];
  float ffn[4 * 2 * DM];
  int sel[4];
  __nv_bfloat16 gsel[2 * DM];
  uint4 cs[8 * 4 * DH / 2];
  uint2 stat[SQ];
  __align__(1024) __nv_bfloat16 xn[SQ * DM];
  __align__(1024) uint4 o[SQ * QD / 8];
};
__device__ Scratch g_scratch;

__device__ __forceinline__ uint32_t smem_u32(const void* p) { return (uint32_t)__cvta_generic_to_shared(p); }
__device__ __forceinline__ void mbar_init(uint32_t bar, int cnt) { asm volatile("mbarrier.init.shared::cta.b64 [%0], %1;" ::"r"(bar), "r"(cnt)); }
__device__ __forceinline__ void mbar_expect_tx(uint32_t bar, uint32_t bytes) {
  asm volatile("mbarrier.arrive.expect_tx.shared::cta.b64 _, [%0], %1;" ::"r"(bar), "r"(bytes) : "memory");
}
__device__ __forceinline__ void mbar_arrive(uint32_t bar) { asm volatile("mbarrier.arrive.shared::cta.b64 _, [%0];" ::"r"(bar) : "memory"); }
__device__ __forceinline__ void mbar_arrive_cluster(uint32_t addr) { asm volatile("mbarrier.arrive.shared::cluster.b64 _, [%0];" ::"r"(addr) : "memory"); }
__device__ __forceinline__ bool mbar_try(uint32_t bar, uint32_t parity) {
  uint32_t ok;
  asm volatile("{\n.reg .pred p;\nmbarrier.try_wait.parity.shared::cta.b64 p, [%1], %2;\nselp.u32 %0, 1, 0, p;\n}\n" : "=r"(ok) : "r"(bar), "r"(parity) : "memory");
  return ok;
}
__device__ __forceinline__ void mbar_wait(uint32_t bar, uint32_t parity, int& budget) {
#pragma unroll 1
  while (!mbar_try(bar, parity)) { if (--budget < 0) break; }
}
__device__ __forceinline__ void mbar_wait(uint32_t bar, uint32_t parity) {
#pragma unroll 1
  while (!mbar_try(bar, parity)) {}
}
__device__ __forceinline__ unsigned ld_acquire(const unsigned* p) { unsigned v; asm volatile("ld.acquire.gpu.global.u32 %0, [%1];" : "=r"(v) : "l"(p) : "memory"); return v; }
__device__ __forceinline__ void wait_flag(const unsigned* p, unsigned target) {
#pragma unroll 1
  while (__any_sync(~0u, (int)(ld_acquire(p) - target) < 0)) {}
}
__device__ __forceinline__ void red_release(unsigned* p) { asm volatile("red.release.gpu.global.add.u32 [%0], 1;" ::"l"(p) : "memory"); }
__device__ __forceinline__ void fence_proxy_async() { asm volatile("fence.proxy.async.global;" ::: "memory"); }
__device__ __forceinline__ bool elect() {
  uint32_t p;
  asm volatile("{\n.reg .pred P;\nelect.sync _|P, 0xffffffff;\nselp.u32 %0, 1, 0, P;\n}\n" : "=r"(p));
  return p;
}
__device__ __forceinline__ void cluster_arrive() { asm volatile("barrier.cluster.arrive.relaxed.aligned;" ::: "memory"); }
__device__ __forceinline__ void cluster_wait() { asm volatile("barrier.cluster.wait.aligned;" ::: "memory"); }
__device__ __forceinline__ void cluster_sync() { cluster_arrive(); cluster_wait(); }
__device__ __forceinline__ void tma2d(uint32_t dst, const CUtensorMap* tm, int c0, int c1, uint32_t bar) {
  asm volatile("cp.async.bulk.tensor.2d.shared::cluster.global.mbarrier::complete_tx::bytes [%0], [%1, {%3, %4}], [%2];"
               ::"r"(dst), "l"(tm), "r"(bar), "r"(c0), "r"(c1) : "memory");
}
constexpr uint64_t POL_FIRST = 0x12F0000000000000ull;
__device__ __forceinline__ void tma4d_mc(uint32_t dst, const CUtensorMap* tm, int c2, int c3, uint32_t bar) {
  asm volatile("cp.async.bulk.tensor.4d.shared::cluster.global.mbarrier::complete_tx::bytes.multicast::cluster.L2::cache_hint [%0], [%1, {%3, %3, %4, %5}], [%2], %6, %7;"
               ::"r"(dst), "l"(tm), "r"(bar), "r"(0), "r"(c2), "r"(c3), "h"((uint16_t)3), "l"(POL_FIRST) : "memory");
}
__device__ __forceinline__ void tma5d_mc(uint32_t dst, const CUtensorMap* tm, int c2, int c4, uint32_t bar) {
  asm volatile("cp.async.bulk.tensor.5d.shared::cluster.global.mbarrier::complete_tx::bytes.multicast::cluster.L2::cache_hint [%0], [%1, {%3, %3, %4, %3, %5}], [%2], %6, %7;"
               ::"r"(dst), "l"(tm), "r"(bar), "r"(0), "r"(c2), "r"(c4), "h"((uint16_t)3), "l"(POL_FIRST) : "memory");
}
__device__ __forceinline__ void bulk_load(uint32_t dst, const void* src, uint32_t bytes, uint32_t bar) {
  asm volatile("cp.async.bulk.shared::cluster.global.mbarrier::complete_tx::bytes.L2::cache_hint [%0], [%1], %2, [%3], %4;" ::"r"(dst), "l"(src), "r"(bytes), "r"(bar), "l"(POL_FIRST) : "memory");
}
__device__ __forceinline__ void tma2d_store(const CUtensorMap* tm, uint32_t src, int c0, int c1) {
  asm volatile("cp.async.bulk.tensor.2d.global.shared::cta.bulk_group [%0, {%2, %3}], [%1];" ::"l"(tm), "r"(src), "r"(c0), "r"(c1) : "memory");
}
__device__ __forceinline__ uint32_t lds32(uint32_t a) { uint32_t v; asm volatile("ld.shared.u32 %0, [%1];" : "=r"(v) : "r"(a) : "memory"); return v; }
__device__ __forceinline__ uint2 lds64(uint32_t a) { uint2 v; asm volatile("ld.shared.v2.u32 {%0,%1}, [%2];" : "=r"(v.x), "=r"(v.y) : "r"(a) : "memory"); return v; }
__device__ __forceinline__ uint4 lds128(uint32_t a) { uint4 v; asm volatile("ld.shared.v4.u32 {%0,%1,%2,%3}, [%4];" : "=r"(v.x), "=r"(v.y), "=r"(v.z), "=r"(v.w) : "r"(a) : "memory"); return v; }
__device__ __forceinline__ void ldsm4(uint32_t a, uint32_t* v) {
  asm volatile("ldmatrix.sync.aligned.m8n8.x4.shared.b16 {%0,%1,%2,%3}, [%4];" : "=r"(v[0]), "=r"(v[1]), "=r"(v[2]), "=r"(v[3]) : "r"(a) : "memory");
}
__device__ __forceinline__ void stsm4(uint32_t a, const uint32_t* v) {
  asm volatile("stmatrix.sync.aligned.m8n8.x4.shared.b16 [%0], {%1,%2,%3,%4};" ::"r"(a), "r"(v[0]), "r"(v[1]), "r"(v[2]), "r"(v[3]) : "memory");
}
__device__ __forceinline__ void sts32(uint32_t a, uint32_t v) { asm volatile("st.shared.u32 [%0], %1;" ::"r"(a), "r"(v) : "memory"); }
__device__ __forceinline__ void st_pkt(uint4* p, uint32_t a, uint32_t b, uint32_t c, uint32_t d) {
  asm volatile("st.relaxed.gpu.global.v4.b32 [%0], {%1, %2, %3, %4};" ::"l"(p), "r"(a), "r"(b), "r"(c), "r"(d) : "memory");
}
__device__ __forceinline__ void st_pkt8(void* p, uint32_t a, uint32_t b) {
  asm volatile("{\n.reg .b64 v;\nmov.b64 v, {%1, %2};\nst.relaxed.gpu.global.b64 [%0], v;\n}\n" ::"l"(p), "r"(a), "r"(b) : "memory");
}
__device__ __forceinline__ uint4 ld_pkt(const uint4* p) {
  uint4 v;
  asm volatile("{\n.reg .b128 v;\nld.relaxed.gpu.global.b128 v, [%4];\nmov.b128 {%0, %1, %2, %3}, v;\n}\n" : "=r"(v.x), "=r"(v.y), "=r"(v.z), "=r"(v.w) : "l"(p) : "memory");
  return v;
}
__device__ __forceinline__ uint4 ldg_nc(const void* p) {
  uint4 v;
  asm volatile("ld.global.nc.v4.u32 {%0,%1,%2,%3}, [%4];" : "=r"(v.x), "=r"(v.y), "=r"(v.z), "=r"(v.w) : "l"(p));
  return v;
}
#define WG_FENCE() asm volatile("wgmma.fence.sync.aligned;" ::: "memory")
#define WG_COMMIT() asm volatile("wgmma.commit_group.sync.aligned;" ::: "memory")
#define WG_WAIT(n) asm volatile("wgmma.wait_group.sync.aligned " #n ";" ::: "memory")
template <int N> __device__ __forceinline__ void reg_fence(float (&d)[N]) {
#pragma unroll
  for (int i = 0; i < N; i++) asm volatile("" : "+f"(d[i])::"memory");
}
template <int N> __device__ __forceinline__ void reg_fence(uint32_t (&d)[N]) {
#pragma unroll
  for (int i = 0; i < N; i++) asm volatile("" : "+r"(d[i])::"memory");
}
__device__ __forceinline__ constexpr uint64_t desc_hi(uint32_t lbo, uint32_t sbo, uint64_t sw) {
  return ((uint64_t)(lbo >> 4) << 16) | ((uint64_t)(sbo >> 4) << 32) | (sw << 62);
}
__device__ __forceinline__ uint64_t mkdesc(uint32_t addr, uint64_t hi) { return hi | (uint64_t)((addr & 0x3FFFF) >> 4); }
__device__ __forceinline__ uint32_t pack_bf16(float lo, float hi) { uint32_t r; asm("cvt.rn.bf16x2.f32 %0, %1, %2;" : "=r"(r) : "f"(hi), "f"(lo)); return r; }
__device__ __forceinline__ float bf_lo(uint32_t v) { return __uint_as_float(v << 16); }
__device__ __forceinline__ float bf_hi(uint32_t v) { return __uint_as_float(v & 0xffff0000u); }
__device__ __forceinline__ uint32_t hadd2(uint32_t a, uint32_t b) { uint32_t r; asm("add.rn.bf16x2 %0, %1, %2;" : "=r"(r) : "r"(a), "r"(b)); return r; }
__device__ __forceinline__ uint32_t hsub2(uint32_t a, uint32_t b) { uint32_t r; asm("sub.rn.bf16x2 %0, %1, %2;" : "=r"(r) : "r"(a), "r"(b)); return r; }
__device__ __forceinline__ uint32_t hmul2(uint32_t a, uint32_t b) { uint32_t r; asm("mul.rn.bf16x2 %0, %1, %2;" : "=r"(r) : "r"(a), "r"(b)); return r; }
__device__ __forceinline__ float rbf(float x) { return __bfloat162float(__float2bfloat16_rn(x)); }
__device__ __forceinline__ float ex2(float x) { float y; asm("ex2.approx.ftz.f32 %0, %1;" : "=f"(y) : "f"(x)); return y; }
__device__ __forceinline__ float rcp(float x) { float y; asm("rcp.approx.ftz.f32 %0, %1;" : "=f"(y) : "f"(x)); return y; }
__device__ __forceinline__ float sigmoid_f(float x) { return rcp(1.f + ex2(x * -1.4426950408889634f)); }
__device__ __forceinline__ float silu_f(float x) { return x * sigmoid_f(x); }

__device__ __forceinline__ void wg_ss192t(float (&d)[96], uint64_t da, uint64_t db, int sd) {
  asm volatile("{\n.reg .pred p;\nsetp.ne.b32 p, %98, 0;\n"
    "wgmma.mma_async.sync.aligned.m64n192k16.f32.bf16.bf16 {%0,%1,%2,%3,%4,%5,%6,%7,%8,%9,%10,%11,%12,%13,%14,%15,%16,%17,%18,%19,%20,%21,%22,%23,%24,%25,%26,%27,%28,%29,%30,%31,%32,%33,%34,%35,%36,%37,%38,%39,%40,%41,%42,%43,%44,%45,%46,%47,%48,%49,%50,%51,%52,%53,%54,%55,%56,%57,%58,%59,%60,%61,%62,%63,%64,%65,%66,%67,%68,%69,%70,%71,%72,%73,%74,%75,%76,%77,%78,%79,%80,%81,%82,%83,%84,%85,%86,%87,%88,%89,%90,%91,%92,%93,%94,%95}, %96, %97, p, 1, 1, 0, 1;\n}\n"
    : "+f"(d[0]),"+f"(d[1]),"+f"(d[2]),"+f"(d[3]),"+f"(d[4]),"+f"(d[5]),"+f"(d[6]),"+f"(d[7]),"+f"(d[8]),"+f"(d[9]),"+f"(d[10]),"+f"(d[11]),"+f"(d[12]),"+f"(d[13]),"+f"(d[14]),"+f"(d[15]),"+f"(d[16]),"+f"(d[17]),"+f"(d[18]),"+f"(d[19]),"+f"(d[20]),"+f"(d[21]),"+f"(d[22]),"+f"(d[23]),"+f"(d[24]),"+f"(d[25]),"+f"(d[26]),"+f"(d[27]),"+f"(d[28]),"+f"(d[29]),"+f"(d[30]),"+f"(d[31]),"+f"(d[32]),"+f"(d[33]),"+f"(d[34]),"+f"(d[35]),"+f"(d[36]),"+f"(d[37]),"+f"(d[38]),"+f"(d[39]),"+f"(d[40]),"+f"(d[41]),"+f"(d[42]),"+f"(d[43]),"+f"(d[44]),"+f"(d[45]),"+f"(d[46]),"+f"(d[47]),"+f"(d[48]),"+f"(d[49]),"+f"(d[50]),"+f"(d[51]),"+f"(d[52]),"+f"(d[53]),"+f"(d[54]),"+f"(d[55]),"+f"(d[56]),"+f"(d[57]),"+f"(d[58]),"+f"(d[59]),"+f"(d[60]),"+f"(d[61]),"+f"(d[62]),"+f"(d[63]),"+f"(d[64]),"+f"(d[65]),"+f"(d[66]),"+f"(d[67]),"+f"(d[68]),"+f"(d[69]),"+f"(d[70]),"+f"(d[71]),"+f"(d[72]),"+f"(d[73]),"+f"(d[74]),"+f"(d[75]),"+f"(d[76]),"+f"(d[77]),"+f"(d[78]),"+f"(d[79]),"+f"(d[80]),"+f"(d[81]),"+f"(d[82]),"+f"(d[83]),"+f"(d[84]),"+f"(d[85]),"+f"(d[86]),"+f"(d[87]),"+f"(d[88]),"+f"(d[89]),"+f"(d[90]),"+f"(d[91]),"+f"(d[92]),"+f"(d[93]),"+f"(d[94]),"+f"(d[95])
    : "l"(da), "l"(db), "r"(sd));
}
__device__ __forceinline__ void wg_rs64(float (&d)[32], uint32_t a0, uint32_t a1, uint32_t a2, uint32_t a3, uint64_t db, int sd) {
  asm volatile("{\n.reg .pred p;\nsetp.ne.b32 p, %37, 0;\n"
    "wgmma.mma_async.sync.aligned.m64n64k16.f32.bf16.bf16 {%0,%1,%2,%3,%4,%5,%6,%7,%8,%9,%10,%11,%12,%13,%14,%15,%16,%17,%18,%19,%20,%21,%22,%23,%24,%25,%26,%27,%28,%29,%30,%31}, {%32,%33,%34,%35}, %36, p, 1, 1, 0;\n}\n"
    : "+f"(d[0]),"+f"(d[1]),"+f"(d[2]),"+f"(d[3]),"+f"(d[4]),"+f"(d[5]),"+f"(d[6]),"+f"(d[7]),"+f"(d[8]),"+f"(d[9]),"+f"(d[10]),"+f"(d[11]),"+f"(d[12]),"+f"(d[13]),"+f"(d[14]),"+f"(d[15]),"+f"(d[16]),"+f"(d[17]),"+f"(d[18]),"+f"(d[19]),"+f"(d[20]),"+f"(d[21]),"+f"(d[22]),"+f"(d[23]),"+f"(d[24]),"+f"(d[25]),"+f"(d[26]),"+f"(d[27]),"+f"(d[28]),"+f"(d[29]),"+f"(d[30]),"+f"(d[31])
    : "r"(a0), "r"(a1), "r"(a2), "r"(a3), "l"(db), "r"(sd));
}
__device__ __forceinline__ void wg_rs192t(float (&d)[96], uint32_t a0, uint32_t a1, uint32_t a2, uint32_t a3, uint64_t db, int sd) {
  asm volatile("{\n.reg .pred p;\nsetp.ne.b32 p, %101, 0;\n"
    "wgmma.mma_async.sync.aligned.m64n192k16.f32.bf16.bf16 {%0,%1,%2,%3,%4,%5,%6,%7,%8,%9,%10,%11,%12,%13,%14,%15,%16,%17,%18,%19,%20,%21,%22,%23,%24,%25,%26,%27,%28,%29,%30,%31,%32,%33,%34,%35,%36,%37,%38,%39,%40,%41,%42,%43,%44,%45,%46,%47,%48,%49,%50,%51,%52,%53,%54,%55,%56,%57,%58,%59,%60,%61,%62,%63,%64,%65,%66,%67,%68,%69,%70,%71,%72,%73,%74,%75,%76,%77,%78,%79,%80,%81,%82,%83,%84,%85,%86,%87,%88,%89,%90,%91,%92,%93,%94,%95}, {%96,%97,%98,%99}, %100, p, 1, 1, 1;\n}\n"
    : "+f"(d[0]),"+f"(d[1]),"+f"(d[2]),"+f"(d[3]),"+f"(d[4]),"+f"(d[5]),"+f"(d[6]),"+f"(d[7]),"+f"(d[8]),"+f"(d[9]),"+f"(d[10]),"+f"(d[11]),"+f"(d[12]),"+f"(d[13]),"+f"(d[14]),"+f"(d[15]),"+f"(d[16]),"+f"(d[17]),"+f"(d[18]),"+f"(d[19]),"+f"(d[20]),"+f"(d[21]),"+f"(d[22]),"+f"(d[23]),"+f"(d[24]),"+f"(d[25]),"+f"(d[26]),"+f"(d[27]),"+f"(d[28]),"+f"(d[29]),"+f"(d[30]),"+f"(d[31]),"+f"(d[32]),"+f"(d[33]),"+f"(d[34]),"+f"(d[35]),"+f"(d[36]),"+f"(d[37]),"+f"(d[38]),"+f"(d[39]),"+f"(d[40]),"+f"(d[41]),"+f"(d[42]),"+f"(d[43]),"+f"(d[44]),"+f"(d[45]),"+f"(d[46]),"+f"(d[47]),"+f"(d[48]),"+f"(d[49]),"+f"(d[50]),"+f"(d[51]),"+f"(d[52]),"+f"(d[53]),"+f"(d[54]),"+f"(d[55]),"+f"(d[56]),"+f"(d[57]),"+f"(d[58]),"+f"(d[59]),"+f"(d[60]),"+f"(d[61]),"+f"(d[62]),"+f"(d[63]),"+f"(d[64]),"+f"(d[65]),"+f"(d[66]),"+f"(d[67]),"+f"(d[68]),"+f"(d[69]),"+f"(d[70]),"+f"(d[71]),"+f"(d[72]),"+f"(d[73]),"+f"(d[74]),"+f"(d[75]),"+f"(d[76]),"+f"(d[77]),"+f"(d[78]),"+f"(d[79]),"+f"(d[80]),"+f"(d[81]),"+f"(d[82]),"+f"(d[83]),"+f"(d[84]),"+f"(d[85]),"+f"(d[86]),"+f"(d[87]),"+f"(d[88]),"+f"(d[89]),"+f"(d[90]),"+f"(d[91]),"+f"(d[92]),"+f"(d[93]),"+f"(d[94]),"+f"(d[95])
    : "r"(a0), "r"(a1), "r"(a2), "r"(a3), "l"(db), "r"(sd));
}
__device__ __forceinline__ void wg_ss160t(float (&d)[80], uint64_t da, uint64_t db, int sd) {
  asm volatile("{\n.reg .pred p;\nsetp.ne.b32 p, %82, 0;\n"
    "wgmma.mma_async.sync.aligned.m64n160k16.f32.bf16.bf16 {%0,%1,%2,%3,%4,%5,%6,%7,%8,%9,%10,%11,%12,%13,%14,%15,%16,%17,%18,%19,%20,%21,%22,%23,%24,%25,%26,%27,%28,%29,%30,%31,%32,%33,%34,%35,%36,%37,%38,%39,%40,%41,%42,%43,%44,%45,%46,%47,%48,%49,%50,%51,%52,%53,%54,%55,%56,%57,%58,%59,%60,%61,%62,%63,%64,%65,%66,%67,%68,%69,%70,%71,%72,%73,%74,%75,%76,%77,%78,%79}, %80, %81, p, 1, 1, 0, 1;\n}\n"
    : "+f"(d[0]),"+f"(d[1]),"+f"(d[2]),"+f"(d[3]),"+f"(d[4]),"+f"(d[5]),"+f"(d[6]),"+f"(d[7]),"+f"(d[8]),"+f"(d[9]),"+f"(d[10]),"+f"(d[11]),"+f"(d[12]),"+f"(d[13]),"+f"(d[14]),"+f"(d[15]),"+f"(d[16]),"+f"(d[17]),"+f"(d[18]),"+f"(d[19]),"+f"(d[20]),"+f"(d[21]),"+f"(d[22]),"+f"(d[23]),"+f"(d[24]),"+f"(d[25]),"+f"(d[26]),"+f"(d[27]),"+f"(d[28]),"+f"(d[29]),"+f"(d[30]),"+f"(d[31]),"+f"(d[32]),"+f"(d[33]),"+f"(d[34]),"+f"(d[35]),"+f"(d[36]),"+f"(d[37]),"+f"(d[38]),"+f"(d[39]),"+f"(d[40]),"+f"(d[41]),"+f"(d[42]),"+f"(d[43]),"+f"(d[44]),"+f"(d[45]),"+f"(d[46]),"+f"(d[47]),"+f"(d[48]),"+f"(d[49]),"+f"(d[50]),"+f"(d[51]),"+f"(d[52]),"+f"(d[53]),"+f"(d[54]),"+f"(d[55]),"+f"(d[56]),"+f"(d[57]),"+f"(d[58]),"+f"(d[59]),"+f"(d[60]),"+f"(d[61]),"+f"(d[62]),"+f"(d[63]),"+f"(d[64]),"+f"(d[65]),"+f"(d[66]),"+f"(d[67]),"+f"(d[68]),"+f"(d[69]),"+f"(d[70]),"+f"(d[71]),"+f"(d[72]),"+f"(d[73]),"+f"(d[74]),"+f"(d[75]),"+f"(d[76]),"+f"(d[77]),"+f"(d[78]),"+f"(d[79])
    : "l"(da), "l"(db), "r"(sd));
}
__device__ __forceinline__ void wg_ss80t(float (&d)[40], uint64_t da, uint64_t db, int sd) {
  asm volatile("{\n.reg .pred p;\nsetp.ne.b32 p, %42, 0;\n"
    "wgmma.mma_async.sync.aligned.m64n80k16.f32.bf16.bf16 {%0,%1,%2,%3,%4,%5,%6,%7,%8,%9,%10,%11,%12,%13,%14,%15,%16,%17,%18,%19,%20,%21,%22,%23,%24,%25,%26,%27,%28,%29,%30,%31,%32,%33,%34,%35,%36,%37,%38,%39}, %40, %41, p, 1, 1, 0, 1;\n}\n"
    : "+f"(d[0]),"+f"(d[1]),"+f"(d[2]),"+f"(d[3]),"+f"(d[4]),"+f"(d[5]),"+f"(d[6]),"+f"(d[7]),"+f"(d[8]),"+f"(d[9]),"+f"(d[10]),"+f"(d[11]),"+f"(d[12]),"+f"(d[13]),"+f"(d[14]),"+f"(d[15]),"+f"(d[16]),"+f"(d[17]),"+f"(d[18]),"+f"(d[19]),"+f"(d[20]),"+f"(d[21]),"+f"(d[22]),"+f"(d[23]),"+f"(d[24]),"+f"(d[25]),"+f"(d[26]),"+f"(d[27]),"+f"(d[28]),"+f"(d[29]),"+f"(d[30]),"+f"(d[31]),"+f"(d[32]),"+f"(d[33]),"+f"(d[34]),"+f"(d[35]),"+f"(d[36]),"+f"(d[37]),"+f"(d[38]),"+f"(d[39])
    : "l"(da), "l"(db), "r"(sd));
}

struct Maps { CUtensorMap x, xn, wq, k, v, wo, w3[2], xg, xe, out; };
struct Params {
  const __nv_bfloat16 *x, *wr, *wg, *wu, *wd, *k, *v;
  Scratch* s;
};

__device__ __forceinline__ void side_cta(const Params& p, int sc, unsigned epoch, float* sm) {
  const int tid = threadIdx.x, lane = tid & 31, warp = tid >> 5;
  int budget = WAIT_BUDGET;
  float* s_x = sm;
  float* s_red = sm + 1280;
  float* s_h = s_red + 6144;
  uint4* s_c = (uint4*)(s_h + 768);
  uint2* s_st = (uint2*)(s_c + 16);
  constexpr int DEPTH = 7, STEP = 4 * 6144;
  const uint32_t ring = smem_u32(s_st + 512) + tid * 16;
  const int cg = tid % 96, ks = tid / 96, cd = tid % 80, kd = tid / 80;
  const __nv_bfloat16* wp = (cg < 48 ? p.wg : p.wu) + (size_t)(ks * 160) * FF + sc * 384 + (cg % 48) * 8;
  int kf = 0, pitch = FF;
  uint32_t slot = ring;
  auto refill = [&]() {
    if (kf == 40) { wp = p.wd + (size_t)(sc * 384 + kd * 96) * DM + cd * 8; pitch = DM; }
    if (kf < (tid < 320 ? 64 : 40)) {
#pragma unroll
      for (int j = 0; j < 4; j++) asm volatile("cp.async.cg.shared.global.L2::cache_hint [%0], [%1], 16, %2;" ::"r"(slot + j * 6144), "l"(wp + j * pitch), "l"(POL_FIRST) : "memory");
    }
    asm volatile("cp.async.commit_group;" ::: "memory");
    wp += 4 * pitch; kf++;
    slot += STEP; if (slot == ring + DEPTH * STEP) slot = ring;
  };
  auto gemv = [&](int n, const float* x0, const float* x1, float* out) {
    float a[2][8] = {};
#pragma unroll 1
    for (int k = 0; k < n; k += 4) {
      refill();
      asm volatile("cp.async.wait_group %0;" ::"n"(DEPTH - 1) : "memory");
      const float4 f0 = *(const float4*)(x0 + k), f1 = *(const float4*)(x1 + k);
      const float y0[4] = {f0.x, f0.y, f0.z, f0.w}, y1[4] = {f1.x, f1.y, f1.z, f1.w};
#pragma unroll
      for (int j = 0; j < 4; j++) {
        const uint4 v = lds128(slot + j * 6144);
        const uint32_t u[4] = {v.x, v.y, v.z, v.w};
#pragma unroll
        for (int i = 0; i < 4; i++) {
          a[0][2 * i] += y0[j] * bf_lo(u[i]); a[0][2 * i + 1] += y0[j] * bf_hi(u[i]);
          a[1][2 * i] += y1[j] * bf_lo(u[i]); a[1][2 * i + 1] += y1[j] * bf_hi(u[i]);
        }
      }
    }
#pragma unroll
    for (int i = 0; i < 16; i++) out[(i >> 3) * 768 + (i & 7)] = a[i >> 3][i & 7];
  };
  auto load_row = [&](const __nv_bfloat16* r, uint32_t (&v)[10]) {
    const uint4 a = __ldg((const uint4*)r + lane), b = __ldg((const uint4*)r + 32 + lane);
    const uint2 c = __ldg((const uint2*)r + 128 + lane);
    v[0] = a.x; v[1] = a.y; v[2] = a.z; v[3] = a.w; v[4] = b.x; v[5] = b.y; v[6] = b.z; v[7] = b.w; v[8] = c.x; v[9] = c.y;
  };
  uint32_t wr[10], xb[3][10];
  load_row(p.wr, wr);
  auto stat2 = [&](int pair) {
    uint4 v;
    do v = ld_pkt((const uint4*)p.s->stat + pair); while ((((v.x ^ (epoch + 1)) | (v.z ^ (epoch + 1))) & 0xffff) && --budget >= 0);
    return make_uint4(__byte_perm(v.x, 0, 0x3232), v.y, __byte_perm(v.z, 0, 0x3232), v.w);
  };
  if (tid < 256) ((uint4*)s_st)[tid] = stat2(sc * 256 + tid);
  __syncthreads();
#pragma unroll
  for (int b = 0; b < 3; b++) load_row(p.x + (size_t)(sc * 512 + warp + 12 * b) * DM, xb[b]);
#pragma unroll 1
  for (int k = 0; k < DEPTH - 1; k++) refill();
  float v0 = -INFINITY, v1 = -INFINITY; int i0 = 0xfff, i1 = 0xfff;
  auto better = [](float a, int ia, float b, int ib) { return a > b || (a == b && ia < ib); };
  auto push = [&](float v, int i) {
    if (better(v, i, v0, i0)) { v1 = v0; i1 = i0; v0 = v; i0 = i; }
    else if (better(v, i, v1, i1)) { v1 = v; i1 = i; }
  };
  auto push2 = [&](uint4 c) { push(__uint_as_float(c.x), c.y & 0xfff); push(__uint_as_float(c.z), c.w & 0xfff); };
#pragma unroll 1
  for (int l3 = warp; l3 < 512; l3 += 36) {
#pragma unroll
    for (int b = 0; b < 3; b++) {
      const int lr = l3 + 12 * b;
      if (lr >= 512) break;
      const uint2 st = s_st[lr];
      uint32_t v[10];
#pragma unroll
      for (int i = 0; i < 10; i++) v[i] = hsub2(xb[b][i], st.x);
      if (lr + 36 < 512) load_row(p.x + (size_t)(sc * 512 + lr + 36) * DM, xb[b]);
      float r0 = 0.f, r1 = 0.f;
#pragma unroll
      for (int i = 0; i < 10; i++) {
        const uint32_t xn = pack_bf16(bf_lo(v[i]) * __uint_as_float(st.y), bf_hi(v[i]) * __uint_as_float(st.y));
        r0 = fmaf(bf_lo(xn), bf_lo(wr[i]), r0); r1 = fmaf(bf_hi(xn), bf_hi(wr[i]), r1);
      }
      r0 += r1;
#pragma unroll
      for (int o = 16; o > 0; o >>= 1) r0 += __shfl_xor_sync(~0u, r0, o);
      push(rbf(r0), sc * 512 + lr);
    }
  }
  if (lane == 0) s_c[warp] = make_uint4(__float_as_uint(v0), i0, __float_as_uint(v1), i1);
  __syncthreads();
#pragma unroll 1
  for (int w = 1; w < 12; w++) push2(s_c[(warp + w) % 12]);
  const uint32_t tag = (epoch + 1) << 12;
  if (tid == 0) st_pkt(p.s->cand + sc, __float_as_uint(v0), i0 | tag, __float_as_uint(v1), i1);
  {
    uint4 c;
    do c = ld_pkt(p.s->cand + (lane & 3)); while (((c.y ^ tag) >> 12) && --budget >= 0);
#pragma unroll 1
    for (int w = 1; w < 4; w++) { const int o = (sc + w) & 3; push2(make_uint4(__shfl_sync(~0u, c.x, o), __shfl_sync(~0u, c.y, o), __shfl_sync(~0u, c.z, o), __shfl_sync(~0u, c.w, o))); }
  }
  if (i0 >= SQ) i0 = 0;
  if (i1 >= SQ) i1 = (i0 == 0) ? 1 : 0;
  if (tid < 320) {
    const int row = tid < 160 ? i0 : i1;
    const uint2 u = __ldg((const uint2*)(p.x + (size_t)row * DM) + tid % 160);
    const uint4 st = stat2(row >> 1);
    const uint32_t mean2 = row & 1 ? st.z : st.x, d0 = hsub2(u.x, mean2), d1 = hsub2(u.y, mean2);
    const float inv = __uint_as_float(row & 1 ? st.w : st.y);
    ((float4*)s_x)[tid] = make_float4(rbf(bf_lo(d0) * inv), rbf(bf_hi(d0) * inv), rbf(bf_lo(d1) * inv), rbf(bf_hi(d1) * inv));
  }
  __syncthreads();
  gemv(160, s_x + ks * 160, s_x + DM + ks * 160, s_red + ks * 1536 + cg * 8);
  __syncthreads();
#pragma unroll
  for (int t = 0; t < 2; t++) {
    float g = 0.f, u = 0.f;
#pragma unroll
    for (int k = 0; k < 4; k++) { g += s_red[(k * 2 + t) * 768 + tid]; u += s_red[(k * 2 + t) * 768 + 384 + tid]; }
    s_h[t * 384 + tid] = rbf(rbf(silu_f(rbf(g))) * rbf(u));
  }
  __syncthreads();
  if (tid < 320) gemv(96, s_h + kd * 96, s_h + 384 + kd * 96, s_red + kd * 1536 + cd * 8);
  __syncthreads();
  const int o4 = tid + (tid < 160 ? 0 : 32);
  if (tid < 320) {
    const float4 *r = (const float4*)s_red + o4, a = r[0], b = r[384], c = r[768], d = r[1152];
    ((float4*)p.s->ffn)[sc * 320 + tid] = make_float4(a.x + b.x + c.x + d.x, a.y + b.y + c.y + d.y, a.z + b.z + c.z + d.z, a.w + b.w + c.w + d.w);
  }
  __syncthreads();
  if (tid == 0) { __threadfence(); s_c[0].x = (atomicAdd(&p.s->flag[FL_SIDE], 1u) & 3u) == 3u; __threadfence(); }
  __syncthreads();
  if (s_c[0].x) {
    if (tid < 320) {
      const float4 *r = (const float4*)p.s->ffn + tid, a = __ldcg(r), b = __ldcg(r + 320), c = __ldcg(r + 640), d = __ldcg(r + 960), x = ((float4*)s_x)[tid];
      const float rs = rbf(sigmoid_f(tid < 160 ? v0 : v1));
      auto gate = [&](float xn, float y) { return silu_f(rbf(xn + rbf(rbf(y) * rs))); };
      if (tid == 0) { p.s->sel[0] = i0; p.s->sel[1] = i1; }
      ((uint2*)p.s->gsel)[tid] =
          make_uint2(pack_bf16(gate(x.x, a.x + b.x + c.x + d.x), gate(x.y, a.y + b.y + c.y + d.y)), pack_bf16(gate(x.z, a.z + b.z + c.z + d.z), gate(x.w, a.w + b.w + c.w + d.w)));
    }
    __syncthreads();
    if (tid == 0) red_release(&p.s->flag[FL_FFN]);
  }
}

constexpr float SM_C = 0.07216878364870322f * 1.4426950408889634f;

constexpr int LD = 0, LS = 3;
__device__ __forceinline__ void ln_piece(const Params& p, uint32_t (&r)[48], int k, int row, int l16) {
  auto f = [&](int i) { return __uint_as_float(r[i]); };
  if (k == LD) {
#pragma unroll
    for (int i = 0; i < 5; i++) {
      const uint4 v = ldg_nc((const uint4*)(p.x + (size_t)row * DM) + i * 16 + l16);
      r[4 * i] = v.x; r[4 * i + 1] = v.y; r[4 * i + 2] = v.z; r[4 * i + 3] = v.w;
    }
    asm volatile("ld.relaxed.gpu.global.v2.u32 {%0,%1}, [%2];" : "=r"(r[20]), "=r"(r[21]) : "l"(&p.s->done));
  } else if (k == LS || k == LS + 1) {
    if (k == LS) { r[22] = __shfl_sync(~0u, r[0], 0, 16) << 16; r[23] = r[24] = 0; }
    float s0 = f(23), s1 = 0.f, q0 = f(24), q1 = 0.f;
#pragma unroll
    for (int i = 10 * (k - LS); i < 10 * (k - LS) + 10; i++) {
      const float a = bf_lo(r[i]) - f(22), b = bf_hi(r[i]) - f(22);
      s0 += a; s1 += b; q0 = fmaf(a, a, q0); q1 = fmaf(b, b, q1);
    }
    r[23] = __float_as_uint(s0 + s1); r[24] = __float_as_uint(q0 + q1);
  } else if (k == LS + 2) {
    float s0 = f(23), q0 = f(24);
#pragma unroll
    for (int o = 8; o > 0; o >>= 1) { s0 += __shfl_xor_sync(~0u, s0, o); q0 += __shfl_xor_sync(~0u, q0, o); }
    s0 *= 1.f / DM;
    const float mean = f(22) + s0, var = rbf(fmaxf(fmaf(q0, 1.f / DM, -s0 * s0), 0.f));
    float sd; asm("sqrt.approx.ftz.f32 %0, %1;" : "=f"(sd) : "f"(rbf(var + 1e-5f)));
    const float inv = rcp(rbf(sd));
    r[22] = pack_bf16(mean, mean); r[23] = __float_as_uint(inv * SM_C);
    const uint32_t tag = __funnelshift_r(r[20], r[21], 7) + 1;
    if (l16 == 0) st_pkt8(&p.s->stat[row], __byte_perm(tag, r[22], 0x7610), __float_as_uint(inv));
  } else if (k > LS + 2 && k <= LS + 5) {
#pragma unroll
    for (int j = 2 * (k - LS - 3); j < 2 * (k - LS - 3) + 2 && j < 5; j++) {
#pragma unroll
      for (int i = 4 * j; i < 4 * j + 4; i++) { const uint32_t d = hsub2(r[i], r[22]); r[i] = pack_bf16(bf_lo(d) * f(23), bf_hi(d) * f(23)); }
      *((uint4*)(p.s->xn + (size_t)row * DM) + j * 16 + l16) = make_uint4(r[4 * j], r[4 * j + 1], r[4 * j + 2], r[4 * j + 3]);
    }
  }
}

constexpr float SM_HI = 0x1p64f, SM_LO = 0x1p-64f;
__device__ __forceinline__ void exp_block(float (&s)[32], float& l0, float& l1, int from = 0, int to = 32) {
#pragma unroll
  for (int i = from; i < to; i++) { s[i] = ex2(s[i]); if (i & 2) l1 += s[i]; else l0 += s[i]; }
}
__device__ __forceinline__ float quad_sum(float v) { v += __shfl_xor_sync(~0u, v, 1); return v + __shfl_xor_sync(~0u, v, 2); }
__device__ __forceinline__ float quad_max(float v) { v = fmaxf(v, __shfl_xor_sync(~0u, v, 1)); return fmaxf(v, __shfl_xor_sync(~0u, v, 2)); }
__device__ __noinline__ void safe_head(const uint32_t* kp, const uint32_t* vp, uint4* io) {
  uint32_t fq[48];
#pragma unroll
  for (int i = 0; i < 12; i++) { const uint4 v = io[(i >> 1) * 512 + (i & 1) * 32]; fq[4 * i] = v.x; fq[4 * i + 1] = v.y; fq[4 * i + 2] = v.z; fq[4 * i + 3] = v.w; }
  float m0 = -INFINITY, m1 = -INFINITY;
#pragma unroll 1
  for (int pass = 0; pass < 3; pass++) {
    float o[48] = {}, l0 = 0.f, l1 = 0.f;
#pragma unroll 1
    for (int n = 0; n < 64; n++) {
      const uint32_t *kr = kp + n * (8 * DH / 2), *vr = vp + n * (8 * DH / 2) + (pass - 1) * 48;
      float d[4] = {};
#pragma unroll
      for (int t = 0; t < 12; t++)
        asm volatile("mma.sync.aligned.m16n8k16.row.col.f32.bf16.bf16.f32 {%0,%1,%2,%3}, {%4,%5,%6,%7}, {%8,%9}, {%0,%1,%2,%3};"
                     : "+f"(d[0]), "+f"(d[1]), "+f"(d[2]), "+f"(d[3])
                     : "r"(fq[4 * t]), "r"(fq[4 * t + 1]), "r"(fq[4 * t + 2]), "r"(fq[4 * t + 3]), "r"(__ldg(kr + 8 * t)), "r"(__ldg(kr + 8 * t + 4)));
      if (pass == 0) { m0 = fmaxf(m0, fmaxf(d[0], d[1])); m1 = fmaxf(m1, fmaxf(d[2], d[3])); continue; }
      d[0] = ex2(d[0] - m0); d[1] = ex2(d[1] - m0); d[2] = ex2(d[2] - m1); d[3] = ex2(d[3] - m1);
      l0 += d[0] + d[1]; l1 += d[2] + d[3];
      const uint32_t p0 = pack_bf16(d[0], d[1]), p1 = pack_bf16(d[2], d[3]);
#pragma unroll
      for (int c = 0; c < 12; c++)
        asm volatile("{\n.reg .b32 t;\nmovmatrix.sync.aligned.m8n8.trans.b16 t, %6;\n"
                     "mma.sync.aligned.m16n8k8.row.col.f32.bf16.bf16.f32 {%0,%1,%2,%3}, {%4,%5}, {t}, {%0,%1,%2,%3};\n}\n"
                     : "+f"(o[4 * c]), "+f"(o[4 * c + 1]), "+f"(o[4 * c + 2]), "+f"(o[4 * c + 3]) : "r"(p0), "r"(p1), "r"(__ldg(vr + 4 * c)));
    }
    if (pass == 0) { m0 = quad_max(m0); m1 = quad_max(m1); continue; }
    l0 = rcp(quad_sum(l0)); l1 = rcp(quad_sum(l1));
#pragma unroll
    for (int i = 0; i < 6; i++) {
      const float* v = o + 16 * (i >> 1) + 2 * (i & 1);
      const float r = i & 1 ? l1 : l0;
      io[(3 * (pass - 1) + (i >> 1)) * 512 + (i & 1) * 32] =
          make_uint4(pack_bf16(v[0] * r, v[1] * r), pack_bf16(v[4] * r, v[5] * r), pack_bf16(v[8] * r, v[9] * r), pack_bf16(v[12] * r, v[13] * r));
    }
  }
}

__device__ __forceinline__ constexpr int end_stage(int n) { return n < 4 ? n : n < 6 ? n - 4 : n == 6 ? 4 : n % 5; }
__device__ __forceinline__ constexpr int sent(int n) { return n < 8 ? 0 : n < 9 ? 3 : n < 11 ? 5 : n < 13 ? 8 : n < 16 ? 10 : n < 17 ? 14 : 15; }
#define N16 16
template <int N> struct IntC { static constexpr int value = N; };
template <int N, int I = 0, class F> __device__ __forceinline__ void static_for(F&& f) { if constexpr (I < N) { f(IntC<I>{}); static_for<N, I + 1>(f); } }

extern __shared__ __align__(1024) uint8_t smem_raw[];
constexpr uint32_t EA = 160, EB = 184;
#define SMEM_LAYOUT                                                                                                          \
  [[maybe_unused]] const uint32_t sb = smem_u32(smem_raw), bar_a = sb + OFF_M, bar_b = bar_a + 40, bar_x = bar_a + 88,      \
      bar_u = bar_a + 96, bar_e = bar_a + 104, bar_o = bar_a + 200, bar_w = bar_a + 208, bar_z = bar_a + 288,                \
      bar_s = bar_a + 296, bar_d = bar_a + 304, s_stat = bar_a + 512, s_sel = s_stat + 1024;

__device__ __forceinline__ int cluster_role() {
  uint32_t t, n;
  asm("mov.u32 %0, %%smid;" : "=r"(t)); asm("mov.u32 %0, %%nsmid;" : "=r"(n));
  t >>= 1;
  return n != 132 ? blockIdx.x >> 1 : t < 32 ? t : t < 60 ? t + 1 + (((t - 32) * 37) >> 8) : t < 62 ? t + 4 : (t - 58) * 8;
}

__device__ __forceinline__ int k_block(int t, int hg) {
  const int i = (t * 11) >> 5;
  return ((i < 6 ? (hg & 6) + (i & 1) : hg ^ (i & 1)) * 4 + (i >> 1)) * 6 + (t == 3 * i ? 4 : 2 * (t - 3 * i) - 2);
}

__device__ __noinline__ int errands(Scratch* s, const Maps& m, int qt, int hg, int warp, uint32_t tag, int budget) {
  SMEM_LAYOUT
  const int lane = threadIdx.x & 31, kq = hg >> 1, nh = hg & 1;
  if (warp == 1) {
#pragma unroll 1
    for (int u = 0; u < 5; u++) {
      mbar_wait(bar_o, u & 1);
      if (lane == 0) red_release(&s->flag[u ? FL_O + (qt * 8 + hg) * 8 : FL_XN + qt * 32]);
      __syncwarp();
    }
  } else if (warp == 2) {
    mbar_wait(bar_x, 0, budget);
    while ((int)(ld_acquire(&s->flag[FL_FFN]) - tag) < 0 && --budget >= 0) {}
    if (lane < 21) {
      const uint4 v = __ldcg(lane ? (const uint4*)(s->gsel + (lane > 10 ? DM - 80 : 0) + nh * 320 + kq * 80) + lane - 1 : (const uint4*)s->sel);
      asm volatile("st.shared.v4.u32 [%0], {%1,%2,%3,%4};" ::"r"(s_sel + 16 * lane), "r"(v.x), "r"(v.y), "r"(v.z), "r"(v.w) : "memory");
    }
    __syncwarp();
    if (lane == 0) { mbar_arrive(bar_u); asm volatile("red.relaxed.gpu.global.add.u64 [%0], 1;" ::"l"(&s->done) : "memory"); }
    while ((int)(ld_acquire(&s->flag[FL_RD + (qt * 8 + (hg ^ 1)) * 8]) - tag) < 0 && --budget >= 0) {}
    if (lane < 3) mbar_arrive(bar_z);
  } else {
    wait_flag(&s->flag[FL_XN + qt * 32], tag * 8);
    fence_proxy_async();
    mbar_wait(bar_a + EA + 32, 1);
    uint32_t a8 = 0, pha = 1;
    const int kb = (qt * 192 + k_block(lane, hg)) * 512;
#pragma unroll 1
    for (int n = 0; n < 54; n++) {
      const int t = n - 30, ko = __shfl_sync(~0u, kb, t);
      if (t == 0 || t == 18) {
        wait_flag(&s->flag[FL_O + (qt * 8 + (t ? 2 * kq + (lane & 1) : lane & 7)) * 8], tag * 4 - (t ? 0 : 1));
        fence_proxy_async();
      }
      mbar_wait(bar_a + EA + a8, pha);
      const uint32_t fb = bar_a + a8, dst = sb + a8 * (TA >> 3);
      if (elect()) {
        if (t >= 0) {
          mbar_expect_tx(fb, TA);
          bulk_load(dst, s->o + ko, TA, fb);
          if (t == 8) {
            mbar_expect_tx(bar_x, 6 * 3840);
#pragma unroll 1
            for (int e = 0; e < 6; e++) tma2d(sb + OFF_B + TW + e * TB, &m.xg, nh * 320 + kq * 80, qt * 128 + e * 24, bar_x);
            asm volatile("prefetch.tensormap [%0];\nprefetch.tensormap [%1];\nprefetch.tensormap [%2];\nprefetch.tensormap [%3];"
                         ::"l"(m.w3), "l"(m.w3 + 1), "l"(&m.xe), "l"(&m.out) : "memory");
          }
          if (t == 22) asm volatile("red.relaxed.gpu.global.add.u32 [%0], 1;" ::"l"(&s->flag[FL_RD + (qt * 8 + hg) * 8]) : "memory");
        } else if (n >= 10 && pha) mbar_arrive(fb);
        else { mbar_expect_tx(fb, TA); tma2d(dst, &m.xn, 8 * a8 + (pha || (n >= 15 && n < 20) ? 0 : 320), qt * 128, fb); }
      }
      a8 += 8; if (a8 == 40) { a8 = 0; pha ^= 1; }
    }
    if (lane < 3) mbar_arrive(bar_z);
  }
  return budget;
}

__global__ void __launch_bounds__(384, 1) __cluster_dims__(2, 1, 1)
fused_kernel(const Params p, const __grid_constant__ Maps m) {
  SMEM_LAYOUT
  const int wi = __shfl_sync(~0u, threadIdx.x >> 5, 0), wg = wi >> 2;
  const int lane = threadIdx.x & 31;
  const int cl = cluster_role();
  const int rank = blockIdx.x & 1;

  if (cl >= 64) {
    const unsigned epoch = (unsigned)(__ldcg(&p.s->done) >> 7);
    side_cta(p, 2 * cl + rank - 128, epoch, (float*)smem_raw);
    return;
  }
  const int qt = (cl & 7) * 2 + rank, hg = cl >> 3;
  const int kq = hg >> 1, nh = hg & 1;

  const int s0 = qt < 8 ? 0 : 5, kg0 = 10 * ((qt >> 1) & 3);
  if (elect()) {
    const int c = (int)(0x5ff7700000ull >> (4 * wi) & 15) + 1;
    for (int i = 0; i < 4; i++) mbar_init(bar_a + 32 * wi + 8 * i, c);
    asm volatile("fence.mbarrier_init.release.cluster;" ::: "memory");
  }
  __syncwarp();
  cluster_arrive();
  if (wi < 2 && elect()) {
    if (wi) { asm volatile("prefetch.tensormap [%0];" ::"l"(&m.wq) : "memory"); mbar_expect_tx(bar_b, TB); mbar_expect_tx(bar_b + 8, TB); }
    else for (int i = 0; i < 2; i++) { mbar_expect_tx(bar_a + 8 * i, TA); tma2d(sb + i * TA, &m.x, 64 * (s0 + i), qt * 128, bar_a + 8 * i); }
  }
  __syncwarp();
  cluster_wait();
  if (wi == 1 && elect())
    for (int i = 0; i < 2; i++) tma4d_mc(sb + OFF_B + i * TB + rank * (TB / 2), &m.wq, 12 * hg, 8 * (s0 + i) + 4 * rank, bar_b + 8 * i);
  if (wg > 0) {
    const int w = wg - 1;
    const int cw = wi - 4;
    asm volatile("setmaxnreg.inc.sync.aligned.u32 232;");
    uint32_t fr[48];
    reg_fence(fr);
    auto ln_row = [&]() { int v = qt * 128 + hg * 16 + cw * 2 + (lane >> 4); asm volatile("" : "+r"(v)); return v; };
    uint32_t rel_addr;
    asm volatile("mapa.shared::cluster.u32 %0, %1, %2;" : "=r"(rel_addr) : "r"(bar_b + EB), "r"(lane & 1));
    auto rel_a = [&](uint32_t o8) { if (lane == 0) mbar_arrive(bar_a + EA + o8); };
    auto rel_b = [&](uint32_t o8) { if (lane < 2) mbar_arrive_cluster(rel_addr + o8); };
    uint32_t b8 = 0, phb = 0;
    auto next_pair = [&]() { b8 += 16; if (b8 == 48) { b8 = 0; phb ^= 1; } };
    const int g = lane >> 2, q = lane & 3;
    constexpr uint64_t HI_A = desc_hi(16, 1024, 1);
    constexpr uint64_t HI_W = desc_hi(1024, 3072, 1);
    constexpr uint64_t HI_O = desc_hi(2048, 512, 2);
    if (w == 1) asm volatile("bar.arrive 1, 256;" ::: "memory");

    uint32_t zero; asm volatile("mov.u32 %0, %%tid.y;" : "=r"(zero));
    float acc[96];
    uint4* optr = p.s->o + (size_t)(qt * 192 + hg * 24) * 512 + (cw * 16 + g) * 4 + (q ^ ((g >> 1) & 3));
    uint32_t rl[4];
    auto store_o = [&](int pp) {
#pragma unroll
      for (int i = (12 * pp + 8) / 9; i < (12 * (pp + 1) + 8) / 9; i++) {
#pragma unroll
        for (int k = 4 * i; k < 4 * i + 4; k++)
          asm volatile("{\n.reg .b32 t;\nmul.rn.bf16x2 t, %0, %2;\nfma.rn.bf16x2 %0, %0, %1, t;\n}\n" : "+r"(fr[k]) : "r"(rl[i & 1]), "r"(rl[2 + (i & 1)]));
        fr[4 * i] &= ~1u;
        optr[(i >> 1) * 512 + (i & 1) * 32] = make_uint4(fr[4 * i], fr[4 * i + 1], fr[4 * i + 2], fr[4 * i + 3]);
      }
      if (pp == 8) optr += 6 * 512;
    };
    auto fresh = [&]() { uint32_t v = sb; asm volatile("" : "+r"(v)); return v; };
    reg_fence(rl);

#pragma unroll 1
    for (int u = 0; u < 4; u++) {
      const uint32_t sq = fresh();
      const uint64_t dA = mkdesc(sq + w * 8192, HI_A), dB0 = mkdesc(sq + OFF_B, HI_W);
      uint32_t pb8 = 0;
#pragma unroll
      for (int s = 0; s < 10; s++) {
        const uint32_t o8 = b8 + 8 * (s & 1);
        const uint64_t dW = dB0 + o8 * (TB >> 7);
        mbar_wait(bar_a + 8 * (s % 5), s / 5);
        mbar_wait(bar_b + o8, phb);
        if (s == 9 || (s >= LS && u == 0)) asm volatile("bar.sync %0, 256;" ::"r"(1 + w) : "memory");
        WG_FENCE();
#pragma unroll
        for (int kk = 0; kk < 4; kk++) wg_ss192t(acc, dA + ((s % 5) * (TA >> 4) + kk * 2), dW + kk * 384, kk != 0 || s != 0);
        WG_COMMIT();
        if (s >= LS && (s == 9) == (u > 0)) asm volatile("bar.arrive %0, 256;" ::"r"(2 - w) : "memory");
        if (s > 0) { WG_WAIT(1); rel_a(8 * ((s - 1) % 5)); rel_b(pb8); }
        if (s < 9) { if (u > 0) store_o(s); else ln_piece(p, fr, s, ln_row(), lane & 15); }
        if (s == 8) { __syncwarp(); if (lane == 0) mbar_arrive(bar_o); }
        pb8 = o8;
        if (s & 1) next_pair();
      }
      if (u == 0) {
        mbar_wait(bar_s, 0);
        const uint2 s0 = lds64(s_stat + (cw * 16 + g) * 8), s1 = lds64(s_stat + 64 + (cw * 16 + g) * 8);
        const uint32_t msk = q == 0 ? 0xffffffffu : q == 1 ? 0xffffu : 0u;
        const float c0 = SM_C * __uint_as_float(s0.y), c1 = SM_C * __uint_as_float(s1.y);
        uint32_t am[4] = {(s0.x ^ 0x80008000u) & msk, (s1.x ^ 0x80008000u) & msk, 0, 0};
        reg_fence(am);
        WG_FENCE();
        wg_rs192t(acc, am[0], am[1], am[2], am[3], mkdesc(sb, desc_hi(1024, 0, 1)), 1);
        WG_COMMIT();
        asm volatile("bar.arrive %0, 256;" ::"r"(2 - w) : "memory");
        WG_WAIT(0);
        reg_fence(acc);
#pragma unroll
        for (int i = 0; i < 24; i++) { acc[4 * i] *= c0; acc[4 * i + 1] *= c0; acc[4 * i + 2] *= c1; acc[4 * i + 3] *= c1; }
      } else { WG_WAIT(0); reg_fence(acc); }
      rel_b(pb8);
      rel_a(32);
#pragma unroll
      for (int i = 0; i < 48; i++) fr[i] = pack_bf16(acc[2 * i], acc[2 * i + 1]);
      reg_fence(fr);
      float sc[32], l0 = 0.f, l1 = 0.f;
      uint32_t pf[16], k8;
      auto pack_p = [&](const float (&s_)[32], int from = 0, int to = 16) {
#pragma unroll
        for (int i = from; i < to; i++) pf[i] = pack_bf16(s_[2 * i], s_[2 * i + 1]);
      };
      auto scores = [&](int j, int pass = 11) {
        k8 = b8 + 8;
        mbar_wait(bar_b + k8, phb);
        next_pair();
        mbar_wait(bar_b + b8, phb);
        const uint64_t dk = mkdesc(sb + OFF_B, HI_W) + k8 * (TB >> 7);
        asm volatile("bar.sync %0, 256;" ::"r"(1 + w) : "memory");
        WG_FENCE();
#pragma unroll
        for (int t = 0; t < 12; t++) {
          wg_rs64(sc, fr[4 * t], fr[4 * t + 1], fr[4 * t + 2], fr[4 * t + 3], dk + (t >> 2) * 64 + (t & 3) * 2, t != 0);
          if (t == 11) WG_COMMIT();
          if (t == pass) asm volatile("bar.arrive %0, 256;" ::"r"(2 - w) : "memory");
        }
      };
      auto pv = [&](int add) {
        const uint64_t dv = mkdesc(sb + OFF_B, HI_W) + b8 * (TB >> 7);
#pragma unroll
        for (int kk = 0; kk < 4; kk++) wg_rs192t(acc, pf[4 * kk], pf[4 * kk + 1], pf[4 * kk + 2], pf[4 * kk + 3], dv + kk * 384, kk != 0 || add);
        WG_COMMIT();
      };
      auto finish = [&]() {
        WG_WAIT(1);
        reg_fence(sc);
        exp_block(sc, l0, l1);
        rel_b(k8 + (__float_as_uint(l0) & __float_as_uint(l1) & zero));
        WG_WAIT(0);
        reg_fence(acc); reg_fence(pf);
        rel_b(b8);
        pack_p(sc);
      };
      {
        mbar_wait(bar_b + b8, phb);
        const uint64_t dk = mkdesc(sb + OFF_B, HI_W) + b8 * (TB >> 7);
        asm volatile("bar.sync %0, 256;" ::"r"(1 + w) : "memory");
#pragma unroll
        for (int t = 0; t < 12; t++) {
          if (t == 0) WG_FENCE();
          wg_rs64(sc, fr[4 * t], fr[4 * t + 1], fr[4 * t + 2], fr[4 * t + 3], dk + (t >> 2) * 64 + (t & 3) * 2, t != 0);
          if (t == 7) asm volatile("bar.arrive %0, 256;" ::"r"(2 - w) : "memory");
        }
        WG_COMMIT();
        WG_WAIT(0);
        reg_fence(sc);
        constexpr int NE = 8;
        float s0[32];
#pragma unroll
        for (int i = 0; i < 32; i++) s0[i] = i < NE ? sc[i] : __uint_as_float(__float_as_uint(sc[i]) ^ zero);
        exp_block(s0, l0, l1, 0, NE);
        pack_p(s0, 0, NE / 2);
#pragma unroll
        for (int i = NE; i < 32; i++) asm volatile("" : "+f"(s0[i])::"memory");
#pragma unroll
        for (int i = 0; i < NE / 2; i++) asm volatile("" : "+r"(pf[i])::"memory");
        rel_b(b8);
        scores(1, 8);
        const uint32_t z = lds32(s_stat) & zero;
#pragma unroll
        for (int i = NE; i < 32; i++) {
          asm("{\n.reg .pred p;\nsetp.eq.u32 p, %1, 0;\n@p ex2.approx.ftz.f32 %0, %0;\n}\n" : "+f"(s0[i]) : "r"(z));
          if (i & 2) l1 += s0[i]; else l0 += s0[i];
        }
        pack_p(s0, NE / 2, 16);
        reg_fence(pf);
        WG_FENCE();
        pv(0);
        finish();
      }
#pragma unroll 1
      for (int j = 2; j < 8; j++) { scores(j); pv(1); finish(); }
      const uint32_t v8 = b8 + 8;
      mbar_wait(bar_b + v8, phb);
      next_pair();
      {
        const uint64_t dv = mkdesc(sb + OFF_B, HI_W) + v8 * (TB >> 7);
        asm volatile("bar.sync %0, 256;" ::"r"(1 + w) : "memory");
        WG_FENCE();
#pragma unroll
        for (int kk = 0; kk < 4; kk++) {
          wg_rs192t(acc, pf[4 * kk], pf[4 * kk + 1], pf[4 * kk + 2], pf[4 * kk + 3], dv + kk * 384, 1);
          if (kk == 1 && (u < 3 || w == 0)) asm volatile("bar.arrive %0, 256;" ::"r"(2 - w) : "memory");
        }
        WG_COMMIT();
      }
      l0 = quad_sum(l0); l1 = quad_sum(l1);
      const bool unsafe = __any_sync(~0u, !(l0 >= SM_LO && l1 >= SM_LO && l0 + l1 <= SM_HI));
      l0 = rcp(l0); l1 = rcp(l1);
      rl[0] = pack_bf16(l0, l0); rl[1] = pack_bf16(l1, l1);
      l0 -= bf_lo(rl[0]); l1 -= bf_lo(rl[1]);
      rl[2] = pack_bf16(l0, l0); rl[3] = pack_bf16(l1, l1);
      WG_WAIT(0);
      reg_fence(acc);
      rel_b(v8);
      if (__builtin_expect(unsafe, 0)) {
        int o = hg * 4 + u; asm volatile("" : "+r"(o));
        o = (o * SKC + (SKC - WIN) + g) * (DH / 2) + q;
#pragma unroll
        for (int i = 0; i < 12; i++) optr[(i >> 1) * 512 + (i & 1) * 32] = make_uint4(fr[4 * i], fr[4 * i + 1], fr[4 * i + 2], fr[4 * i + 3]);
        safe_head((const uint32_t*)p.k + o, (const uint32_t*)p.v + o, optr);
#pragma unroll
        for (int i = 0; i < 12; i++) { const uint4 v = optr[(i >> 1) * 512 + (i & 1) * 32]; fr[4 * i] = v.x; fr[4 * i + 1] = v.y; fr[4 * i + 2] = v.z; fr[4 * i + 3] = v.w; }
        rl[0] = rl[1] = 0x3f803f80u; rl[2] = rl[3] = 0;
      } else {
#pragma unroll
        for (int i = 0; i < 24; i++) {
          fr[8 * (i >> 2) + (i & 3)] = pack_bf16(acc[4 * i], acc[4 * i + 1]);
          fr[8 * (i >> 2) + 4 + (i & 3)] = pack_bf16(acc[4 * i + 2], acc[4 * i + 3]);
        }
      }
    }

    float aF[80], aS[80];
    uint32_t pha = 0, a8 = 0, pa8 = 0, pb8 = 0;
#pragma unroll 1
    for (int s = 0; s < 19; s++) {
      const uint64_t d0 = mkdesc(sb, HI_O), dO = d0 + (a8 * (TA >> 7) + w * 256), dB = d0 + ((OFF_B >> 4) + b8 * (TB >> 7));
      mbar_wait(bar_a + a8, pha);
      mbar_wait(bar_b + b8, phb);
      WG_FENCE();
#pragma unroll
      for (int kk = 0; kk < 4; kk++) wg_ss160t(aF, dO + ((kk >> 1) * 512 + (kk & 1) * 2), dB + ((kk >> 1) * 640 + (kk & 1) * 64), kk != 0 || s != 0);
      WG_COMMIT();
      mbar_wait(bar_b + b8 + 8, phb);
      WG_WAIT(1);
      if (s > 0) { rel_a(pa8); rel_b(pb8 + 8); }
      WG_FENCE();
#pragma unroll
      for (int kk = 0; kk < 4; kk++) wg_ss160t(aS, dO + ((kk >> 1) * 512 + (kk & 1) * 2), dB + ((TB >> 4) + (kk >> 1) * 640 + (kk & 1) * 64), kk != 0 || s != 0);
      WG_COMMIT();
      if (s < 9) {
#pragma unroll
        for (int pp = 0; pp < 9; pp++) if (s == pp) store_o(pp);
        if (s == 8) { __syncwarp(); if (lane == 0) mbar_arrive(bar_o); }
      } else if (s < 15) {
        const int b = 2 * cw + ((lane >> 3) & 1);
        uint32_t ga = sb + OFF_B + TW + ((b * 11) >> 5) * (TB - 3840) + b * 1280 + (lane & 7) * 160 + (lane >> 4) * 16;
        if (s < 14) {
          mbar_wait(bar_x, 0);
          ga += 32 * (s - 9);
          ldsm4(ga, fr);
#pragma unroll
          for (int i = 0; i < 4; i++) {
            const uint2 st = lds64(s_stat + (cw * 16 + g + 8 * (i & 1)) * 8);
            const uint32_t d = hsub2(fr[i], st.x), xn = pack_bf16(bf_lo(d) * __uint_as_float(st.y), bf_hi(d) * __uint_as_float(st.y));
            fr[i] = pack_bf16(silu_f(bf_lo(xn)), silu_f(bf_hi(xn)));
          }
          stsm4(ga, fr);
        } else {
          mbar_wait(bar_u, 0);
          const uint2 sel = lds64(s_sel);
          const uint32_t row = qt * 128 + cw * 16 + (lane & 15);
          if (row == sel.x || row == sel.y) ga = s_sel + 16 + (row == sel.y ? 160 : 0) + (lane >> 4) * 16;
#pragma unroll
          for (int k = 0; k < 5; k++) ldsm4(ga + 32 * k, fr + 4 * k);
        }
      }
      WG_WAIT(1);
      rel_b(b8);
      pa8 = a8; a8 += 8; if (a8 == 40) { a8 = 0; pha ^= 1; }
      pb8 = b8; next_pair();
    }
    const int t128 = threadIdx.x & 127;
    uint4* const xbase = p.s->o + (size_t)(qt * 192 + nh * 24 + 10) * 512 + w * 640 + t128;
    uint4* const dst = xbase + kq * (48 * 512);
    float q1[40], q2[40], oth[40], own[40];
    auto take = [&](float (&x)[40], const float* a) {
#pragma unroll
      for (int k = 0; k < 40; k++) x[k] = __uint_as_float(__float_as_uint(a[k]) ^ zero);
      reg_fence(x);
    };
    reg_fence(aF);
    take(q1, aF);
    auto fa = [&](int i) { return mbar_try(bar_a + 8 * ((4 + i) % 5), i == 0); };
    auto fb = [&](int e) { return mbar_try(bar_b + 8 * (e % 6), (e / 6) & 1); };
    auto send = [&](int m) {
      const float* v = (m < 5 ? q1 : m < 10 ? q2 : oth) + 8 * (m % 5);
      st_pkt(dst + (m / 5) * 1280 + (m % 5) * 128, pack_bf16(v[0], v[1]) | 1, pack_bf16(v[2], v[3]), pack_bf16(v[4], v[5]), pack_bf16(v[6], v[7]));
    };
    static_for<20>([&](auto n_) {
      constexpr int n = n_.value, i = end_stage(n), e = 142 + n / 2, qi = n == 4 ? 1 : n == 6 ? 0 : n / 5;
      float (&acc_)[40] = qi == 0 ? q1 : qi == 1 ? q2 : qi == 2 ? oth : own;
      if (n == 0) while (!(fa(0) & fa(1) & fb(142) & fb(143))) {}
      if (n == 2) while (!(fa(2) & fa(3) & fb(144))) {}
      if (n == 6) while (!(fa(4) & fb(145) & fb(146) & mbar_try(bar_z, 0))) {}
      if (n == 10) while (!(fb(147) & fb(148) & fb(149))) {}
      const uint64_t d0 = mkdesc(fresh(), HI_O), dw = d0 + w * 256;
      WG_FENCE();
#pragma unroll
      for (int kk = 0; kk < 4; kk++)
        wg_ss80t(acc_, dw + (((4 + i) % 5) * (TA >> 4) + (kk >> 1) * 512 + (kk & 1) * 2),
                 d0 + ((OFF_B >> 4) + (e % 6) * (TB >> 4) + (n & 1) * 768 + (kk >> 1) * 384 + (kk & 1) * 64), 1);
      WG_COMMIT();
      if ((!(n & 1) && n <= N16) || n == 15 || n == 7) WG_WAIT(1);
      if (n == 0) rel_a(24);
      if (!(n & 1) && n <= 8) rel_b(8 * ((e - 1) % 6));
      if (n == 1) take(q2, aF + 40);
      if (n == 8) cluster_arrive();
      if (n == 10 || n == 12 || n == 14 || n == N16) rel_a(4u * n - 40);
      if (n == 7) reg_fence(q1);
      if (n == 10) reg_fence(q2);
      if (n == 15) reg_fence(oth);
      if (n == 14 || n == 17) while (!fb(n == 14 ? 150 : 151)) {}
      static_for<sent(n + 1) - sent(n)>([&](auto k_) { send(sent(n) + k_.value); });
      if (n == 8) {
        reg_fence(aS);
#pragma unroll
        for (int k = 0; k < 40; k++) oth[k] = kq & 1 ? aS[k] : aS[40 + k];
        reg_fence(oth);
      }
      if (n == 12) {
        reg_fence(aS);
#pragma unroll
        for (int k = 0; k < 40; k++) own[k] = kq & 1 ? aS[40 + k] : aS[k];
        reg_fence(own);
      }
    });
    {
      auto poll = [&](int e, uint4 (&v)[5]) {
#pragma unroll
        for (int i = 0; i < 5; i++) v[i] = ld_pkt(xbase + (kq ^ (e < 2 ? 2 + e : 1)) * (48 * 512) + (e < 2 ? kq & 1 : 2) * 1280 + i * 128);
      };
      auto check = [&](int e, uint4 (&v)[5]) {
        auto tags = [&]() { uint32_t t; asm("{\n.reg .b32 t;\nlop3.b32 t, %1, %2, %3, 0x80;\nlop3.b32 %0, t, %4, %5, 0x80;\n}\n" : "=r"(t) : "r"(v[0].x), "r"(v[1].x), "r"(v[2].x), "r"(v[3].x), "r"(v[4].x)); return t & 1; };
        while (!__all_sync(~0u, tags())) poll(e, v);
      };
      auto add = [&](const uint4 (&v)[5]) {
#pragma unroll
        for (int i = 0; i < 5; i++) {
          float* o = own + 8 * i;
          o[0] += bf_lo(v[i].x); o[1] += bf_hi(v[i].x); o[2] += bf_lo(v[i].y); o[3] += bf_hi(v[i].y);
          o[4] += bf_lo(v[i].z); o[5] += bf_hi(v[i].z); o[6] += bf_lo(v[i].w); o[7] += bf_hi(v[i].w);
        }
      };
      uint4 v[2][5];
#pragma unroll
      for (int e = 0; e < 2; e++) {
        mbar_wait(bar_e + 16 * e + 8 * w, 0);
#pragma unroll
        for (int i = 0; i < 5; i++) v[e][i] = lds128(sb + OFF_B + (2 + e) * TB + (w * 640 + i * 128 + t128) * 16);
      }
      check(0, v[0]); check(1, v[1]);
#pragma unroll
      for (int i = 0; i < 5; i++) v[0][i] = make_uint4(hadd2(v[0][i].x, v[1][i].x), hadd2(v[0][i].y, v[1][i].y), hadd2(v[0][i].z, v[1][i].z), hadd2(v[0][i].w, v[1][i].w));
      uint32_t xr[20];
      const uint32_t xs = sb + OFF_B + 4 * TB + cw * 2560, xa = xs + (lane & 15) * 160 + (lane >> 4) * 16;
      mbar_wait(bar_e + 32, 0);
#pragma unroll
      for (int k = 0; k < 5; k++) ldsm4(xa + 32 * k, xr + 4 * k);
      WG_WAIT(0);
      reg_fence(own);
      poll(2, v[1]);
      add(v[0]);
      reg_fence(own);
      check(2, v[1]); add(v[1]);
      if (lane == 0) mbar_arrive(bar_w);
#pragma unroll
      for (int i = 0; i < 20; i++) xr[i] = hadd2(xr[i], hmul2(pack_bf16(own[2 * i], own[2 * i + 1]), fr[i]));
#pragma unroll
      for (int k = 0; k < 5; k++) stsm4(xa + 32 * k, xr + 4 * k);
      asm volatile("fence.proxy.async.shared::cta;" ::: "memory");
      __syncwarp();
      if (elect()) {
        tma2d_store(&m.out, xs, nh * 320 + kq * 80, qt * 128 + cw * 16);
        asm volatile("cp.async.bulk.commit_group;\ncp.async.bulk.wait_group.read 0;" ::: "memory");
      }
      __syncwarp();
    }
    cluster_wait();
  } else {
    asm volatile("setmaxnreg.dec.sync.aligned.u32 40;");
    uint32_t tid_; asm volatile("mov.u32 %0, %%tid.x;" : "=r"(tid_));
    const int warp = __shfl_sync(~0u, tid_ >> 5, 0);
    auto is_warp = [&](int k) { uint32_t e; asm volatile("{\n.reg .pred q;\nsetp.eq.u32 q, %1, %2;\nselp.u32 %0, 1, 0, q;\n}" : "=r"(e) : "r"(warp), "r"(k)); return e != 0; };
    if (warp > 0) {
      const unsigned epoch = (unsigned)(__ldcg(&p.s->done) >> 7);
      int budget = WAIT_BUDGET;
      const uint32_t tag = epoch + 1;
      mbar_wait(bar_a + EA, 0, budget);
      mbar_wait(bar_b + (kg0 & ~7), 0, budget); mbar_wait(bar_b + (kg0 & ~7) + 8, 0, budget);
      float cs0 = 0.f, cs1 = 0.f;
      const int n = rank * 96 + (warp - 1) * 32;
#pragma unroll 1
      for (int kg = kg0 + (lane >> 4) * 5, e = kg + 5; kg < e; kg++) {
        const uint32_t ad = sb + OFF_B + kg * 3072 + (n >> 6) * 1024 + (n & 63) * 2 + (lane & 15) * 4;
#pragma unroll
        for (int k = 0; k < 8; k++) { const uint32_t v = lds32(ad ^ (k * 0x90)); cs0 += bf_lo(v); cs1 += bf_hi(v); }
      }
      cs0 += __shfl_xor_sync(~0u, cs0, 16); cs1 += __shfl_xor_sync(~0u, cs1, 16);
      if (lane < 16) st_pkt8((uint2*)(p.s->cs + (hg * 4 + (qt >> 2)) * 96 + (n >> 1) + lane) + ((qt >> 1) & 1), (__float_as_uint(cs0) & ~3u) | (tag & 3), __float_as_uint(cs1));
      if (lane < 2) { uint32_t a; asm volatile("mapa.shared::cluster.u32 %0, %1, %2;" : "=r"(a) : "r"(bar_d), "r"(lane)); mbar_arrive_cluster(a); }
      mbar_wait(bar_a + EA, 1, budget);
      uint4 v[5];
      while (true) {
        uint32_t bad = 0;
#pragma unroll
        for (int i = 0; i < 5; i++) v[i] = ld_pkt(i < 4 ? p.s->cs + (hg * 4 + i) * 96 + (tid_ - 32) : (const uint4*)p.s->stat + qt * 64 + (tid_ & 63));
#pragma unroll
        for (int i = 0; i < 5; i++) bad |= (v[i].x ^ tag) | (v[i].z ^ tag);
        if (!__any_sync(~0u, bad & 3) || --budget < 0) break;
      }
      asm volatile("st.shared.v4.u32 [%0], {%1,%2,%3,%4};" ::"r"(s_stat + (tid_ & 63) * 16), "r"(__byte_perm(v[4].x, 0, 0x3232)), "r"(v[4].y), "r"(__byte_perm(v[4].z, 0, 0x3232)), "r"(v[4].w) : "memory");
      cs0 = cs1 = 0.f;
#pragma unroll
      for (int i = 0; i < 4; i++) { cs0 += __uint_as_float(v[i].x & ~3u) + __uint_as_float(v[i].z & ~3u); cs1 += __uint_as_float(v[i].y) + __uint_as_float(v[i].w); }
#pragma unroll
      for (int k = 0; k < 8; k++) {
        const uint32_t t = k < 3 ? pack_bf16(cs0, cs1) : 0;
        sts32((sb + (warp - 1) * 1024 + lane * 4) ^ (k * 0x90), t);
        cs0 -= bf_lo(t); cs1 -= bf_hi(t);
      }
      asm volatile("fence.proxy.async.shared::cta;" ::: "memory");
      __syncwarp();
      if (lane < 2) mbar_arrive(bar_s);
      budget = errands(p.s, m, qt, hg, warp, tag, budget);
      if (is_warp(2)) {
        mbar_wait(bar_w, 0, budget);
        if (budget < 0) asm volatile("st.global.u32 [%0], %1;" ::"l"(0ull), "r"(budget) : "memory");
      }
    } else {
      uint32_t fb = bar_b + 16, dst = sb + OFF_B + 2 * TB, ph = 1;
      auto next = [&]() { fb += 8; dst += TB; if (fb == bar_b + 48) { fb = bar_b; dst = sb + OFF_B; ph ^= 1; } };
#pragma unroll 1
      for (int u = 0; u < 4; u++) {
        const int h = hg * 4 + u;
        int s = u ? (u == 2 ? 5 : 0) : s0 + 2;
#pragma unroll 1
        for (int i = u ? 0 : 2; i < 10; i++) {
          if (u == 0) {
            const uint32_t a8 = 8 * (i < 5 ? i : i - 5);
            mbar_wait(bar_a + 8 * (i < 7 ? i - 2 : i - 7), i >= 7);
            mbar_wait(bar_a + EA + a8, i < 5);
            if (elect()) { mbar_expect_tx(bar_a + a8, TA); tma2d(sb + a8 * (TA >> 3), &m.x, 64 * s, qt * 128, bar_a + a8); }
            if (i == 6 + (kg0 >> 3)) mbar_wait(bar_d, 0);
          }
          mbar_wait(fb + EB, ph);
          if (elect()) { mbar_expect_tx(fb, TB); tma4d_mc(dst + rank * (TB / 2), &m.wq, 3 * h, 8 * s + 4 * rank, fb); }
          next();
          if (++s == 10) s = 0;
        }
        const int kv0 = (h * SKC + (SKC - WIN)) / 8 + 4 * rank;
#pragma unroll 1
        for (int i = 0; i < 16; i++) {
          const bool isk = (0x2AAB >> i) & 1;
          mbar_wait(fb + EB, ph);
          if (elect()) { mbar_expect_tx(fb, TB); tma4d_mc(dst + rank * (TB / 2), isk ? &m.k : &m.v, 0, kv0 + 8 * (isk ? (i + 1) >> 1 : (i - 1) >> 1), fb); }
          next();
        }
      }
      const int cF = 10 * nh + 5 - 5 * (kq >> 1), cS = 10 * nh + 5 * (kq >> 1);
      const int kb = 4 * (k_block(lane, hg) + rank);
#pragma unroll 1
      for (int n = 0; n < 38; n++) {
        const int c2 = __shfl_sync(~0u, kb, n >> 1);
        mbar_wait(fb + EB, ph);
        if (elect()) { mbar_expect_tx(fb, TW); tma5d_mc(dst + rank * (TW / 2), &m.wo, c2, n & 1 ? cS : cF, fb); }
        next();
      }
      const int odd = ((0x7fb0 ^ (kq & 1 ? 0xffc00 : 0)) >> lane) & 1;
      const int tq = __shfl_sync(~0u, kb, 19 + end_stage(lane)) << 16 | odd << 7 | ((lane < 10 ? cF : cS) + 2 * odd);
#pragma unroll 1
      for (int n = 0; n < 20; n += 2) {
        const int t0 = __shfl_sync(~0u, tq, n), t1 = __shfl_sync(~0u, tq, n + 1);
        mbar_wait(fb + EB, ph);
        if (elect()) {
          mbar_expect_tx(fb, TB);
          tma5d_mc(dst + rank * (TB / 4), (const CUtensorMap*)((const char*)m.w3 + (t0 & 128)), t0 >> 16, t0 & 31, fb);
          tma5d_mc(dst + TB / 2 + rank * (TB / 4), (const CUtensorMap*)((const char*)m.w3 + (t1 & 128)), t1 >> 16, t1 & 31, fb);
        }
        next();
      }
      mbar_wait(bar_a + EA + 16, 0);
      if (elect()) { mbar_expect_tx(bar_e + 32, TW); tma2d(sb + OFF_B + 4 * TB, &m.xe, nh * 320 + kq * 80, qt * 128, bar_e + 32); }
    }
    if (warp & 1) {
      const int e = warp >> 1, ms = 2 * e + ((lane >> 2) & 1);
      const uint4* src = p.s->o + (size_t)(qt * 192 + nh * 24 + 10 + (kq ^ (2 + e)) * 48) * 512 + (kq & 1) * 1280 + (ms & 1) * 640;
      uint32_t todo = 0xff;
      bool ok = lane >= 8;
      mbar_wait(bar_z, 0);
#pragma unroll 1
      while (todo) {
        if (!ok) ok = ld_pkt(src + 4 * 128 + (lane & 3) * 32 + 31).x & 1;
        const uint32_t got = __ballot_sync(~0u, ok) & todo, go = __ballot_sync(~0u, ((got >> (lane & 28)) & 15) == 15);
        if (go) mbar_wait(bar_a + EA + 8 * e, 0);
        if ((go & 0x11) >> lane & 1) {
          mbar_expect_tx(bar_e + 8 * ms, TW / 2); bulk_load(sb + OFF_B + (2 + e) * TB + (ms & 1) * (TW / 2), src, TW / 2, bar_e + 8 * ms);
        }
        todo &= ~go;
      }
    }
    cluster_sync();
  }
}

typedef CUresult (*EncodeFn)(CUtensorMap*, CUtensorMapDataType, cuuint32_t, void*, const cuuint64_t*, const cuuint64_t*,
                             const cuuint32_t*, const cuuint32_t*, CUtensorMapInterleave, CUtensorMapSwizzle,
                             CUtensorMapL2promotion, CUtensorMapFloatOOBfill);

void encode(EncodeFn fn, CUtensorMap* tm, void* base, int rank, const cuuint64_t* dims, const cuuint64_t* strides,
            const cuuint32_t* box, CUtensorMapSwizzle sw) {
  const cuuint32_t es[5] = {1, 1, 1, 1, 1};
  fn(tm, CU_TENSOR_MAP_DATA_TYPE_BFLOAT16, rank, base, dims, strides, box, es, CU_TENSOR_MAP_INTERLEAVE_NONE, sw,
     CU_TENSOR_MAP_L2_PROMOTION_L2_128B, CU_TENSOR_MAP_FLOAT_OOB_FILL_NONE);
}

}

extern "C" void kernel_launch(void* const* d_in, const int* in_sizes, int n_in, void* d_out, int out_size) {
  static EncodeFn fn = nullptr;
  static Scratch* scr = nullptr;
  if (!fn) {
    void* f = nullptr;
    cudaDriverEntryPointQueryResult st;
    cudaGetDriverEntryPoint("cuTensorMapEncodeTiled", &f, cudaEnableDefault, &st);
    fn = (EncodeFn)f;
    cudaGetSymbolAddress((void**)&scr, g_scratch);
    cudaFuncSetAttribute(fused_kernel, cudaFuncAttributeMaxDynamicSharedMemorySize, SMEM_BYTES);
  }
  Maps m;
  { const cuuint64_t d[2] = {DM, SQ}, s[1] = {DM * 2}; const cuuint32_t b[2] = {64, 128};
    encode(fn, &m.x, d_in[0], 2, d, s, b, CU_TENSOR_MAP_SWIZZLE_128B);
    encode(fn, &m.xn, scr->xn, 2, d, s, b, CU_TENSOR_MAP_SWIZZLE_128B); }
  { const cuuint64_t d[4] = {64, 8, QD / 64, DM / 8}, s[3] = {QD * 2, 128, 8 * QD * 2}; const cuuint32_t b[4] = {64, 8, 3, 4};
    encode(fn, &m.wq, d_in[3], 4, d, s, b, CU_TENSOR_MAP_SWIZZLE_128B); }
  { const cuuint64_t d[4] = {64, 8, 3, NH * SKC / 8}, s[3] = {DH * 2, 128, 8 * DH * 2}; const cuuint32_t b[4] = {64, 8, 3, 4};
    encode(fn, &m.k, d_in[1], 4, d, s, b, CU_TENSOR_MAP_SWIZZLE_128B);
    encode(fn, &m.v, d_in[2], 4, d, s, b, CU_TENSOR_MAP_SWIZZLE_128B); }
  {
    const cuuint64_t d[5] = {32, 2, QD / 8, 4, DM / 32}, s[4] = {DM * 2, 8 * DM * 2, 2 * DM * 2, 64}; const cuuint32_t b[5] = {32, 2, 4, 4, 5};
    encode(fn, &m.wo, d_in[4], 5, d, s, b, CU_TENSOR_MAP_SWIZZLE_64B);
    const cuuint32_t b3[5] = {32, 2, 4, 4, 3};
    encode(fn, &m.w3[0], d_in[4], 5, d, s, b3, CU_TENSOR_MAP_SWIZZLE_64B);
    encode(fn, &m.w3[1], (char*)d_in[4] + 32, 5, d, s, b3, CU_TENSOR_MAP_SWIZZLE_64B); }
  { const cuuint64_t d[2] = {DM, SQ}, s[1] = {DM * 2}; const cuuint32_t bg[2] = {80, 24}, bx[2] = {80, 128}, bo[2] = {80, 16};
    encode(fn, &m.xg, d_in[0], 2, d, s, bg, CU_TENSOR_MAP_SWIZZLE_NONE);
    encode(fn, &m.xe, d_in[0], 2, d, s, bx, CU_TENSOR_MAP_SWIZZLE_NONE);
    encode(fn, &m.out, d_out, 2, d, s, bo, CU_TENSOR_MAP_SWIZZLE_NONE); }
  Params p;
  p.x = (const __nv_bfloat16*)d_in[0]; p.wr = (const __nv_bfloat16*)d_in[6]; p.wg = (const __nv_bfloat16*)d_in[7];
  p.wu = (const __nv_bfloat16*)d_in[8]; p.wd = (const __nv_bfloat16*)d_in[9];

  p.k = (const __nv_bfloat16*)d_in[1]; p.v = (const __nv_bfloat16*)d_in[2]; p.s = scr;
  cudaLaunchConfig_t cfg = {};
  cfg.gridDim = dim3(132); cfg.blockDim = dim3(384); cfg.dynamicSmemBytes = SMEM_BYTES; cfg.stream = cudaStreamPerThread;
  cudaLaunchKernelEx(&cfg, fused_kernel, p, m);
}
```

```cpp
#include <cuda_runtime.h>
#include <cuda_bf16.h>
#include <cuda.h>
#include <stdint.h>

namespace {

constexpr int SQ = 2048, DM = 640, NH = 32, DH = 192, SKC = 2048, WIN = 512, FF = 1536;
constexpr int QD = NH * DH;
constexpr uint32_t TA = 16384, TB = 24576, TW = 20480, OFF_B = 5 * TA, OFF_M = OFF_B + 6 * TB, SMEM_BYTES = OFF_M + 3072;
constexpr int WAIT_BUDGET = 1 << 20;

constexpr int FL_XN = 0;
constexpr int FL_O = 512;
constexpr int FL_RD = FL_O + 1024;
constexpr int FL_FFN = FL_RD + 1024;
constexpr int FL_SIDE = FL_FFN + 32;
struct __align__(1024) Scratch {
  unsigned long long done, pad0[15];
  unsigned flag[FL_SIDE + 32];
  uint4 cand[8];
  float ffn[4 * 2 * DM];
  int sel[4];
  __nv_bfloat16 gsel[2 * DM];
  uint4 cs[8 * 4 * DH / 2];
  uint2 stat[SQ];
  __align__(1024) __nv_bfloat16 xn[SQ * DM];
  __align__(1024) uint4 o[SQ * QD / 8];
};
__device__ Scratch g_scratch;

__device__ __forceinline__ uint32_t smem_u32(const void* p) { return (uint32_t)__cvta_generic_to_shared(p); }
__device__ __forceinline__ void mbar_init(uint32_t bar, int cnt) { asm volatile("mbarrier.init.shared::cta.b64 [%0], %1;" ::"r"(bar), "r"(cnt)); }
__device__ __forceinline__ void mbar_expect_tx(uint32_t bar, uint32_t bytes) {
  asm volatile("mbarrier.arrive.expect_tx.shared::cta.b64 _, [%0], %1;" ::"r"(bar), "r"(bytes) : "memory");
}
__device__ __forceinline__ void mbar_arrive(uint32_t bar) { asm volatile("mbarrier.arrive.shared::cta.b64 _, [%0];" ::"r"(bar) : "memory"); }
__device__ __forceinline__ void mbar_arrive_cluster(uint32_t addr) { asm volatile("mbarrier.arrive.shared::cluster.b64 _, [%0];" ::"r"(addr) : "memory"); }
__device__ __forceinline__ bool mbar_try(uint32_t bar, uint32_t parity) {
  uint32_t ok;
  asm volatile("{\n.reg .pred p;\nmbarrier.try_wait.parity.shared::cta.b64 p, [%1], %2;\nselp.u32 %0, 1, 0, p;\n}\n" : "=r"(ok) : "r"(bar), "r"(parity) : "memory");
  return ok;
}
__device__ __forceinline__ void mbar_wait(uint32_t bar, uint32_t parity, int& budget) {
#pragma unroll 1
  while (!mbar_try(bar, parity)) { if (--budget < 0) break; }
}
__device__ __forceinline__ void mbar_wait(uint32_t bar, uint32_t parity) {
#pragma unroll 1
  while (!mbar_try(bar, parity)) {}
}
__device__ __forceinline__ unsigned ld_acquire(const unsigned* p) { unsigned v; asm volatile("ld.acquire.gpu.global.u32 %0, [%1];" : "=r"(v) : "l"(p) : "memory"); return v; }
__device__ __forceinline__ void wait_flag(const unsigned* p, unsigned target) {
#pragma unroll 1
  while (__any_sync(~0u, (int)(ld_acquire(p) - target) < 0)) {}
}
__device__ __forceinline__ void red_release(unsigned* p) { asm volatile("red.release.gpu.global.add.u32 [%0], 1;" ::"l"(p) : "memory"); }
__device__ __forceinline__ void fence_proxy_async() { asm volatile("fence.proxy.async.global;" ::: "memory"); }
__device__ __forceinline__ bool elect() {
  uint32_t p;
  asm volatile("{\n.reg .pred P;\nelect.sync _|P, 0xffffffff;\nselp.u32 %0, 1, 0, P;\n}\n" : "=r"(p));
  return p;
}
__device__ __forceinline__ void cluster_arrive() { asm volatile("barrier.cluster.arrive.relaxed.aligned;" ::: "memory"); }
__device__ __forceinline__ void cluster_wait() { asm volatile("barrier.cluster.wait.aligned;" ::: "memory"); }
__device__ __forceinline__ void cluster_sync() { cluster_arrive(); cluster_wait(); }
__device__ __forceinline__ void tma2d(uint32_t dst, const CUtensorMap* tm, int c0, int c1, uint32_t bar) {
  asm volatile("cp.async.bulk.tensor.2d.shared::cluster.global.mbarrier::complete_tx::bytes [%0], [%1, {%3, %4}], [%2];"
               ::"r"(dst), "l"(tm), "r"(bar), "r"(c0), "r"(c1) : "memory");
}
constexpr uint64_t POL_FIRST = 0x12F0000000000000ull;
__device__ __forceinline__ void tma4d_mc(uint32_t dst, const CUtensorMap* tm, int c2, int c3, uint32_t bar) {
  asm volatile("cp.async.bulk.tensor.4d.shared::cluster.global.mbarrier::complete_tx::bytes.multicast::cluster.L2::cache_hint [%0], [%1, {%3, %3, %4, %5}], [%2], %6, %7;"
               ::"r"(dst), "l"(tm), "r"(bar), "r"(0), "r"(c2), "r"(c3), "h"((uint16_t)3), "l"(POL_FIRST) : "memory");
}
__device__ __forceinline__ void tma5d_mc(uint32_t dst, const CUtensorMap* tm, int c2, int c4, uint32_t bar) {
  asm volatile("cp.async.bulk.tensor.5d.shared::cluster.global.mbarrier::complete_tx::bytes.multicast::cluster.L2::cache_hint [%0], [%1, {%3, %3, %4, %3, %5}], [%2], %6, %7;"
               ::"r"(dst), "l"(tm), "r"(bar), "r"(0), "r"(c2), "r"(c4), "h"((uint16_t)3), "l"(POL_FIRST) : "memory");
}
__device__ __forceinline__ void bulk_load(uint32_t dst, const void* src, uint32_t bytes, uint32_t bar) {
  asm volatile("cp.async.bulk.shared::cluster.global.mbarrier::complete_tx::bytes.L2::cache_hint [%0], [%1], %2, [%3], %4;" ::"r"(dst), "l"(src), "r"(bytes), "r"(bar), "l"(POL_FIRST) : "memory");
}
__device__ __forceinline__ void tma2d_store(const CUtensorMap* tm, uint32_t src, int c0, int c1) {
  asm volatile("cp.async.bulk.tensor.2d.global.shared::cta.bulk_group [%0, {%2, %3}], [%1];" ::"l"(tm), "r"(src), "r"(c0), "r"(c1) : "memory");
}
__device__ __forceinline__ uint32_t lds32(uint32_t a) { uint32_t v; asm volatile("ld.shared.u32 %0, [%1];" : "=r"(v) : "r"(a) : "memory"); return v; }
__device__ __forceinline__ uint2 lds64(uint32_t a) { uint2 v; asm volatile("ld.shared.v2.u32 {%0,%1}, [%2];" : "=r"(v.x), "=r"(v.y) : "r"(a) : "memory"); return v; }
__device__ __forceinline__ uint4 lds128(uint32_t a) { uint4 v; asm volatile("ld.shared.v4.u32 {%0,%1,%2,%3}, [%4];" : "=r"(v.x), "=r"(v.y), "=r"(v.z), "=r"(v.w) : "r"(a) : "memory"); return v; }
__device__ __forceinline__ void ldsm4(uint32_t a, uint32_t* v) {
  asm volatile("ldmatrix.sync.aligned.m8n8.x4.shared.b16 {%0,%1,%2,%3}, [%4];" : "=r"(v[0]), "=r"(v[1]), "=r"(v[2]), "=r"(v[3]) : "r"(a) : "memory");
}
__device__ __forceinline__ void stsm4(uint32_t a, const uint32_t* v) {
  asm volatile("stmatrix.sync.aligned.m8n8.x4.shared.b16 [%0], {%1,%2,%3,%4};" ::"r"(a), "r"(v[0]), "r"(v[1]), "r"(v[2]), "r"(v[3]) : "memory");
}
__device__ __forceinline__ void sts32(uint32_t a, uint32_t v) { asm volatile("st.shared.u32 [%0], %1;" ::"r"(a), "r"(v) : "memory"); }
__device__ __forceinline__ void st_pkt(uint4* p, uint32_t a, uint32_t b, uint32_t c, uint32_t d) {
  asm volatile("st.relaxed.gpu.global.v4.b32 [%0], {%1, %2, %3, %4};" ::"l"(p), "r"(a), "r"(b), "r"(c), "r"(d) : "memory");
}
__device__ __forceinline__ void st_pkt8(void* p, uint32_t a, uint32_t b) {
  asm volatile("{\n.reg .b64 v;\nmov.b64 v, {%1, %2};\nst.relaxed.gpu.global.b64 [%0], v;\n}\n" ::"l"(p), "r"(a), "r"(b) : "memory");
}
__device__ __forceinline__ uint4 ld_pkt(const uint4* p) {
  uint4 v;
  asm volatile("{\n.reg .b128 v;\nld.relaxed.gpu.global.b128 v, [%4];\nmov.b128 {%0, %1, %2, %3}, v;\n}\n" : "=r"(v.x), "=r"(v.y), "=r"(v.z), "=r"(v.w) : "l"(p) : "memory");
  return v;
}
__device__ __forceinline__ uint4 ldg_nc(const void* p) {
  uint4 v;
  asm volatile("ld.global.nc.v4.u32 {%0,%1,%2,%3}, [%4];" : "=r"(v.x), "=r"(v.y), "=r"(v.z), "=r"(v.w) : "l"(p));
  return v;
}
#define WG_FENCE() asm volatile("wgmma.fence.sync.aligned;" ::: "memory")
#define WG_COMMIT() asm volatile("wgmma.commit_group.sync.aligned;" ::: "memory")
#define WG_WAIT(n) asm volatile("wgmma.wait_group.sync.aligned " #n ";" ::: "memory")
template <int N> __device__ __forceinline__ void reg_fence(float (&d)[N]) {
#pragma unroll
  for (int i = 0; i < N; i++) asm volatile("" : "+f"(d[i])::"memory");
}
template <int N> __device__ __forceinline__ void reg_fence(uint32_t (&d)[N]) {
#pragma unroll
  for (int i = 0; i < N; i++) asm volatile("" : "+r"(d[i])::"memory");
}
__device__ __forceinline__ constexpr uint64_t desc_hi(uint32_t lbo, uint32_t sbo, uint64_t sw) {
  return ((uint64_t)(lbo >> 4) << 16) | ((uint64_t)(sbo >> 4) << 32) | (sw << 62);
}
__device__ __forceinline__ uint64_t mkdesc(uint32_t addr, uint64_t hi) { return hi | (uint64_t)((addr & 0x3FFFF) >> 4); }
__device__ __forceinline__ uint32_t pack_bf16(float lo, float hi) { uint32_t r; asm("cvt.rn.bf16x2.f32 %0, %1, %2;" : "=r"(r) : "f"(hi), "f"(lo)); return r; }
__device__ __forceinline__ float bf_lo(uint32_t v) { return __uint_as_float(v << 16); }
__device__ __forceinline__ float bf_hi(uint32_t v) { return __uint_as_float(v & 0xffff0000u); }
__device__ __forceinline__ uint32_t hadd2(uint32_t a, uint32_t b) { uint32_t r; asm("add.rn.bf16x2 %0, %1, %2;" : "=r"(r) : "r"(a), "r"(b)); return r; }
__device__ __forceinline__ uint32_t hsub2(uint32_t a, uint32_t b) { uint32_t r; asm("sub.rn.bf16x2 %0, %1, %2;" : "=r"(r) : "r"(a), "r"(b)); return r; }
__device__ __forceinline__ uint32_t hmul2(uint32_t a, uint32_t b) { uint32_t r; asm("mul.rn.bf16x2 %0, %1, %2;" : "=r"(r) : "r"(a), "r"(b)); return r; }
__device__ __forceinline__ float rbf(float x) { return __bfloat162float(__float2bfloat16_rn(x)); }
__device__ __forceinline__ float ex2(float x) { float y; asm("ex2.approx.ftz.f32 %0, %1;" : "=f"(y) : "f"(x)); return y; }
__device__ __forceinline__ float rcp(float x) { float y; asm("rcp.approx.ftz.f32 %0, %1;" : "=f"(y) : "f"(x)); return y; }
__device__ __forceinline__ float sigmoid_f(float x) { return rcp(1.f + ex2(x * -1.4426950408889634f)); }
__device__ __forceinline__ float silu_f(float x) { return x * sigmoid_f(x); }

__device__ __forceinline__ void wg_ss192t(float (&d)[96], uint64_t da, uint64_t db, int sd) {
  asm volatile("{\n.reg .pred p;\nsetp.ne.b32 p, %98, 0;\n"
    "wgmma.mma_async.sync.aligned.m64n192k16.f32.bf16.bf16 {%0,%1,%2,%3,%4,%5,%6,%7,%8,%9,%10,%11,%12,%13,%14,%15,%16,%17,%18,%19,%20,%21,%22,%23,%24,%25,%26,%27,%28,%29,%30,%31,%32,%33,%34,%35,%36,%37,%38,%39,%40,%41,%42,%43,%44,%45,%46,%47,%48,%49,%50,%51,%52,%53,%54,%55,%56,%57,%58,%59,%60,%61,%62,%63,%64,%65,%66,%67,%68,%69,%70,%71,%72,%73,%74,%75,%76,%77,%78,%79,%80,%81,%82,%83,%84,%85,%86,%87,%88,%89,%90,%91,%92,%93,%94,%95}, %96, %97, p, 1, 1, 0, 1;\n}\n"
    : "+f"(d[0]),"+f"(d[1]),"+f"(d[2]),"+f"(d[3]),"+f"(d[4]),"+f"(d[5]),"+f"(d[6]),"+f"(d[7]),"+f"(d[8]),"+f"(d[9]),"+f"(d[10]),"+f"(d[11]),"+f"(d[12]),"+f"(d[13]),"+f"(d[14]),"+f"(d[15]),"+f"(d[16]),"+f"(d[17]),"+f"(d[18]),"+f"(d[19]),"+f"(d[20]),"+f"(d[21]),"+f"(d[22]),"+f"(d[23]),"+f"(d[24]),"+f"(d[25]),"+f"(d[26]),"+f"(d[27]),"+f"(d[28]),"+f"(d[29]),"+f"(d[30]),"+f"(d[31]),"+f"(d[32]),"+f"(d[33]),"+f"(d[34]),"+f"(d[35]),"+f"(d[36]),"+f"(d[37]),"+f"(d[38]),"+f"(d[39]),"+f"(d[40]),"+f"(d[41]),"+f"(d[42]),"+f"(d[43]),"+f"(d[44]),"+f"(d[45]),"+f"(d[46]),"+f"(d[47]),"+f"(d[48]),"+f"(d[49]),"+f"(d[50]),"+f"(d[51]),"+f"(d[52]),"+f"(d[53]),"+f"(d[54]),"+f"(d[55]),"+f"(d[56]),"+f"(d[57]),"+f"(d[58]),"+f"(d[59]),"+f"(d[60]),"+f"(d[61]),"+f"(d[62]),"+f"(d[63]),"+f"(d[64]),"+f"(d[65]),"+f"(d[66]),"+f"(d[67]),"+f"(d[68]),"+f"(d[69]),"+f"(d[70]),"+f"(d[71]),"+f"(d[72]),"+f"(d[73]),"+f"(d[74]),"+f"(d[75]),"+f"(d[76]),"+f"(d[77]),"+f"(d[78]),"+f"(d[79]),"+f"(d[80]),"+f"(d[81]),"+f"(d[82]),"+f"(d[83]),"+f"(d[84]),"+f"(d[85]),"+f"(d[86]),"+f"(d[87]),"+f"(d[88]),"+f"(d[89]),"+f"(d[90]),"+f"(d[91]),"+f"(d[92]),"+f"(d[93]),"+f"(d[94]),"+f"(d[95])
    : "l"(da), "l"(db), "r"(sd));
}
__device__ __forceinline__ void wg_rs64(float (&d)[32], uint32_t a0, uint32_t a1, uint32_t a2, uint32_t a3, uint64_t db, int sd) {
  asm volatile("{\n.reg .pred p;\nsetp.ne.b32 p, %37, 0;\n"
    "wgmma.mma_async.sync.aligned.m64n64k16.f32.bf16.bf16 {%0,%1,%2,%3,%4,%5,%6,%7,%8,%9,%10,%11,%12,%13,%14,%15,%16,%17,%18,%19,%20,%21,%22,%23,%24,%25,%26,%27,%28,%29,%30,%31}, {%32,%33,%34,%35}, %36, p, 1, 1, 0;\n}\n"
    : "+f"(d[0]),"+f"(d[1]),"+f"(d[2]),"+f"(d[3]),"+f"(d[4]),"+f"(d[5]),"+f"(d[6]),"+f"(d[7]),"+f"(d[8]),"+f"(d[9]),"+f"(d[10]),"+f"(d[11]),"+f"(d[12]),"+f"(d[13]),"+f"(d[14]),"+f"(d[15]),"+f"(d[16]),"+f"(d[17]),"+f"(d[18]),"+f"(d[19]),"+f"(d[20]),"+f"(d[21]),"+f"(d[22]),"+f"(d[23]),"+f"(d[24]),"+f"(d[25]),"+f"(d[26]),"+f"(d[27]),"+f"(d[28]),"+f"(d[29]),"+f"(d[30]),"+f"(d[31])
    : "r"(a0), "r"(a1), "r"(a2), "r"(a3), "l"(db), "r"(sd));
}
__device__ __forceinline__ void wg_rs192t(float (&d)[96], uint32_t a0, uint32_t a1, uint32_t a2, uint32_t a3, uint64_t db, int sd) {
  asm volatile("{\n.reg .pred p;\nsetp.ne.b32 p, %101, 0;\n"
    "wgmma.mma_async.sync.aligned.m64n192k16.f32.bf16.bf16 {%0,%1,%2,%3,%4,%5,%6,%7,%8,%9,%10,%11,%12,%13,%14,%15,%16,%17,%18,%19,%20,%21,%22,%23,%24,%25,%26,%27,%28,%29,%30,%31,%32,%33,%34,%35,%36,%37,%38,%39,%40,%41,%42,%43,%44,%45,%46,%47,%48,%49,%50,%51,%52,%53,%54,%55,%56,%57,%58,%59,%60,%61,%62,%63,%64,%65,%66,%67,%68,%69,%70,%71,%72,%73,%74,%75,%76,%77,%78,%79,%80,%81,%82,%83,%84,%85,%86,%87,%88,%89,%90,%91,%92,%93,%94,%95}, {%96,%97,%98,%99}, %100, p, 1, 1, 1;\n}\n"
    : "+f"(d[0]),"+f"(d[1]),"+f"(d[2]),"+f"(d[3]),"+f"(d[4]),"+f"(d[5]),"+f"(d[6]),"+f"(d[7]),"+f"(d[8]),"+f"(d[9]),"+f"(d[10]),"+f"(d[11]),"+f"(d[12]),"+f"(d[13]),"+f"(d[14]),"+f"(d[15]),"+f"(d[16]),"+f"(d[17]),"+f"(d[18]),"+f"(d[19]),"+f"(d[20]),"+f"(d[21]),"+f"(d[22]),"+f"(d[23]),"+f"(d[24]),"+f"(d[25]),"+f"(d[26]),"+f"(d[27]),"+f"(d[28]),"+f"(d[29]),"+f"(d[30]),"+f"(d[31]),"+f"(d[32]),"+f"(d[33]),"+f"(d[34]),"+f"(d[35]),"+f"(d[36]),"+f"(d[37]),"+f"(d[38]),"+f"(d[39]),"+f"(d[40]),"+f"(d[41]),"+f"(d[42]),"+f"(d[43]),"+f"(d[44]),"+f"(d[45]),"+f"(d[46]),"+f"(d[47]),"+f"(d[48]),"+f"(d[49]),"+f"(d[50]),"+f"(d[51]),"+f"(d[52]),"+f"(d[53]),"+f"(d[54]),"+f"(d[55]),"+f"(d[56]),"+f"(d[57]),"+f"(d[58]),"+f"(d[59]),"+f"(d[60]),"+f"(d[61]),"+f"(d[62]),"+f"(d[63]),"+f"(d[64]),"+f"(d[65]),"+f"(d[66]),"+f"(d[67]),"+f"(d[68]),"+f"(d[69]),"+f"(d[70]),"+f"(d[71]),"+f"(d[72]),"+f"(d[73]),"+f"(d[74]),"+f"(d[75]),"+f"(d[76]),"+f"(d[77]),"+f"(d[78]),"+f"(d[79]),"+f"(d[80]),"+f"(d[81]),"+f"(d[82]),"+f"(d[83]),"+f"(d[84]),"+f"(d[85]),"+f"(d[86]),"+f"(d[87]),"+f"(d[88]),"+f"(d[89]),"+f"(d[90]),"+f"(d[91]),"+f"(d[92]),"+f"(d[93]),"+f"(d[94]),"+f"(d[95])
    : "r"(a0), "r"(a1), "r"(a2), "r"(a3), "l"(db), "r"(sd));
}
__device__ __forceinline__ void wg_ss160t(float (&d)[80], uint64_t da, uint64_t db, int sd) {
  asm volatile("{\n.reg .pred p;\nsetp.ne.b32 p, %82, 0;\n"
    "wgmma.mma_async.sync.aligned.m64n160k16.f32.bf16.bf16 {%0,%1,%2,%3,%4,%5,%6,%7,%8,%9,%10,%11,%12,%13,%14,%15,%16,%17,%18,%19,%20,%21,%22,%23,%24,%25,%26,%27,%28,%29,%30,%31,%32,%33,%34,%35,%36,%37,%38,%39,%40,%41,%42,%43,%44,%45,%46,%47,%48,%49,%50,%51,%52,%53,%54,%55,%56,%57,%58,%59,%60,%61,%62,%63,%64,%65,%66,%67,%68,%69,%70,%71,%72,%73,%74,%75,%76,%77,%78,%79}, %80, %81, p, 1, 1, 0, 1;\n}\n"
    : "+f"(d[0]),"+f"(d[1]),"+f"(d[2]),"+f"(d[3]),"+f"(d[4]),"+f"(d[5]),"+f"(d[6]),"+f"(d[7]),"+f"(d[8]),"+f"(d[9]),"+f"(d[10]),"+f"(d[11]),"+f"(d[12]),"+f"(d[13]),"+f"(d[14]),"+f"(d[15]),"+f"(d[16]),"+f"(d[17]),"+f"(d[18]),"+f"(d[19]),"+f"(d[20]),"+f"(d[21]),"+f"(d[22]),"+f"(d[23]),"+f"(d[24]),"+f"(d[25]),"+f"(d[26]),"+f"(d[27]),"+f"(d[28]),"+f"(d[29]),"+f"(d[30]),"+f"(d[31]),"+f"(d[32]),"+f"(d[33]),"+f"(d[34]),"+f"(d[35]),"+f"(d[36]),"+f"(d[37]),"+f"(d[38]),"+f"(d[39]),"+f"(d[40]),"+f"(d[41]),"+f"(d[42]),"+f"(d[43]),"+f"(d[44]),"+f"(d[45]),"+f"(d[46]),"+f"(d[47]),"+f"(d[48]),"+f"(d[49]),"+f"(d[50]),"+f"(d[51]),"+f"(d[52]),"+f"(d[53]),"+f"(d[54]),"+f"(d[55]),"+f"(d[56]),"+f"(d[57]),"+f"(d[58]),"+f"(d[59]),"+f"(d[60]),"+f"(d[61]),"+f"(d[62]),"+f"(d[63]),"+f"(d[64]),"+f"(d[65]),"+f"(d[66]),"+f"(d[67]),"+f"(d[68]),"+f"(d[69]),"+f"(d[70]),"+f"(d[71]),"+f"(d[72]),"+f"(d[73]),"+f"(d[74]),"+f"(d[75]),"+f"(d[76]),"+f"(d[77]),"+f"(d[78]),"+f"(d[79])
    : "l"(da), "l"(db), "r"(sd));
}
__device__ __forceinline__ void wg_ss80t(float (&d)[40], uint64_t da, uint64_t db, int sd) {
  asm volatile("{\n.reg .pred p;\nsetp.ne.b32 p, %42, 0;\n"
    "wgmma.mma_async.sync.aligned.m64n80k16.f32.bf16.bf16 {%0,%1,%2,%3,%4,%5,%6,%7,%8,%9,%10,%11,%12,%13,%14,%15,%16,%17,%18,%19,%20,%21,%22,%23,%24,%25,%26,%27,%28,%29,%30,%31,%32,%33,%34,%35,%36,%37,%38,%39}, %40, %41, p, 1, 1, 0, 1;\n}\n"
    : "+f"(d[0]),"+f"(d[1]),"+f"(d[2]),"+f"(d[3]),"+f"(d[4]),"+f"(d[5]),"+f"(d[6]),"+f"(d[7]),"+f"(d[8]),"+f"(d[9]),"+f"(d[10]),"+f"(d[11]),"+f"(d[12]),"+f"(d[13]),"+f"(d[14]),"+f"(d[15]),"+f"(d[16]),"+f"(d[17]),"+f"(d[18]),"+f"(d[19]),"+f"(d[20]),"+f"(d[21]),"+f"(d[22]),"+f"(d[23]),"+f"(d[24]),"+f"(d[25]),"+f"(d[26]),"+f"(d[27]),"+f"(d[28]),"+f"(d[29]),"+f"(d[30]),"+f"(d[31]),"+f"(d[32]),"+f"(d[33]),"+f"(d[34]),"+f"(d[35]),"+f"(d[36]),"+f"(d[37]),"+f"(d[38]),"+f"(d[39])
    : "l"(da), "l"(db), "r"(sd));
}

struct Maps { CUtensorMap x, xn, wq, k, v, wo, w3[2], xg, xe, out; };
struct Params {
  const __nv_bfloat16 *x, *wr, *wg, *wu, *wd, *k, *v;
  Scratch* s;
};

__device__ __forceinline__ void side_cta(const Params& p, int sc, unsigned epoch, float* sm) {
  const int tid = threadIdx.x, lane = tid & 31, warp = tid >> 5;
  int budget = WAIT_BUDGET;
  float* s_x = sm;
  float* s_red = sm + 1280;
  float* s_h = s_red + 6144;
  uint4* s_c = (uint4*)(s_h + 768);
  uint2* s_st = (uint2*)(s_c + 16);
  constexpr int DEPTH = 7, STEP = 4 * 6144;
  const uint32_t ring = smem_u32(s_st + 512) + tid * 16;
  const int cg = tid % 96, ks = tid / 96, cd = tid % 80, kd = tid / 80;
  const __nv_bfloat16* wp = (cg < 48 ? p.wg : p.wu) + (size_t)(ks * 160) * FF + sc * 384 + (cg % 48) * 8;
  int kf = 0, pitch = FF;
  uint32_t slot = ring;
  auto refill = [&]() {
    if (kf == 40) { wp = p.wd + (size_t)(sc * 384 + kd * 96) * DM + cd * 8; pitch = DM; }
    if (kf < (tid < 320 ? 64 : 40)) {
#pragma unroll
      for (int j = 0; j < 4; j++) asm volatile("cp.async.cg.shared.global.L2::cache_hint [%0], [%1], 16, %2;" ::"r"(slot + j * 6144), "l"(wp + j * pitch), "l"(POL_FIRST) : "memory");
    }
    asm volatile("cp.async.commit_group;" ::: "memory");
    wp += 4 * pitch; kf++;
    slot += STEP; if (slot == ring + DEPTH * STEP) slot = ring;
  };
  auto gemv = [&](int n, const float* x0, const float* x1, float* out) {
    float a[2][8] = {};
#pragma unroll 1
    for (int k = 0; k < n; k += 4) {
      refill();
      asm volatile("cp.async.wait_group %0;" ::"n"(DEPTH - 1) : "memory");
      const float4 f0 = *(const float4*)(x0 + k), f1 = *(const float4*)(x1 + k);
      const float y0[4] = {f0.x, f0.y, f0.z, f0.w}, y1[4] = {f1.x, f1.y, f1.z, f1.w};
#pragma unroll
      for (int j = 0; j < 4; j++) {
        const uint4 v = lds128(slot + j * 6144);
        const uint32_t u[4] = {v.x, v.y, v.z, v.w};
#pragma unroll
        for (int i = 0; i < 4; i++) {
          a[0][2 * i] += y0[j] * bf_lo(u[i]); a[0][2 * i + 1] += y0[j] * bf_hi(u[i]);
          a[1][2 * i] += y1[j] * bf_lo(u[i]); a[1][2 * i + 1] += y1[j] * bf_hi(u[i]);
        }
      }
    }
#pragma unroll
    for (int i = 0; i < 16; i++) out[(i >> 3) * 768 + (i & 7)] = a[i >> 3][i & 7];
  };
  auto load_row = [&](const __nv_bfloat16* r, uint32_t (&v)[10]) {
    const uint4 a = __ldg((const uint4*)r + lane), b = __ldg((const uint4*)r + 32 + lane);
    const uint2 c = __ldg((const uint2*)r + 128 + lane);
    v[0] = a.x; v[1] = a.y; v[2] = a.z; v[3] = a.w; v[4] = b.x; v[5] = b.y; v[6] = b.z; v[7] = b.w; v[8] = c.x; v[9] = c.y;
  };
  uint32_t wr[10], xb[3][10];
  load_row(p.wr, wr);
  auto stat2 = [&](int pair) {
    uint4 v;
    do v = ld_pkt((const uint4*)p.s->stat + pair); while ((((v.x ^ (epoch + 1)) | (v.z ^ (epoch + 1))) & 0xffff) && --budget >= 0);
    return make_uint4(__byte_perm(v.x, 0, 0x3232), v.y, __byte_perm(v.z, 0, 0x3232), v.w);
  };
  if (tid < 256) ((uint4*)s_st)[tid] = stat2(sc * 256 + tid);
  __syncthreads();
#pragma unroll
  for (int b = 0; b < 3; b++) load_row(p.x + (size_t)(sc * 512 + warp + 12 * b) * DM, xb[b]);
#pragma unroll 1
  for (int k = 0; k < DEPTH - 1; k++) refill();
  float v0 = -INFINITY, v1 = -INFINITY; int i0 = 0xfff, i1 = 0xfff;
  auto better = [](float a, int ia, float b, int ib) { return a > b || (a == b && ia < ib); };
  auto push = [&](float v, int i) {
    if (better(v, i, v0, i0)) { v1 = v0; i1 = i0; v0 = v; i0 = i; }
    else if (better(v, i, v1, i1)) { v1 = v; i1 = i; }
  };
  auto push2 = [&](uint4 c) { push(__uint_as_float(c.x), c.y & 0xfff); push(__uint_as_float(c.z), c.w & 0xfff); };
#pragma unroll 1
  for (int l3 = warp; l3 < 512; l3 += 36) {
#pragma unroll
    for (int b = 0; b < 3; b++) {
      const int lr = l3 + 12 * b;
      if (lr >= 512) break;
      const uint2 st = s_st[lr];
      uint32_t v[10];
#pragma unroll
      for (int i = 0; i < 10; i++) v[i] = hsub2(xb[b][i], st.x);
      if (lr + 36 < 512) load_row(p.x + (size_t)(sc * 512 + lr + 36) * DM, xb[b]);
      float r0 = 0.f, r1 = 0.f;
#pragma unroll
      for (int i = 0; i < 10; i++) {
        const uint32_t xn = pack_bf16(bf_lo(v[i]) * __uint_as_float(st.y), bf_hi(v[i]) * __uint_as_float(st.y));
        r0 = fmaf(bf_lo(xn), bf_lo(wr[i]), r0); r1 = fmaf(bf_hi(xn), bf_hi(wr[i]), r1);
      }
      r0 += r1;
#pragma unroll
      for (int o = 16; o > 0; o >>= 1) r0 += __shfl_xor_sync(~0u, r0, o);
      push(rbf(r0), sc * 512 + lr);
    }
  }
  if (lane == 0) s_c[warp] = make_uint4(__float_as_uint(v0), i0, __float_as_uint(v1), i1);
  __syncthreads();
#pragma unroll 1
  for (int w = 1; w < 12; w++) push2(s_c[(warp + w) % 12]);
  const uint32_t tag = (epoch + 1) << 12;
  if (tid == 0) st_pkt(p.s->cand + sc, __float_as_uint(v0), i0 | tag, __float_as_uint(v1), i1);
  {
    uint4 c;
    do c = ld_pkt(p.s->cand + (lane & 3)); while (((c.y ^ tag) >> 12) && --budget >= 0);
#pragma unroll 1
    for (int w = 1; w < 4; w++) { const int o = (sc + w) & 3; push2(make_uint4(__shfl_sync(~0u, c.x, o), __shfl_sync(~0u, c.y, o), __shfl_sync(~0u, c.z, o), __shfl_sync(~0u, c.w, o))); }
  }
  if (i0 >= SQ) i0 = 0;
  if (i1 >= SQ) i1 = (i0 == 0) ? 1 : 0;
  if (tid < 320) {
    const int row = tid < 160 ? i0 : i1;
    const uint2 u = __ldg((const uint2*)(p.x + (size_t)row * DM) + tid % 160);
    const uint4 st = stat2(row >> 1);
    const uint32_t mean2 = row & 1 ? st.z : st.x, d0 = hsub2(u.x, mean2), d1 = hsub2(u.y, mean2);
    const float inv = __uint_as_float(row & 1 ? st.w : st.y);
    ((float4*)s_x)[tid] = make_float4(rbf(bf_lo(d0) * inv), rbf(bf_hi(d0) * inv), rbf(bf_lo(d1) * inv), rbf(bf_hi(d1) * inv));
  }
  __syncthreads();
  gemv(160, s_x + ks * 160, s_x + DM + ks * 160, s_red + ks * 1536 + cg * 8);
  __syncthreads();
#pragma unroll
  for (int t = 0; t < 2; t++) {
    float g = 0.f, u = 0.f;
#pragma unroll
    for (int k = 0; k < 4; k++) { g += s_red[(k * 2 + t) * 768 + tid]; u += s_red[(k * 2 + t) * 768 + 384 + tid]; }
    s_h[t * 384 + tid] = rbf(rbf(silu_f(rbf(g))) * rbf(u));
  }
  __syncthreads();
  if (tid < 320) gemv(96, s_h + kd * 96, s_h + 384 + kd * 96, s_red + kd * 1536 + cd * 8);
  __syncthreads();
  const int o4 = tid + (tid < 160 ? 0 : 32);
  if (tid < 320) {
    const float4 *r = (const float4*)s_red + o4, a = r[0], b = r[384], c = r[768], d = r[1152];
    ((float4*)p.s->ffn)[sc * 320 + tid] = make_float4(a.x + b.x + c.x + d.x, a.y + b.y + c.y + d.y, a.z + b.z + c.z + d.z, a.w + b.w + c.w + d.w);
  }
  __syncthreads();
  if (tid == 0) { __threadfence(); s_c[0].x = (atomicAdd(&p.s->flag[FL_SIDE], 1u) & 3u) == 3u; __threadfence(); }
  __syncthreads();
  if (s_c[0].x) {
    if (tid < 320) {
      const float4 *r = (const float4*)p.s->ffn + tid, a = __ldcg(r), b = __ldcg(r + 320), c = __ldcg(r + 640), d = __ldcg(r + 960), x = ((float4*)s_x)[tid];
      const float rs = rbf(sigmoid_f(tid < 160 ? v0 : v1));
      auto gate = [&](float xn, float y) { return silu_f(rbf(xn + rbf(rbf(y) * rs))); };
      if (tid == 0) { p.s->sel[0] = i0; p.s->sel[1] = i1; }
      ((uint2*)p.s->gsel)[tid] =
          make_uint2(pack_bf16(gate(x.x, a.x + b.x + c.x + d.x), gate(x.y, a.y + b.y + c.y + d.y)), pack_bf16(gate(x.z, a.z + b.z + c.z + d.z), gate(x.w, a.w + b.w + c.w + d.w)));
    }
    __syncthreads();
    if (tid == 0) red_release(&p.s->flag[FL_FFN]);
  }
}

constexpr float SM_C = 0.07216878364870322f * 1.4426950408889634f;

constexpr int LD = 0, LS = 3;
__device__ __forceinline__ void ln_piece(const Params& p, uint32_t (&r)[48], int k, int row, int l16) {
  auto f = [&](int i) { return __uint_as_float(r[i]); };
  if (k == LD) {
#pragma unroll
    for (int i = 0; i < 5; i++) {
      const uint4 v = ldg_nc((const uint4*)(p.x + (size_t)row * DM) + i * 16 + l16);
      r[4 * i] = v.x; r[4 * i + 1] = v.y; r[4 * i + 2] = v.z; r[4 * i + 3] = v.w;
    }
    asm volatile("ld.relaxed.gpu.global.v2.u32 {%0,%1}, [%2];" : "=r"(r[20]), "=r"(r[21]) : "l"(&p.s->done));
  } else if (k == LS || k == LS + 1) {
    if (k == LS) { r[22] = __shfl_sync(~0u, r[0], 0, 16) << 16; r[23] = r[24] = 0; }
    float s0 = f(23), s1 = 0.f, q0 = f(24), q1 = 0.f;
#pragma unroll
    for (int i = 10 * (k - LS); i < 10 * (k - LS) + 10; i++) {
      const float a = bf_lo(r[i]) - f(22), b = bf_hi(r[i]) - f(22);
      s0 += a; s1 += b; q0 = fmaf(a, a, q0); q1 = fmaf(b, b, q1);
    }
    r[23] = __float_as_uint(s0 + s1); r[24] = __float_as_uint(q0 + q1);
  } else if (k == LS + 2) {
    float s0 = f(23), q0 = f(24);
#pragma unroll
    for (int o = 8; o > 0; o >>= 1) { s0 += __shfl_xor_sync(~0u, s0, o); q0 += __shfl_xor_sync(~0u, q0, o); }
    s0 *= 1.f / DM;
    const float mean = f(22) + s0, var = rbf(fmaxf(fmaf(q0, 1.f / DM, -s0 * s0), 0.f));
    float sd; asm("sqrt.approx.ftz.f32 %0, %1;" : "=f"(sd) : "f"(rbf(var + 1e-5f)));
    const float inv = rcp(rbf(sd));
    r[22] = pack_bf16(mean, mean); r[23] = __float_as_uint(inv * SM_C);
    const uint32_t tag = __funnelshift_r(r[20], r[21], 7) + 1;
    if (l16 == 0) st_pkt8(&p.s->stat[row], __byte_perm(tag, r[22], 0x7610), __float_as_uint(inv));
  } else if (k > LS + 2 && k <= LS + 5) {
#pragma unroll
    for (int j = 2 * (k - LS - 3); j < 2 * (k - LS - 3) + 2 && j < 5; j++) {
#pragma unroll
      for (int i = 4 * j; i < 4 * j + 4; i++) { const uint32_t d = hsub2(r[i], r[22]); r[i] = pack_bf16(bf_lo(d) * f(23), bf_hi(d) * f(23)); }
      *((uint4*)(p.s->xn + (size_t)row * DM) + j * 16 + l16) = make_uint4(r[4 * j], r[4 * j + 1], r[4 * j + 2], r[4 * j + 3]);
    }
  }
}

constexpr float SM_HI = 0x1p64f, SM_LO = 0x1p-64f;
__device__ __forceinline__ void exp_block(float (&s)[32], float& l0, float& l1, int from = 0, int to = 32) {
#pragma unroll
  for (int i = from; i < to; i++) { s[i] = ex2(s[i]); if (i & 2) l1 += s[i]; else l0 += s[i]; }
}
__device__ __forceinline__ float quad_sum(float v) { v += __shfl_xor_sync(~0u, v, 1); return v + __shfl_xor_sync(~0u, v, 2); }
__device__ __forceinline__ float quad_max(float v) { v = fmaxf(v, __shfl_xor_sync(~0u, v, 1)); return fmaxf(v, __shfl_xor_sync(~0u, v, 2)); }
__device__ __noinline__ void safe_head(const uint32_t* kp, const uint32_t* vp, uint4* io) {
  uint32_t fq[48];
#pragma unroll
  for (int i = 0; i < 12; i++) { const uint4 v = io[(i >> 1) * 512 + (i & 1) * 32]; fq[4 * i] = v.x; fq[4 * i + 1] = v.y; fq[4 * i + 2] = v.z; fq[4 * i + 3] = v.w; }
  float m0 = -INFINITY, m1 = -INFINITY;
#pragma unroll 1
  for (int pass = 0; pass < 3; pass++) {
    float o[48] = {}, l0 = 0.f, l1 = 0.f;
#pragma unroll 1
    for (int n = 0; n < 64; n++) {
      const uint32_t *kr = kp + n * (8 * DH / 2), *vr = vp + n * (8 * DH / 2) + (pass - 1) * 48;
      float d[4] = {};
#pragma unroll
      for (int t = 0; t < 12; t++)
        asm volatile("mma.sync.aligned.m16n8k16.row.col.f32.bf16.bf16.f32 {%0,%1,%2,%3}, {%4,%5,%6,%7}, {%8,%9}, {%0,%1,%2,%3};"
                     : "+f"(d[0]), "+f"(d[1]), "+f"(d[2]), "+f"(d[3])
                     : "r"(fq[4 * t]), "r"(fq[4 * t + 1]), "r"(fq[4 * t + 2]), "r"(fq[4 * t + 3]), "r"(__ldg(kr + 8 * t)), "r"(__ldg(kr + 8 * t + 4)));
      if (pass == 0) { m0 = fmaxf(m0, fmaxf(d[0], d[1])); m1 = fmaxf(m1, fmaxf(d[2], d[3])); continue; }
      d[0] = ex2(d[0] - m0); d[1] = ex2(d[1] - m0); d[2] = ex2(d[2] - m1); d[3] = ex2(d[3] - m1);
      l0 += d[0] + d[1]; l1 += d[2] + d[3];
      const uint32_t p0 = pack_bf16(d[0], d[1]), p1 = pack_bf16(d[2], d[3]);
#pragma unroll
      for (int c = 0; c < 12; c++)
        asm volatile("{\n.reg .b32 t;\nmovmatrix.sync.aligned.m8n8.trans.b16 t, %6;\n"
                     "mma.sync.aligned.m16n8k8.row.col.f32.bf16.bf16.f32 {%0,%1,%2,%3}, {%4,%5}, {t}, {%0,%1,%2,%3};\n}\n"
                     : "+f"(o[4 * c]), "+f"(o[4 * c + 1]), "+f"(o[4 * c + 2]), "+f"(o[4 * c + 3]) : "r"(p0), "r"(p1), "r"(__ldg(vr + 4 * c)));
    }
    if (pass == 0) { m0 = quad_max(m0); m1 = quad_max(m1); continue; }
    l0 = rcp(quad_sum(l0)); l1 = rcp(quad_sum(l1));
#pragma unroll
    for (int i = 0; i < 6; i++) {
      const float* v = o + 16 * (i >> 1) + 2 * (i & 1);
      const float r = i & 1 ? l1 : l0;
      io[(3 * (pass - 1) + (i >> 1)) * 512 + (i & 1) * 32] =
          make_uint4(pack_bf16(v[0] * r, v[1] * r), pack_bf16(v[4] * r, v[5] * r), pack_bf16(v[8] * r, v[9] * r), pack_bf16(v[12] * r, v[13] * r));
    }
  }
}

__device__ __forceinline__ constexpr int end_stage(int n) { return n < 4 ? n : n < 6 ? n - 4 : n == 6 ? 4 : n % 5; }
__device__ __forceinline__ constexpr int sent(int n) { return n < 8 ? 0 : n < 9 ? 3 : n < 11 ? 5 : n < 13 ? 8 : n < 16 ? 10 : n < 17 ? 14 : 15; }
template <int N> struct IntC { static constexpr int value = N; };
template <int N, int I = 0, class F> __device__ __forceinline__ void static_for(F&& f) { if constexpr (I < N) { f(IntC<I>{}); static_for<N, I + 1>(f); } }

extern __shared__ __align__(1024) uint8_t smem_raw[];
constexpr uint32_t EA = 160, EB = 184;
#define SMEM_LAYOUT                                                                                                          \
  [[maybe_unused]] const uint32_t sb = smem_u32(smem_raw), bar_a = sb + OFF_M, bar_b = bar_a + 40, bar_x = bar_a + 88,      \
      bar_u = bar_a + 96, bar_e = bar_a + 104, bar_o = bar_a + 200, bar_w = bar_a + 208, bar_c = bar_a + 216,                \
      bar_z = bar_a + 288, bar_s = bar_a + 296, bar_d = bar_a + 304, s_stat = bar_a + 512, s_sel = s_stat + 1024;

__device__ __forceinline__ int cluster_role() {
  uint32_t t, n;
  asm("mov.u32 %0, %%smid;" : "=r"(t)); asm("mov.u32 %0, %%nsmid;" : "=r"(n));
  t >>= 1;
  return n != 132 ? blockIdx.x >> 1 : t < 32 ? t : t < 60 ? t + 1 + (((t - 32) * 37) >> 8) : t < 62 ? t + 4 : (t - 58) * 8;
}

__device__ __forceinline__ int k_block(int t, int hg) {
  const int i = (t * 11) >> 5;
  return ((i < 6 ? (hg & 6) + (i & 1) : hg ^ (i & 1)) * 4 + (i >> 1)) * 6 + (t == 3 * i ? 4 : 2 * (t - 3 * i) - 2);
}

__device__ __noinline__ int errands(Scratch* s, const Maps& m, int qt, int hg, int warp, uint32_t tag, int budget) {
  SMEM_LAYOUT
  const int lane = threadIdx.x & 31, kq = hg >> 1, nh = hg & 1;
  if (warp == 1) {
#pragma unroll 1
    for (int u = 0; u < 5; u++) {
      mbar_wait(bar_o, u & 1);
      if (lane == 0) red_release(&s->flag[u ? FL_O + (qt * 8 + hg) * 8 : FL_XN + qt * 32]);
      __syncwarp();
    }
  } else if (warp == 2) {
    mbar_wait(bar_x, 0, budget);
    while ((int)(ld_acquire(&s->flag[FL_FFN]) - tag) < 0 && --budget >= 0) {}
    if (lane < 21) {
      const uint4 v = __ldcg(lane ? (const uint4*)(s->gsel + (lane > 10 ? DM - 80 : 0) + nh * 320 + kq * 80) + lane - 1 : (const uint4*)s->sel);
      asm volatile("st.shared.v4.u32 [%0], {%1,%2,%3,%4};" ::"r"(s_sel + 16 * lane), "r"(v.x), "r"(v.y), "r"(v.z), "r"(v.w) : "memory");
    }
    __syncwarp();
    if (lane == 0) { mbar_arrive(bar_u); asm volatile("red.relaxed.gpu.global.add.u64 [%0], 1;" ::"l"(&s->done) : "memory"); }
    while ((int)(ld_acquire(&s->flag[FL_RD + (qt * 8 + (hg ^ 1)) * 8]) - tag) < 0 && --budget >= 0) {}
    if (lane < 3) mbar_arrive(bar_z);
  } else {
    wait_flag(&s->flag[FL_XN + qt * 32], tag * 8);
    fence_proxy_async();
    mbar_wait(bar_a + EA + 32, 1);
    uint32_t a8 = 0, pha = 1;
    const int kb = (qt * 192 + k_block(lane, hg)) * 512;
#pragma unroll 1
    for (int n = 0; n < 54; n++) {
      const int t = n - 30, ko = __shfl_sync(~0u, kb, t);
      if (t == 0 || t == 18) {
        wait_flag(&s->flag[FL_O + (qt * 8 + (t ? 2 * kq + (lane & 1) : lane & 7)) * 8], tag * 4 - (t ? 0 : 1));
        fence_proxy_async();
      }
      mbar_wait(bar_a + EA + a8, pha);
      const uint32_t fb = bar_a + a8, dst = sb + a8 * (TA >> 3);
      if (elect()) {
        if (t >= 0) {
          mbar_expect_tx(fb, TA);
          bulk_load(dst, s->o + ko, TA, fb);
          if (t == 8) {
            mbar_expect_tx(bar_x, 6 * 3840);
#pragma unroll 1
            for (int e = 0; e < 6; e++) tma2d(sb + OFF_B + TW + e * TB, &m.xg, nh * 320 + kq * 80, qt * 128 + e * 24, bar_x);
            asm volatile("prefetch.tensormap [%0];\nprefetch.tensormap [%1];\nprefetch.tensormap [%2];\nprefetch.tensormap [%3];"
                         ::"l"(m.w3), "l"(m.w3 + 1), "l"(&m.xe), "l"(&m.out) : "memory");
          }
          if (t == 22) asm volatile("red.relaxed.gpu.global.add.u32 [%0], 1;" ::"l"(&s->flag[FL_RD + (qt * 8 + hg) * 8]) : "memory");
        } else if (n >= 10 && pha) mbar_arrive(fb);
        else { mbar_expect_tx(fb, TA); tma2d(dst, &m.xn, 8 * a8 + (pha || (n >= 15 && n < 20) ? 0 : 320), qt * 128, fb); }
      }
      a8 += 8; if (a8 == 40) { a8 = 0; pha ^= 1; }
    }
    if (lane < 3) mbar_arrive(bar_z);
  }
  return budget;
}

__global__ void __launch_bounds__(384, 1) __cluster_dims__(2, 1, 1)
fused_kernel(const Params p, const __grid_constant__ Maps m) {
  SMEM_LAYOUT
  const int wi = __shfl_sync(~0u, threadIdx.x >> 5, 0), wg = wi >> 2;
  const int lane = threadIdx.x & 31;
  const int cl = cluster_role();
  const int rank = blockIdx.x & 1;

  if (cl >= 64) {
    const unsigned epoch = (unsigned)(__ldcg(&p.s->done) >> 7);
    side_cta(p, 2 * cl + rank - 128, epoch, (float*)smem_raw);
    return;
  }
  const int qt = (cl & 7) * 2 + rank, hg = cl >> 3;
  const int kq = hg >> 1, nh = hg & 1;

  const int s0 = qt < 8 ? 0 : 5, kg0 = 10 * ((qt >> 1) & 3);
  if (elect()) {
    const int c = (int)(0x5ff7700000ull >> (4 * wi) & 15) + 1;
    for (int i = 0; i < 4; i++) mbar_init(bar_a + 32 * wi + 8 * i, c);
    asm volatile("fence.mbarrier_init.release.cluster;" ::: "memory");
  }
  __syncwarp();
  cluster_arrive();
  if (wi < 2 && elect()) {
    if (wi) { asm volatile("prefetch.tensormap [%0];" ::"l"(&m.wq) : "memory"); mbar_expect_tx(bar_b, TB); mbar_expect_tx(bar_b + 8, TB); }
    else for (int i = 0; i < 2; i++) { mbar_expect_tx(bar_a + 8 * i, TA); tma2d(sb + i * TA, &m.x, 64 * (s0 + i), qt * 128, bar_a + 8 * i); }
  }
  __syncwarp();
  cluster_wait();
  if (wi == 1 && elect())
    for (int i = 0; i < 2; i++) tma4d_mc(sb + OFF_B + i * TB + rank * (TB / 2), &m.wq, 12 * hg, 8 * (s0 + i) + 4 * rank, bar_b + 8 * i);
  if (wg > 0) {
    const int w = wg - 1;
    const int cw = wi - 4;
    asm volatile("setmaxnreg.inc.sync.aligned.u32 232;");
    uint32_t fr[48];
    reg_fence(fr);
    auto ln_row = [&]() { int v = qt * 128 + hg * 16 + cw * 2 + (lane >> 4); asm volatile("" : "+r"(v)); return v; };
    uint32_t rel_addr;
    asm volatile("mapa.shared::cluster.u32 %0, %1, %2;" : "=r"(rel_addr) : "r"(bar_b + EB), "r"(lane & 1));
    auto rel_a = [&](uint32_t o8) { if (lane == 0) mbar_arrive(bar_a + EA + o8); };
    auto rel_b = [&](uint32_t o8) { if (lane < 2) mbar_arrive_cluster(rel_addr + o8); };
    uint32_t b8 = 0, phb = 0;
    auto next_pair = [&]() { b8 += 16; if (b8 == 48) { b8 = 0; phb ^= 1; } };
    const int g = lane >> 2, q = lane & 3;
    constexpr uint64_t HI_A = desc_hi(16, 1024, 1);
    constexpr uint64_t HI_W = desc_hi(1024, 3072, 1);
    constexpr uint64_t HI_O = desc_hi(2048, 512, 2);
    if (w == 1) asm volatile("bar.arrive 1, 256;" ::: "memory");

    uint32_t zero; asm volatile("mov.u32 %0, %%tid.y;" : "=r"(zero));
    float acc[96];
    uint4* optr = p.s->o + (size_t)(qt * 192 + hg * 24) * 512 + (cw * 16 + g) * 4 + (q ^ ((g >> 1) & 3));
    uint32_t rl[4];
    auto store_o = [&](int pp) {
#pragma unroll
      for (int i = (12 * pp + 8) / 9; i < (12 * (pp + 1) + 8) / 9; i++) {
#pragma unroll
        for (int k = 4 * i; k < 4 * i + 4; k++)
          asm volatile("{\n.reg .b32 t;\nmul.rn.bf16x2 t, %0, %2;\nfma.rn.bf16x2 %0, %0, %1, t;\n}\n" : "+r"(fr[k]) : "r"(rl[i & 1]), "r"(rl[2 + (i & 1)]));
        fr[4 * i] &= ~1u;
        optr[(i >> 1) * 512 + (i & 1) * 32] = make_uint4(fr[4 * i], fr[4 * i + 1], fr[4 * i + 2], fr[4 * i + 3]);
      }
      if (pp == 8) optr += 6 * 512;
    };
    auto fresh = [&]() { uint32_t v = sb; asm volatile("" : "+r"(v)); return v; };
    reg_fence(rl);

#pragma unroll 1
    for (int u = 0; u < 4; u++) {
      const uint32_t sq = fresh();
      const uint64_t dA = mkdesc(sq + w * 8192, HI_A), dB0 = mkdesc(sq + OFF_B, HI_W);
      uint32_t pb8 = 0;
#pragma unroll
      for (int s = 0; s < 10; s++) {
        const uint32_t o8 = b8 + 8 * (s & 1);
        const uint64_t dW = dB0 + o8 * (TB >> 7);
        mbar_wait(bar_a + 8 * (s % 5), s / 5);
        mbar_wait(bar_b + o8, phb);
        if (s == 9 || (s >= LS && u == 0)) asm volatile("bar.sync %0, 256;" ::"r"(1 + w) : "memory");
        WG_FENCE();
#pragma unroll
        for (int kk = 0; kk < 4; kk++) wg_ss192t(acc, dA + ((s % 5) * (TA >> 4) + kk * 2), dW + kk * 384, kk != 0 || s != 0);
        WG_COMMIT();
        if (s >= LS && (s == 9) == (u > 0)) asm volatile("bar.arrive %0, 256;" ::"r"(2 - w) : "memory");
        if (s > 0) { WG_WAIT(1); rel_a(8 * ((s - 1) % 5)); rel_b(pb8); }
        if (s < 9) {
          if (u > 0) store_o(s);
          else { if (s == 6 && lane == 0) mbar_arrive(bar_c); ln_piece(p, fr, s, ln_row(), lane & 15); }
        }
        if (s == 8) { __syncwarp(); if (lane == 0) mbar_arrive(bar_o); }
        pb8 = o8;
        if (s & 1) next_pair();
      }
      if (u == 0) {
        mbar_wait(bar_s, 0);
        const uint2 s0 = lds64(s_stat + (cw * 16 + g) * 8), s1 = lds64(s_stat + 64 + (cw * 16 + g) * 8);
        const uint32_t msk = q == 0 ? 0xffffffffu : q == 1 ? 0xffffu : 0u;
        const float c0 = SM_C * __uint_as_float(s0.y), c1 = SM_C * __uint_as_float(s1.y);
        uint32_t am[4] = {(s0.x ^ 0x80008000u) & msk, (s1.x ^ 0x80008000u) & msk, 0, 0};
        reg_fence(am);
        WG_FENCE();
        wg_rs192t(acc, am[0], am[1], am[2], am[3], mkdesc(sb, desc_hi(1024, 0, 1)), 1);
        WG_COMMIT();
        asm volatile("bar.arrive %0, 256;" ::"r"(2 - w) : "memory");
        WG_WAIT(0);
        reg_fence(acc);
#pragma unroll
        for (int i = 0; i < 24; i++) { acc[4 * i] *= c0; acc[4 * i + 1] *= c0; acc[4 * i + 2] *= c1; acc[4 * i + 3] *= c1; }
      } else { WG_WAIT(0); reg_fence(acc); }
      rel_b(pb8);
      rel_a(32);
#pragma unroll
      for (int i = 0; i < 48; i++) fr[i] = pack_bf16(acc[2 * i], acc[2 * i + 1]);
      reg_fence(fr);
      float sc[32], l0 = 0.f, l1 = 0.f;
      uint32_t pf[16], k8;
      auto pack_p = [&](const float (&s_)[32], int from = 0, int to = 16) {
#pragma unroll
        for (int i = from; i < to; i++) pf[i] = pack_bf16(s_[2 * i], s_[2 * i + 1]);
      };
      auto scores = [&](int j, int pass = 11) {
        k8 = b8 + 8;
        mbar_wait(bar_b + k8, phb);
        next_pair();
        mbar_wait(bar_b + b8, phb);
        const uint64_t dk = mkdesc(sb + OFF_B, HI_W) + k8 * (TB >> 7);
        asm volatile("bar.sync %0, 256;" ::"r"(1 + w) : "memory");
        WG_FENCE();
#pragma unroll
        for (int t = 0; t < 12; t++) {
          wg_rs64(sc, fr[4 * t], fr[4 * t + 1], fr[4 * t + 2], fr[4 * t + 3], dk + (t >> 2) * 64 + (t & 3) * 2, t != 0);
          if (t == 11) WG_COMMIT();
          if (t == pass) asm volatile("bar.arrive %0, 256;" ::"r"(2 - w) : "memory");
        }
      };
      auto pv = [&](int add) {
        const uint64_t dv = mkdesc(sb + OFF_B, HI_W) + b8 * (TB >> 7);
#pragma unroll
        for (int kk = 0; kk < 4; kk++) wg_rs192t(acc, pf[4 * kk], pf[4 * kk + 1], pf[4 * kk + 2], pf[4 * kk + 3], dv + kk * 384, kk != 0 || add);
        WG_COMMIT();
      };
      auto finish = [&]() {
        WG_WAIT(1);
        reg_fence(sc);
        exp_block(sc, l0, l1);
        rel_b(k8 + (__float_as_uint(l0) & __float_as_uint(l1) & zero));
        WG_WAIT(0);
        reg_fence(acc); reg_fence(pf);
        rel_b(b8);
        pack_p(sc);
      };
      {
        mbar_wait(bar_b + b8, phb);
        const uint64_t dk = mkdesc(sb + OFF_B, HI_W) + b8 * (TB >> 7);
        asm volatile("bar.sync %0, 256;" ::"r"(1 + w) : "memory");
#pragma unroll
        for (int t = 0; t < 12; t++) {
          if (t == 0) WG_FENCE();
          wg_rs64(sc, fr[4 * t], fr[4 * t + 1], fr[4 * t + 2], fr[4 * t + 3], dk + (t >> 2) * 64 + (t & 3) * 2, t != 0);
          if (t == 7) asm volatile("bar.arrive %0, 256;" ::"r"(2 - w) : "memory");
        }
        WG_COMMIT();
        WG_WAIT(0);
        reg_fence(sc);
        constexpr int NE = 8;
        float s0[32];
#pragma unroll
        for (int i = 0; i < 32; i++) s0[i] = i < NE ? sc[i] : __uint_as_float(__float_as_uint(sc[i]) ^ zero);
        exp_block(s0, l0, l1, 0, NE);
        pack_p(s0, 0, NE / 2);
#pragma unroll
        for (int i = NE; i < 32; i++) asm volatile("" : "+f"(s0[i])::"memory");
#pragma unroll
        for (int i = 0; i < NE / 2; i++) asm volatile("" : "+r"(pf[i])::"memory");
        rel_b(b8);
        scores(1, 8);
        const uint32_t z = lds32(s_stat) & zero;
#pragma unroll
        for (int i = NE; i < 32; i++) {
          asm("{\n.reg .pred p;\nsetp.eq.u32 p, %1, 0;\n@p ex2.approx.ftz.f32 %0, %0;\n}\n" : "+f"(s0[i]) : "r"(z));
          if (i & 2) l1 += s0[i]; else l0 += s0[i];
        }
        pack_p(s0, NE / 2, 16);
        reg_fence(pf);
        WG_FENCE();
        pv(0);
        finish();
      }
#pragma unroll 1
      for (int j = 2; j < 8; j++) { scores(j); pv(1); finish(); }
      const uint32_t v8 = b8 + 8;
      mbar_wait(bar_b + v8, phb);
      next_pair();
      {
        const uint64_t dv = mkdesc(sb + OFF_B, HI_W) + v8 * (TB >> 7);
        asm volatile("bar.sync %0, 256;" ::"r"(1 + w) : "memory");
        WG_FENCE();
#pragma unroll
        for (int kk = 0; kk < 4; kk++) {
          wg_rs192t(acc, pf[4 * kk], pf[4 * kk + 1], pf[4 * kk + 2], pf[4 * kk + 3], dv + kk * 384, 1);
          if (kk == 1 && (u < 3 || w == 0)) asm volatile("bar.arrive %0, 256;" ::"r"(2 - w) : "memory");
        }
        WG_COMMIT();
      }
      l0 = quad_sum(l0); l1 = quad_sum(l1);
      const bool unsafe = __any_sync(~0u, !(l0 >= SM_LO && l1 >= SM_LO && l0 + l1 <= SM_HI));
      l0 = rcp(l0); l1 = rcp(l1);
      rl[0] = pack_bf16(l0, l0); rl[1] = pack_bf16(l1, l1);
      l0 -= bf_lo(rl[0]); l1 -= bf_lo(rl[1]);
      rl[2] = pack_bf16(l0, l0); rl[3] = pack_bf16(l1, l1);
      WG_WAIT(0);
      reg_fence(acc);
      rel_b(v8);
      if (__builtin_expect(unsafe, 0)) {
        int o = hg * 4 + u; asm volatile("" : "+r"(o));
        o = (o * SKC + (SKC - WIN) + g) * (DH / 2) + q;
#pragma unroll
        for (int i = 0; i < 12; i++) optr[(i >> 1) * 512 + (i & 1) * 32] = make_uint4(fr[4 * i], fr[4 * i + 1], fr[4 * i + 2], fr[4 * i + 3]);
        safe_head((const uint32_t*)p.k + o, (const uint32_t*)p.v + o, optr);
#pragma unroll
        for (int i = 0; i < 12; i++) { const uint4 v = optr[(i >> 1) * 512 + (i & 1) * 32]; fr[4 * i] = v.x; fr[4 * i + 1] = v.y; fr[4 * i + 2] = v.z; fr[4 * i + 3] = v.w; }
        rl[0] = rl[1] = 0x3f803f80u; rl[2] = rl[3] = 0;
      } else {
#pragma unroll
        for (int i = 0; i < 24; i++) {
          fr[8 * (i >> 2) + (i & 3)] = pack_bf16(acc[4 * i], acc[4 * i + 1]);
          fr[8 * (i >> 2) + 4 + (i & 3)] = pack_bf16(acc[4 * i + 2], acc[4 * i + 3]);
        }
      }
    }

    float aF[80], aS[80];
    uint32_t pha = 0, a8 = 0, pa8 = 0, pb8 = 0;
#pragma unroll 1
    for (int s = 0; s < 19; s++) {
      const uint64_t d0 = mkdesc(sb, HI_O), dO = d0 + (a8 * (TA >> 7) + w * 256), dB = d0 + ((OFF_B >> 4) + b8 * (TB >> 7));
      mbar_wait(bar_a + a8, pha);
      mbar_wait(bar_b + b8, phb);
      WG_FENCE();
#pragma unroll
      for (int kk = 0; kk < 4; kk++) wg_ss160t(aF, dO + ((kk >> 1) * 512 + (kk & 1) * 2), dB + ((kk >> 1) * 640 + (kk & 1) * 64), kk != 0 || s != 0);
      WG_COMMIT();
      mbar_wait(bar_b + b8 + 8, phb);
      WG_WAIT(1);
      if (s > 0) { rel_a(pa8); rel_b(pb8 + 8); }
      WG_FENCE();
#pragma unroll
      for (int kk = 0; kk < 4; kk++) wg_ss160t(aS, dO + ((kk >> 1) * 512 + (kk & 1) * 2), dB + ((TB >> 4) + (kk >> 1) * 640 + (kk & 1) * 64), kk != 0 || s != 0);
      WG_COMMIT();
      if (s < 9) {
#pragma unroll
        for (int pp = 0; pp < 9; pp++) if (s == pp) store_o(pp);
        if (s == 8) { __syncwarp(); if (lane == 0) mbar_arrive(bar_o); }
      } else if (s < 15) {
        const int b = 2 * cw + ((lane >> 3) & 1);
        uint32_t ga = sb + OFF_B + TW + ((b * 11) >> 5) * (TB - 3840) + b * 1280 + (lane & 7) * 160 + (lane >> 4) * 16;
        if (s < 14) {
          mbar_wait(bar_x, 0);
          ga += 32 * (s - 9);
          ldsm4(ga, fr);
#pragma unroll
          for (int i = 0; i < 4; i++) {
            const uint2 st = lds64(s_stat + (cw * 16 + g + 8 * (i & 1)) * 8);
            const uint32_t d = hsub2(fr[i], st.x), xn = pack_bf16(bf_lo(d) * __uint_as_float(st.y), bf_hi(d) * __uint_as_float(st.y));
            fr[i] = pack_bf16(silu_f(bf_lo(xn)), silu_f(bf_hi(xn)));
          }
          stsm4(ga, fr);
        } else {
          mbar_wait(bar_u, 0);
          const uint2 sel = lds64(s_sel);
          const uint32_t row = qt * 128 + cw * 16 + (lane & 15);
          if (row == sel.x || row == sel.y) ga = s_sel + 16 + (row == sel.y ? 160 : 0) + (lane >> 4) * 16;
#pragma unroll
          for (int k = 0; k < 5; k++) ldsm4(ga + 32 * k, fr + 4 * k);
        }
      }
      WG_WAIT(1);
      rel_b(b8);
      pa8 = a8; a8 += 8; if (a8 == 40) { a8 = 0; pha ^= 1; }
      pb8 = b8; next_pair();
    }
    const int t128 = threadIdx.x & 127;
    uint4* const xbase = p.s->o + (size_t)(qt * 192 + nh * 24 + 10) * 512 + w * 640 + t128;
    uint4* const dst = xbase + kq * (48 * 512);
    float q1[40], q2[40], oth[40], own[40];
    auto take = [&](float (&x)[40], const float* a) {
#pragma unroll
      for (int k = 0; k < 40; k++) x[k] = __uint_as_float(__float_as_uint(a[k]) ^ zero);
      reg_fence(x);
    };
    reg_fence(aF);
    take(q1, aF);
    auto fa = [&](int i) { return mbar_try(bar_a + 8 * ((4 + i) % 5), i == 0); };
    auto fb = [&](int e) { return mbar_try(bar_b + 8 * (e % 6), (e / 6) & 1); };
    auto send = [&](int m) {
      const float* v = (m < 5 ? q1 : m < 10 ? q2 : oth) + 8 * (m % 5);
      st_pkt(dst + (m / 5) * 1280 + (m % 5) * 128, pack_bf16(v[0], v[1]) | 1, pack_bf16(v[2], v[3]), pack_bf16(v[4], v[5]), pack_bf16(v[6], v[7]));
    };
    static_for<20>([&](auto n_) {
      constexpr int n = n_.value, i = end_stage(n), e = 142 + n / 2, qi = n == 4 ? 1 : n == 6 ? 0 : n / 5;
      float (&acc_)[40] = qi == 0 ? q1 : qi == 1 ? q2 : qi == 2 ? oth : own;
      if (n == 0) while (!(fa(0) & fa(1) & fb(142) & fb(143))) {}
      if (n == 2) while (!(fa(2) & fa(3) & fb(144))) {}
      if (n == 6) while (!(fa(4) & fb(145) & fb(146) & mbar_try(bar_z, 0))) {}
      if (n == 10) while (!(fb(147) & fb(148) & fb(149))) {}
      const uint64_t d0 = mkdesc(fresh(), HI_O), dw = d0 + w * 256;
      WG_FENCE();
#pragma unroll
      for (int kk = 0; kk < 4; kk++)
        wg_ss80t(acc_, dw + (((4 + i) % 5) * (TA >> 4) + (kk >> 1) * 512 + (kk & 1) * 2),
                 d0 + ((OFF_B >> 4) + (e % 6) * (TB >> 4) + (n & 1) * 768 + (kk >> 1) * 384 + (kk & 1) * 64), 1);
      WG_COMMIT();
      if ((!(n & 1) && n <= 16) || n == 15 || n == 7) WG_WAIT(1);
      if (n == 0) rel_a(24);
      if (!(n & 1) && n <= 8) rel_b(8 * ((e - 1) % 6));
      if (n == 1) take(q2, aF + 40);
      if (n == 10 || n == 12 || n == 14 || n == 16) rel_a(4u * n - 40);
      if (n == 7) reg_fence(q1);
      if (n == 10) reg_fence(q2);
      if (n == 15) reg_fence(oth);
      if (n == 14 || n == 17) while (!fb(n == 14 ? 150 : 151)) {}
      static_for<sent(n + 1) - sent(n)>([&](auto k_) { send(sent(n) + k_.value); });
      if (n == 8) {
        reg_fence(aS);
#pragma unroll
        for (int k = 0; k < 40; k++) oth[k] = kq & 1 ? aS[k] : aS[40 + k];
        reg_fence(oth);
      }
      if (n == 12) {
        reg_fence(aS);
#pragma unroll
        for (int k = 0; k < 40; k++) own[k] = kq & 1 ? aS[40 + k] : aS[k];
        reg_fence(own);
      }
    });
    {
      auto poll = [&](int e, uint4 (&v)[5]) {
#pragma unroll
        for (int i = 0; i < 5; i++) v[i] = ld_pkt(xbase + (kq ^ (e < 2 ? 2 + e : 1)) * (48 * 512) + (e < 2 ? kq & 1 : 2) * 1280 + i * 128);
      };
      auto check = [&](int e, uint4 (&v)[5]) {
        auto tags = [&]() { uint32_t t; asm("{\n.reg .b32 t;\nlop3.b32 t, %1, %2, %3, 0x80;\nlop3.b32 %0, t, %4, %5, 0x80;\n}\n" : "=r"(t) : "r"(v[0].x), "r"(v[1].x), "r"(v[2].x), "r"(v[3].x), "r"(v[4].x)); return t & 1; };
        while (!__all_sync(~0u, tags())) poll(e, v);
      };
      auto add = [&](const uint4 (&v)[5]) {
#pragma unroll
        for (int i = 0; i < 5; i++) {
          float* o = own + 8 * i;
          o[0] += bf_lo(v[i].x); o[1] += bf_hi(v[i].x); o[2] += bf_lo(v[i].y); o[3] += bf_hi(v[i].y);
          o[4] += bf_lo(v[i].z); o[5] += bf_hi(v[i].z); o[6] += bf_lo(v[i].w); o[7] += bf_hi(v[i].w);
        }
      };
      uint4 v[2][5];
#pragma unroll
      for (int e = 0; e < 2; e++) {
        mbar_wait(bar_e + 16 * e + 8 * w, 0);
#pragma unroll
        for (int i = 0; i < 5; i++) v[e][i] = lds128(sb + OFF_B + (2 + e) * TB + (w * 640 + i * 128 + t128) * 16);
      }
      check(0, v[0]); check(1, v[1]);
#pragma unroll
      for (int i = 0; i < 5; i++) v[0][i] = make_uint4(hadd2(v[0][i].x, v[1][i].x), hadd2(v[0][i].y, v[1][i].y), hadd2(v[0][i].z, v[1][i].z), hadd2(v[0][i].w, v[1][i].w));
      uint32_t xr[20];
      const uint32_t xs = sb + OFF_B + 4 * TB + cw * 2560, xa = xs + (lane & 15) * 160 + (lane >> 4) * 16;
      mbar_wait(bar_e + 32, 0);
#pragma unroll
      for (int k = 0; k < 5; k++) ldsm4(xa + 32 * k, xr + 4 * k);
      WG_WAIT(0);
      reg_fence(own);
      poll(2, v[1]);
      add(v[0]);
      reg_fence(own);
      check(2, v[1]); add(v[1]);
      if (lane == 0) mbar_arrive(bar_w);
      cluster_arrive();
#pragma unroll
      for (int i = 0; i < 20; i++) xr[i] = hadd2(xr[i], hmul2(pack_bf16(own[2 * i], own[2 * i + 1]), fr[i]));
#pragma unroll
      for (int k = 0; k < 5; k++) stsm4(xa + 32 * k, xr + 4 * k);
      asm volatile("fence.proxy.async.shared::cta;" ::: "memory");
      __syncwarp();
      if (elect()) {
        tma2d_store(&m.out, xs, nh * 320 + kq * 80, qt * 128 + cw * 16);
        asm volatile("cp.async.bulk.commit_group;\ncp.async.bulk.wait_group.read 0;" ::: "memory");
      }
      __syncwarp();
    }
    cluster_wait();
  } else {
    asm volatile("setmaxnreg.dec.sync.aligned.u32 40;");
    uint32_t tid_; asm volatile("mov.u32 %0, %%tid.x;" : "=r"(tid_));
    const int warp = __shfl_sync(~0u, tid_ >> 5, 0);
    auto is_warp = [&](int k) { uint32_t e; asm volatile("{\n.reg .pred q;\nsetp.eq.u32 q, %1, %2;\nselp.u32 %0, 1, 0, q;\n}" : "=r"(e) : "r"(warp), "r"(k)); return e != 0; };
    if (warp > 0) {
      const unsigned epoch = (unsigned)(__ldcg(&p.s->done) >> 7);
      int budget = WAIT_BUDGET;
      const uint32_t tag = epoch + 1;
      mbar_wait(bar_b + (kg0 & ~7), 0, budget); mbar_wait(bar_b + (kg0 & ~7) + 8, 0, budget);
      float cs0 = 0.f, cs1 = 0.f;
      const int n = rank * 96 + (warp - 1) * 32;
#pragma unroll 1
      for (int kg = kg0 + (lane >> 4) * 5, e = kg + 5; kg < e; kg++) {
        const uint32_t ad = sb + OFF_B + kg * 3072 + (n >> 6) * 1024 + (n & 63) * 2 + (lane & 15) * 4;
#pragma unroll
        for (int k = 0; k < 8; k++) { const uint32_t v = lds32(ad ^ (k * 0x90)); cs0 += bf_lo(v); cs1 += bf_hi(v); }
      }
      cs0 += __shfl_xor_sync(~0u, cs0, 16); cs1 += __shfl_xor_sync(~0u, cs1, 16);
      if (lane < 16) st_pkt8((uint2*)(p.s->cs + (hg * 4 + (qt >> 2)) * 96 + (n >> 1) + lane) + ((qt >> 1) & 1), (__float_as_uint(cs0) & ~3u) | (tag & 3), __float_as_uint(cs1));
      if (lane < 2) { uint32_t a; asm volatile("mapa.shared::cluster.u32 %0, %1, %2;" : "=r"(a) : "r"(bar_d), "r"(lane)); mbar_arrive_cluster(a); }
      mbar_wait(bar_c, 0, budget);
      uint4 v[5];
      while (true) {
        uint32_t bad = 0;
#pragma unroll
        for (int i = 0; i < 5; i++) v[i] = ld_pkt(i < 4 ? p.s->cs + (hg * 4 + i) * 96 + (tid_ - 32) : (const uint4*)p.s->stat + qt * 64 + (tid_ & 63));
#pragma unroll
        for (int i = 0; i < 5; i++) bad |= (v[i].x ^ tag) | (v[i].z ^ tag);
        if (!__any_sync(~0u, bad & 3) || --budget < 0) break;
      }
      asm volatile("st.shared.v4.u32 [%0], {%1,%2,%3,%4};" ::"r"(s_stat + (tid_ & 63) * 16), "r"(__byte_perm(v[4].x, 0, 0x3232)), "r"(v[4].y), "r"(__byte_perm(v[4].z, 0, 0x3232)), "r"(v[4].w) : "memory");
      cs0 = cs1 = 0.f;
#pragma unroll
      for (int i = 0; i < 4; i++) { cs0 += __uint_as_float(v[i].x & ~3u) + __uint_as_float(v[i].z & ~3u); cs1 += __uint_as_float(v[i].y) + __uint_as_float(v[i].w); }
#pragma unroll
      for (int k = 0; k < 8; k++) {
        const uint32_t t = k < 3 ? pack_bf16(cs0, cs1) : 0;
        sts32((sb + (warp - 1) * 1024 + lane * 4) ^ (k * 0x90), t);
        cs0 -= bf_lo(t); cs1 -= bf_hi(t);
      }
      asm volatile("fence.proxy.async.shared::cta;" ::: "memory");
      __syncwarp();
      if (lane < 2) mbar_arrive(bar_s);
      budget = errands(p.s, m, qt, hg, warp, tag, budget);
      if (is_warp(2)) {
        mbar_wait(bar_w, 0, budget);
        if (budget < 0) asm volatile("st.global.u32 [%0], %1;" ::"l"(0ull), "r"(budget) : "memory");
      }
    } else {
      uint32_t fb = bar_b + 16, dst = sb + OFF_B + 2 * TB, ph = 1;
      auto next = [&]() { fb += 8; dst += TB; if (fb == bar_b + 48) { fb = bar_b; dst = sb + OFF_B; ph ^= 1; } };
#pragma unroll 1
      for (int u = 0; u < 4; u++) {
        const int h = hg * 4 + u;
        int s = u ? (u == 2 ? 5 : 0) : s0 + 2;
#pragma unroll 1
        for (int i = u ? 0 : 2; i < 10; i++) {
          if (u == 0) {
            const uint32_t a8 = 8 * (i < 5 ? i : i - 5);
            mbar_wait(bar_a + 8 * (i < 7 ? i - 2 : i - 7), i >= 7);
            mbar_wait(bar_a + EA + a8, i < 5);
            if (elect()) { mbar_expect_tx(bar_a + a8, TA); tma2d(sb + a8 * (TA >> 3), &m.x, 64 * s, qt * 128, bar_a + a8); }
            if (i == 6 + (kg0 >> 3)) mbar_wait(bar_d, 0);
          }
          mbar_wait(fb + EB, ph);
          if (elect()) { mbar_expect_tx(fb, TB); tma4d_mc(dst + rank * (TB / 2), &m.wq, 3 * h, 8 * s + 4 * rank, fb); }
          next();
          if (++s == 10) s = 0;
        }
        const int kv0 = (h * SKC + (SKC - WIN)) / 8 + 4 * rank;
#pragma unroll 1
        for (int i = 0; i < 16; i++) {
          const bool isk = (0x2AAB >> i) & 1;
          mbar_wait(fb + EB, ph);
          if (elect()) { mbar_expect_tx(fb, TB); tma4d_mc(dst + rank * (TB / 2), isk ? &m.k : &m.v, 0, kv0 + 8 * (isk ? (i + 1) >> 1 : (i - 1) >> 1), fb); }
          next();
        }
      }
      const int cF = 10 * nh + 5 - 5 * (kq >> 1), cS = 10 * nh + 5 * (kq >> 1);
      const int kb = 4 * (k_block(lane, hg) + rank);
#pragma unroll 1
      for (int n = 0; n < 38; n++) {
        const int c2 = __shfl_sync(~0u, kb, n >> 1);
        mbar_wait(fb + EB, ph);
        if (elect()) { mbar_expect_tx(fb, TW); tma5d_mc(dst + rank * (TW / 2), &m.wo, c2, n & 1 ? cS : cF, fb); }
        next();
      }
      const int odd = ((0x7fb0 ^ (kq & 1 ? 0xffc00 : 0)) >> lane) & 1;
      const int tq = __shfl_sync(~0u, kb, 19 + end_stage(lane)) << 16 | odd << 7 | ((lane < 10 ? cF : cS) + 2 * odd);
#pragma unroll 1
      for (int n = 0; n < 20; n += 2) {
        const int t0 = __shfl_sync(~0u, tq, n), t1 = __shfl_sync(~0u, tq, n + 1);
        mbar_wait(fb + EB, ph);
        if (elect()) {
          mbar_expect_tx(fb, TB);
          tma5d_mc(dst + rank * (TB / 4), (const CUtensorMap*)((const char*)m.w3 + (t0 & 128)), t0 >> 16, t0 & 31, fb);
          tma5d_mc(dst + TB / 2 + rank * (TB / 4), (const CUtensorMap*)((const char*)m.w3 + (t1 & 128)), t1 >> 16, t1 & 31, fb);
        }
        next();
      }
      mbar_wait(bar_a + EA + 16, 0);
      if (elect()) { mbar_expect_tx(bar_e + 32, TW); tma2d(sb + OFF_B + 4 * TB, &m.xe, nh * 320 + kq * 80, qt * 128, bar_e + 32); }
    }
    if (warp & 1) {
      const int e = warp >> 1, ms = 2 * e + ((lane >> 2) & 1);
      const uint4* src = p.s->o + (size_t)(qt * 192 + nh * 24 + 10 + (kq ^ (2 + e)) * 48) * 512 + (kq & 1) * 1280 + (ms & 1) * 640;
      uint32_t todo = 0xff;
      bool ok = lane >= 8;
      mbar_wait(bar_z, 0);
#pragma unroll 1
      while (todo) {
        if (!ok) ok = ld_pkt(src + 4 * 128 + (lane & 3) * 32 + 31).x & 1;
        const uint32_t got = __ballot_sync(~0u, ok) & todo, go = __ballot_sync(~0u, ((got >> (lane & 28)) & 15) == 15);
        if (go) mbar_wait(bar_a + EA + 8 * e, 0);
        if ((go & 0x11) >> lane & 1) {
          mbar_expect_tx(bar_e + 8 * ms, TW / 2); bulk_load(sb + OFF_B + (2 + e) * TB + (ms & 1) * (TW / 2), src, TW / 2, bar_e + 8 * ms);
        }
        todo &= ~go;
      }
    }
    cluster_sync();
  }
}

typedef CUresult (*EncodeFn)(CUtensorMap*, CUtensorMapDataType, cuuint32_t, void*, const cuuint64_t*, const cuuint64_t*,
                             const cuuint32_t*, const cuuint32_t*, CUtensorMapInterleave, CUtensorMapSwizzle,
                             CUtensorMapL2promotion, CUtensorMapFloatOOBfill);

void encode(EncodeFn fn, CUtensorMap* tm, void* base, int rank, const cuuint64_t* dims, const cuuint64_t* strides,
            const cuuint32_t* box, CUtensorMapSwizzle sw) {
  const cuuint32_t es[5] = {1, 1, 1, 1, 1};
  fn(tm, CU_TENSOR_MAP_DATA_TYPE_BFLOAT16, rank, base, dims, strides, box, es, CU_TENSOR_MAP_INTERLEAVE_NONE, sw,
     CU_TENSOR_MAP_L2_PROMOTION_L2_128B, CU_TENSOR_MAP_FLOAT_OOB_FILL_NONE);
}

}

extern "C" void kernel_launch(void* const* d_in, const int* in_sizes, int n_in, void* d_out, int out_size) {
  static EncodeFn fn = nullptr;
  static Scratch* scr = nullptr;
  if (!fn) {
    void* f = nullptr;
    cudaDriverEntryPointQueryResult st;
    cudaGetDriverEntryPoint("cuTensorMapEncodeTiled", &f, cudaEnableDefault, &st);
    fn = (EncodeFn)f;
    cudaGetSymbolAddress((void**)&scr, g_scratch);
    cudaFuncSetAttribute(fused_kernel, cudaFuncAttributeMaxDynamicSharedMemorySize, SMEM_BYTES);
  }
  Maps m;
  { const cuuint64_t d[2] = {DM, SQ}, s[1] = {DM * 2}; const cuuint32_t b[2] = {64, 128};
    encode(fn, &m.x, d_in[0], 2, d, s, b, CU_TENSOR_MAP_SWIZZLE_128B);
    encode(fn, &m.xn, scr->xn, 2, d, s, b, CU_TENSOR_MAP_SWIZZLE_128B); }
  { const cuuint64_t d[4] = {64, 8, QD / 64, DM / 8}, s[3] = {QD * 2, 128, 8 * QD * 2}; const cuuint32_t b[4] = {64, 8, 3, 4};
    encode(fn, &m.wq, d_in[3], 4, d, s, b, CU_TENSOR_MAP_SWIZZLE_128B); }
  { const cuuint64_t d[4] = {64, 8, 3, NH * SKC / 8}, s[3] = {DH * 2, 128, 8 * DH * 2}; const cuuint32_t b[4] = {64, 8, 3, 4};
    encode(fn, &m.k, d_in[1], 4, d, s, b, CU_TENSOR_MAP_SWIZZLE_128B);
    encode(fn, &m.v, d_in[2], 4, d, s, b, CU_TENSOR_MAP_SWIZZLE_128B); }
  {
    const cuuint64_t d[5] = {32, 2, QD / 8, 4, DM / 32}, s[4] = {DM * 2, 8 * DM * 2, 2 * DM * 2, 64}; const cuuint32_t b[5] = {32, 2, 4, 4, 5};
    encode(fn, &m.wo, d_in[4], 5, d, s, b, CU_TENSOR_MAP_SWIZZLE_64B);
    const cuuint32_t b3[5] = {32, 2, 4, 4, 3};
    encode(fn, &m.w3[0], d_in[4], 5, d, s, b3, CU_TENSOR_MAP_SWIZZLE_64B);
    encode(fn, &m.w3[1], (char*)d_in[4] + 32, 5, d, s, b3, CU_TENSOR_MAP_SWIZZLE_64B); }
  { const cuuint64_t d[2] = {DM, SQ}, s[1] = {DM * 2}; const cuuint32_t bg[2] = {80, 24}, bx[2] = {80, 128}, bo[2] = {80, 16};
    encode(fn, &m.xg, d_in[0], 2, d, s, bg, CU_TENSOR_MAP_SWIZZLE_NONE);
    encode(fn, &m.xe, d_in[0], 2, d, s, bx, CU_TENSOR_MAP_SWIZZLE_NONE);
    encode(fn, &m.out, d_out, 2, d, s, bo, CU_TENSOR_MAP_SWIZZLE_NONE); }
  Params p;
  p.x = (const __nv_bfloat16*)d_in[0]; p.wr = (const __nv_bfloat16*)d_in[6]; p.wg = (const __nv_bfloat16*)d_in[7];
  p.wu = (const __nv_bfloat16*)d_in[8]; p.wd = (const __nv_bfloat16*)d_in[9];

  p.k = (const __nv_bfloat16*)d_in[1]; p.v = (const __nv_bfloat16*)d_in[2]; p.s = scr;
  cudaLaunchConfig_t cfg = {};
  cfg.gridDim = dim3(132); cfg.blockDim = dim3(384); cfg.dynamicSmemBytes = SMEM_BYTES; cfg.stream = cudaStreamPerThread;
  cudaLaunchKernelEx(&cfg, fused_kernel, p, m);
}
```

```cpp
#include <cuda_runtime.h>
#include <cuda_bf16.h>
#include <cuda.h>
#include <stdint.h>

namespace {

constexpr int SQ = 2048, DM = 640, NH = 32, DH = 192, SKC = 2048, WIN = 512, FF = 1536;
constexpr int QD = NH * DH;
constexpr uint32_t TA = 16384, TB = 24576, TW = 20480, OFF_B = 5 * TA, OFF_M = OFF_B + 6 * TB, SMEM_BYTES = OFF_M + 3072;
constexpr int WAIT_BUDGET = 1 << 20;

constexpr int FL_XN = 0;
constexpr int FL_O = 512;
constexpr int FL_RD = FL_O + 1024;
constexpr int FL_FFN = FL_RD + 1024;
constexpr int FL_SIDE = FL_FFN + 32;
struct __align__(1024) Scratch {
  unsigned long long done, pad0[15];
  unsigned flag[FL_SIDE + 32];
  uint4 cand[8];
  float ffn[4 * 2 * DM];
  int sel[4];
  __nv_bfloat16 gsel[2 * DM];
  uint4 cs[8 * 4 * DH / 2];
  uint2 stat[SQ];
  __align__(1024) __nv_bfloat16 xn[SQ * DM];
  __align__(1024) uint4 o[SQ * QD / 8];
};
__device__ Scratch g_scratch;

__device__ __forceinline__ uint32_t smem_u32(const void* p) { return (uint32_t)__cvta_generic_to_shared(p); }
__device__ __forceinline__ void mbar_init(uint32_t bar, int cnt) { asm volatile("mbarrier.init.shared::cta.b64 [%0], %1;" ::"r"(bar), "r"(cnt)); }
__device__ __forceinline__ void mbar_expect_tx(uint32_t bar, uint32_t bytes) {
  asm volatile("mbarrier.arrive.expect_tx.shared::cta.b64 _, [%0], %1;" ::"r"(bar), "r"(bytes) : "memory");
}
__device__ __forceinline__ void mbar_arrive(uint32_t bar) { asm volatile("mbarrier.arrive.shared::cta.b64 _, [%0];" ::"r"(bar) : "memory"); }
__device__ __forceinline__ void mbar_arrive_cluster(uint32_t addr) { asm volatile("mbarrier.arrive.shared::cluster.b64 _, [%0];" ::"r"(addr) : "memory"); }
__device__ __forceinline__ bool mbar_try(uint32_t bar, uint32_t parity) {
  uint32_t ok;
  asm volatile("{\n.reg .pred p;\nmbarrier.try_wait.parity.shared::cta.b64 p, [%1], %2;\nselp.u32 %0, 1, 0, p;\n}\n" : "=r"(ok) : "r"(bar), "r"(parity) : "memory");
  return ok;
}
__device__ __forceinline__ void mbar_wait(uint32_t bar, uint32_t parity, int& budget) {
#pragma unroll 1
  while (!mbar_try(bar, parity)) { if (--budget < 0) break; }
}
__device__ __forceinline__ void mbar_wait(uint32_t bar, uint32_t parity) {
#pragma unroll 1
  while (!mbar_try(bar, parity)) {}
}
__device__ __forceinline__ unsigned ld_acquire(const unsigned* p) { unsigned v; asm volatile("ld.acquire.gpu.global.u32 %0, [%1];" : "=r"(v) : "l"(p) : "memory"); return v; }
__device__ __forceinline__ void wait_flag(const unsigned* p, unsigned target) {
#pragma unroll 1
  while (__any_sync(~0u, (int)(ld_acquire(p) - target) < 0)) {}
}
__device__ __forceinline__ void red_release(unsigned* p) { asm volatile("red.release.gpu.global.add.u32 [%0], 1;" ::"l"(p) : "memory"); }
__device__ __forceinline__ void fence_proxy_async() { asm volatile("fence.proxy.async.global;" ::: "memory"); }
__device__ __forceinline__ bool elect() {
  uint32_t p;
  asm volatile("{\n.reg .pred P;\nelect.sync _|P, 0xffffffff;\nselp.u32 %0, 1, 0, P;\n}\n" : "=r"(p));
  return p;
}
__device__ __forceinline__ void cluster_arrive() { asm volatile("barrier.cluster.arrive.relaxed.aligned;" ::: "memory"); }
__device__ __forceinline__ void cluster_wait() { asm volatile("barrier.cluster.wait.aligned;" ::: "memory"); }
__device__ __forceinline__ void cluster_sync() { cluster_arrive(); cluster_wait(); }
__device__ __forceinline__ void tma2d(uint32_t dst, const CUtensorMap* tm, int c0, int c1, uint32_t bar) {
  asm volatile("cp.async.bulk.tensor.2d.shared::cluster.global.mbarrier::complete_tx::bytes [%0], [%1, {%3, %4}], [%2];"
               ::"r"(dst), "l"(tm), "r"(bar), "r"(c0), "r"(c1) : "memory");
}
constexpr uint64_t POL_FIRST = 0x12F0000000000000ull;
__device__ __forceinline__ void tma4d_mc(uint32_t dst, const CUtensorMap* tm, int c2, int c3, uint32_t bar) {
  asm volatile("cp.async.bulk.tensor.4d.shared::cluster.global.mbarrier::complete_tx::bytes.multicast::cluster.L2::cache_hint [%0], [%1, {%3, %3, %4, %5}], [%2], %6, %7;"
               ::"r"(dst), "l"(tm), "r"(bar), "r"(0), "r"(c2), "r"(c3), "h"((uint16_t)3), "l"(POL_FIRST) : "memory");
}
__device__ __forceinline__ void tma5d_mc(uint32_t dst, const CUtensorMap* tm, int c2, int c4, uint32_t bar) {
  asm volatile("cp.async.bulk.tensor.5d.shared::cluster.global.mbarrier::complete_tx::bytes.multicast::cluster.L2::cache_hint [%0], [%1, {%3, %3, %4, %3, %5}], [%2], %6, %7;"
               ::"r"(dst), "l"(tm), "r"(bar), "r"(0), "r"(c2), "r"(c4), "h"((uint16_t)3), "l"(POL_FIRST) : "memory");
}
__device__ __forceinline__ void bulk_load(uint32_t dst, const void* src, uint32_t bytes, uint32_t bar) {
  asm volatile("cp.async.bulk.shared::cluster.global.mbarrier::complete_tx::bytes.L2::cache_hint [%0], [%1], %2, [%3], %4;" ::"r"(dst), "l"(src), "r"(bytes), "r"(bar), "l"(POL_FIRST) : "memory");
}
__device__ __forceinline__ void tma2d_store(const CUtensorMap* tm, uint32_t src, int c0, int c1) {
  asm volatile("cp.async.bulk.tensor.2d.global.shared::cta.bulk_group [%0, {%2, %3}], [%1];" ::"l"(tm), "r"(src), "r"(c0), "r"(c1) : "memory");
}
__device__ __forceinline__ uint32_t lds32(uint32_t a) { uint32_t v; asm volatile("ld.shared.u32 %0, [%1];" : "=r"(v) : "r"(a) : "memory"); return v; }
__device__ __forceinline__ uint2 lds64(uint32_t a) { uint2 v; asm volatile("ld.shared.v2.u32 {%0,%1}, [%2];" : "=r"(v.x), "=r"(v.y) : "r"(a) : "memory"); return v; }
__device__ __forceinline__ uint4 lds128(uint32_t a) { uint4 v; asm volatile("ld.shared.v4.u32 {%0,%1,%2,%3}, [%4];" : "=r"(v.x), "=r"(v.y), "=r"(v.z), "=r"(v.w) : "r"(a) : "memory"); return v; }
__device__ __forceinline__ void ldsm4(uint32_t a, uint32_t* v) {
  asm volatile("ldmatrix.sync.aligned.m8n8.x4.shared.b16 {%0,%1,%2,%3}, [%4];" : "=r"(v[0]), "=r"(v[1]), "=r"(v[2]), "=r"(v[3]) : "r"(a) : "memory");
}
__device__ __forceinline__ void stsm4(uint32_t a, const uint32_t* v) {
  asm volatile("stmatrix.sync.aligned.m8n8.x4.shared.b16 [%0], {%1,%2,%3,%4};" ::"r"(a), "r"(v[0]), "r"(v[1]), "r"(v[2]), "r"(v[3]) : "memory");
}
__device__ __forceinline__ void sts32(uint32_t a, uint32_t v) { asm volatile("st.shared.u32 [%0], %1;" ::"r"(a), "r"(v) : "memory"); }
__device__ __forceinline__ void st_pkt(uint4* p, uint32_t a, uint32_t b, uint32_t c, uint32_t d) {
  asm volatile("st.relaxed.gpu.global.v4.b32 [%0], {%1, %2, %3, %4};" ::"l"(p), "r"(a), "r"(b), "r"(c), "r"(d) : "memory");
}
__device__ __forceinline__ void st_pkt8(void* p, uint32_t a, uint32_t b) {
  asm volatile("{\n.reg .b64 v;\nmov.b64 v, {%1, %2};\nst.relaxed.gpu.global.b64 [%0], v;\n}\n" ::"l"(p), "r"(a), "r"(b) : "memory");
}
__device__ __forceinline__ uint4 ld_pkt(const uint4* p) {
  uint4 v;
  asm volatile("{\n.reg .b128 v;\nld.relaxed.gpu.global.b128 v, [%4];\nmov.b128 {%0, %1, %2, %3}, v;\n}\n" : "=r"(v.x), "=r"(v.y), "=r"(v.z), "=r"(v.w) : "l"(p) : "memory");
  return v;
}
__device__ __forceinline__ uint4 ldg_nc(const void* p) {
  uint4 v;
  asm volatile("ld.global.nc.v4.u32 {%0,%1,%2,%3}, [%4];" : "=r"(v.x), "=r"(v.y), "=r"(v.z), "=r"(v.w) : "l"(p));
  return v;
}
#define WG_FENCE() asm volatile("wgmma.fence.sync.aligned;" ::: "memory")
#define WG_COMMIT() asm volatile("wgmma.commit_group.sync.aligned;" ::: "memory")
#define WG_WAIT(n) asm volatile("wgmma.wait_group.sync.aligned " #n ";" ::: "memory")
template <int N> __device__ __forceinline__ void reg_fence(float (&d)[N]) {
#pragma unroll
  for (int i = 0; i < N; i++) asm volatile("" : "+f"(d[i])::"memory");
}
template <int N> __device__ __forceinline__ void reg_fence(uint32_t (&d)[N]) {
#pragma unroll
  for (int i = 0; i < N; i++) asm volatile("" : "+r"(d[i])::"memory");
}
__device__ __forceinline__ constexpr uint64_t desc_hi(uint32_t lbo, uint32_t sbo, uint64_t sw) {
  return ((uint64_t)(lbo >> 4) << 16) | ((uint64_t)(sbo >> 4) << 32) | (sw << 62);
}
__device__ __forceinline__ uint64_t mkdesc(uint32_t addr, uint64_t hi) { return hi | (uint64_t)((addr & 0x3FFFF) >> 4); }
__device__ __forceinline__ uint32_t pack_bf16(float lo, float hi) { uint32_t r; asm("cvt.rn.bf16x2.f32 %0, %1, %2;" : "=r"(r) : "f"(hi), "f"(lo)); return r; }
__device__ __forceinline__ float bf_lo(uint32_t v) { return __uint_as_float(v << 16); }
__device__ __forceinline__ float bf_hi(uint32_t v) { return __uint_as_float(v & 0xffff0000u); }
__device__ __forceinline__ uint32_t hadd2(uint32_t a, uint32_t b) { uint32_t r; asm("add.rn.bf16x2 %0, %1, %2;" : "=r"(r) : "r"(a), "r"(b)); return r; }
__device__ __forceinline__ uint32_t hsub2(uint32_t a, uint32_t b) { uint32_t r; asm("sub.rn.bf16x2 %0, %1, %2;" : "=r"(r) : "r"(a), "r"(b)); return r; }
__device__ __forceinline__ uint32_t hmul2(uint32_t a, uint32_t b) { uint32_t r; asm("mul.rn.bf16x2 %0, %1, %2;" : "=r"(r) : "r"(a), "r"(b)); return r; }
__device__ __forceinline__ float rbf(float x) { return __bfloat162float(__float2bfloat16_rn(x)); }
__device__ __forceinline__ float ex2(float x) { float y; asm("ex2.approx.ftz.f32 %0, %1;" : "=f"(y) : "f"(x)); return y; }
__device__ __forceinline__ float rcp(float x) { float y; asm("rcp.approx.ftz.f32 %0, %1;" : "=f"(y) : "f"(x)); return y; }
__device__ __forceinline__ float sigmoid_f(float x) { return rcp(1.f + ex2(x * -1.4426950408889634f)); }
__device__ __forceinline__ float silu_f(float x) { return x * sigmoid_f(x); }

__device__ __forceinline__ void wg_ss192t(float (&d)[96], uint64_t da, uint64_t db, int sd) {
  asm volatile("{\n.reg .pred p;\nsetp.ne.b32 p, %98, 0;\n"
    "wgmma.mma_async.sync.aligned.m64n192k16.f32.bf16.bf16 {%0,%1,%2,%3,%4,%5,%6,%7,%8,%9,%10,%11,%12,%13,%14,%15,%16,%17,%18,%19,%20,%21,%22,%23,%24,%25,%26,%27,%28,%29,%30,%31,%32,%33,%34,%35,%36,%37,%38,%39,%40,%41,%42,%43,%44,%45,%46,%47,%48,%49,%50,%51,%52,%53,%54,%55,%56,%57,%58,%59,%60,%61,%62,%63,%64,%65,%66,%67,%68,%69,%70,%71,%72,%73,%74,%75,%76,%77,%78,%79,%80,%81,%82,%83,%84,%85,%86,%87,%88,%89,%90,%91,%92,%93,%94,%95}, %96, %97, p, 1, 1, 0, 1;\n}\n"
    : "+f"(d[0]),"+f"(d[1]),"+f"(d[2]),"+f"(d[3]),"+f"(d[4]),"+f"(d[5]),"+f"(d[6]),"+f"(d[7]),"+f"(d[8]),"+f"(d[9]),"+f"(d[10]),"+f"(d[11]),"+f"(d[12]),"+f"(d[13]),"+f"(d[14]),"+f"(d[15]),"+f"(d[16]),"+f"(d[17]),"+f"(d[18]),"+f"(d[19]),"+f"(d[20]),"+f"(d[21]),"+f"(d[22]),"+f"(d[23]),"+f"(d[24]),"+f"(d[25]),"+f"(d[26]),"+f"(d[27]),"+f"(d[28]),"+f"(d[29]),"+f"(d[30]),"+f"(d[31]),"+f"(d[32]),"+f"(d[33]),"+f"(d[34]),"+f"(d[35]),"+f"(d[36]),"+f"(d[37]),"+f"(d[38]),"+f"(d[39]),"+f"(d[40]),"+f"(d[41]),"+f"(d[42]),"+f"(d[43]),"+f"(d[44]),"+f"(d[45]),"+f"(d[46]),"+f"(d[47]),"+f"(d[48]),"+f"(d[49]),"+f"(d[50]),"+f"(d[51]),"+f"(d[52]),"+f"(d[53]),"+f"(d[54]),"+f"(d[55]),"+f"(d[56]),"+f"(d[57]),"+f"(d[58]),"+f"(d[59]),"+f"(d[60]),"+f"(d[61]),"+f"(d[62]),"+f"(d[63]),"+f"(d[64]),"+f"(d[65]),"+f"(d[66]),"+f"(d[67]),"+f"(d[68]),"+f"(d[69]),"+f"(d[70]),"+f"(d[71]),"+f"(d[72]),"+f"(d[73]),"+f"(d[74]),"+f"(d[75]),"+f"(d[76]),"+f"(d[77]),"+f"(d[78]),"+f"(d[79]),"+f"(d[80]),"+f"(d[81]),"+f"(d[82]),"+f"(d[83]),"+f"(d[84]),"+f"(d[85]),"+f"(d[86]),"+f"(d[87]),"+f"(d[88]),"+f"(d[89]),"+f"(d[90]),"+f"(d[91]),"+f"(d[92]),"+f"(d[93]),"+f"(d[94]),"+f"(d[95])
    : "l"(da), "l"(db), "r"(sd));
}
__device__ __forceinline__ void wg_rs64(float (&d)[32], uint32_t a0, uint32_t a1, uint32_t a2, uint32_t a3, uint64_t db, int sd) {
  asm volatile("{\n.reg .pred p;\nsetp.ne.b32 p, %37, 0;\n"
    "wgmma.mma_async.sync.aligned.m64n64k16.f32.bf16.bf16 {%0,%1,%2,%3,%4,%5,%6,%7,%8,%9,%10,%11,%12,%13,%14,%15,%16,%17,%18,%19,%20,%21,%22,%23,%24,%25,%26,%27,%28,%29,%30,%31}, {%32,%33,%34,%35}, %36, p, 1, 1, 0;\n}\n"
    : "+f"(d[0]),"+f"(d[1]),"+f"(d[2]),"+f"(d[3]),"+f"(d[4]),"+f"(d[5]),"+f"(d[6]),"+f"(d[7]),"+f"(d[8]),"+f"(d[9]),"+f"(d[10]),"+f"(d[11]),"+f"(d[12]),"+f"(d[13]),"+f"(d[14]),"+f"(d[15]),"+f"(d[16]),"+f"(d[17]),"+f"(d[18]),"+f"(d[19]),"+f"(d[20]),"+f"(d[21]),"+f"(d[22]),"+f"(d[23]),"+f"(d[24]),"+f"(d[25]),"+f"(d[26]),"+f"(d[27]),"+f"(d[28]),"+f"(d[29]),"+f"(d[30]),"+f"(d[31])
    : "r"(a0), "r"(a1), "r"(a2), "r"(a3), "l"(db), "r"(sd));
}
__device__ __forceinline__ void wg_rs192t(float (&d)[96], uint32_t a0, uint32_t a1, uint32_t a2, uint32_t a3, uint64_t db, int sd) {
  asm volatile("{\n.reg .pred p;\nsetp.ne.b32 p, %101, 0;\n"
    "wgmma.mma_async.sync.aligned.m64n192k16.f32.bf16.bf16 {%0,%1,%2,%3,%4,%5,%6,%7,%8,%9,%10,%11,%12,%13,%14,%15,%16,%17,%18,%19,%20,%21,%22,%23,%24,%25,%26,%27,%28,%29,%30,%31,%32,%33,%34,%35,%36,%37,%38,%39,%40,%41,%42,%43,%44,%45,%46,%47,%48,%49,%50,%51,%52,%53,%54,%55,%56,%57,%58,%59,%60,%61,%62,%63,%64,%65,%66,%67,%68,%69,%70,%71,%72,%73,%74,%75,%76,%77,%78,%79,%80,%81,%82,%83,%84,%85,%86,%87,%88,%89,%90,%91,%92,%93,%94,%95}, {%96,%97,%98,%99}, %100, p, 1, 1, 1;\n}\n"
    : "+f"(d[0]),"+f"(d[1]),"+f"(d[2]),"+f"(d[3]),"+f"(d[4]),"+f"(d[5]),"+f"(d[6]),"+f"(d[7]),"+f"(d[8]),"+f"(d[9]),"+f"(d[10]),"+f"(d[11]),"+f"(d[12]),"+f"(d[13]),"+f"(d[14]),"+f"(d[15]),"+f"(d[16]),"+f"(d[17]),"+f"(d[18]),"+f"(d[19]),"+f"(d[20]),"+f"(d[21]),"+f"(d[22]),"+f"(d[23]),"+f"(d[24]),"+f"(d[25]),"+f"(d[26]),"+f"(d[27]),"+f"(d[28]),"+f"(d[29]),"+f"(d[30]),"+f"(d[31]),"+f"(d[32]),"+f"(d[33]),"+f"(d[34]),"+f"(d[35]),"+f"(d[36]),"+f"(d[37]),"+f"(d[38]),"+f"(d[39]),"+f"(d[40]),"+f"(d[41]),"+f"(d[42]),"+f"(d[43]),"+f"(d[44]),"+f"(d[45]),"+f"(d[46]),"+f"(d[47]),"+f"(d[48]),"+f"(d[49]),"+f"(d[50]),"+f"(d[51]),"+f"(d[52]),"+f"(d[53]),"+f"(d[54]),"+f"(d[55]),"+f"(d[56]),"+f"(d[57]),"+f"(d[58]),"+f"(d[59]),"+f"(d[60]),"+f"(d[61]),"+f"(d[62]),"+f"(d[63]),"+f"(d[64]),"+f"(d[65]),"+f"(d[66]),"+f"(d[67]),"+f"(d[68]),"+f"(d[69]),"+f"(d[70]),"+f"(d[71]),"+f"(d[72]),"+f"(d[73]),"+f"(d[74]),"+f"(d[75]),"+f"(d[76]),"+f"(d[77]),"+f"(d[78]),"+f"(d[79]),"+f"(d[80]),"+f"(d[81]),"+f"(d[82]),"+f"(d[83]),"+f"(d[84]),"+f"(d[85]),"+f"(d[86]),"+f"(d[87]),"+f"(d[88]),"+f"(d[89]),"+f"(d[90]),"+f"(d[91]),"+f"(d[92]),"+f"(d[93]),"+f"(d[94]),"+f"(d[95])
    : "r"(a0), "r"(a1), "r"(a2), "r"(a3), "l"(db), "r"(sd));
}
__device__ __forceinline__ void wg_ss160t(float (&d)[80], uint64_t da, uint64_t db, int sd) {
  asm volatile("{\n.reg .pred p;\nsetp.ne.b32 p, %82, 0;\n"
    "wgmma.mma_async.sync.aligned.m64n160k16.f32.bf16.bf16 {%0,%1,%2,%3,%4,%5,%6,%7,%8,%9,%10,%11,%12,%13,%14,%15,%16,%17,%18,%19,%20,%21,%22,%23,%24,%25,%26,%27,%28,%29,%30,%31,%32,%33,%34,%35,%36,%37,%38,%39,%40,%41,%42,%43,%44,%45,%46,%47,%48,%49,%50,%51,%52,%53,%54,%55,%56,%57,%58,%59,%60,%61,%62,%63,%64,%65,%66,%67,%68,%69,%70,%71,%72,%73,%74,%75,%76,%77,%78,%79}, %80, %81, p, 1, 1, 0, 1;\n}\n"
    : "+f"(d[0]),"+f"(d[1]),"+f"(d[2]),"+f"(d[3]),"+f"(d[4]),"+f"(d[5]),"+f"(d[6]),"+f"(d[7]),"+f"(d[8]),"+f"(d[9]),"+f"(d[10]),"+f"(d[11]),"+f"(d[12]),"+f"(d[13]),"+f"(d[14]),"+f"(d[15]),"+f"(d[16]),"+f"(d[17]),"+f"(d[18]),"+f"(d[19]),"+f"(d[20]),"+f"(d[21]),"+f"(d[22]),"+f"(d[23]),"+f"(d[24]),"+f"(d[25]),"+f"(d[26]),"+f"(d[27]),"+f"(d[28]),"+f"(d[29]),"+f"(d[30]),"+f"(d[31]),"+f"(d[32]),"+f"(d[33]),"+f"(d[34]),"+f"(d[35]),"+f"(d[36]),"+f"(d[37]),"+f"(d[38]),"+f"(d[39]),"+f"(d[40]),"+f"(d[41]),"+f"(d[42]),"+f"(d[43]),"+f"(d[44]),"+f"(d[45]),"+f"(d[46]),"+f"(d[47]),"+f"(d[48]),"+f"(d[49]),"+f"(d[50]),"+f"(d[51]),"+f"(d[52]),"+f"(d[53]),"+f"(d[54]),"+f"(d[55]),"+f"(d[56]),"+f"(d[57]),"+f"(d[58]),"+f"(d[59]),"+f"(d[60]),"+f"(d[61]),"+f"(d[62]),"+f"(d[63]),"+f"(d[64]),"+f"(d[65]),"+f"(d[66]),"+f"(d[67]),"+f"(d[68]),"+f"(d[69]),"+f"(d[70]),"+f"(d[71]),"+f"(d[72]),"+f"(d[73]),"+f"(d[74]),"+f"(d[75]),"+f"(d[76]),"+f"(d[77]),"+f"(d[78]),"+f"(d[79])
    : "l"(da), "l"(db), "r"(sd));
}
__device__ __forceinline__ void wg_ss80t(float (&d)[40], uint64_t da, uint64_t db, int sd) {
  asm volatile("{\n.reg .pred p;\nsetp.ne.b32 p, %42, 0;\n"
    "wgmma.mma_async.sync.aligned.m64n80k16.f32.bf16.bf16 {%0,%1,%2,%3,%4,%5,%6,%7,%8,%9,%10,%11,%12,%13,%14,%15,%16,%17,%18,%19,%20,%21,%22,%23,%24,%25,%26,%27,%28,%29,%30,%31,%32,%33,%34,%35,%36,%37,%38,%39}, %40, %41, p, 1, 1, 0, 1;\n}\n"
    : "+f"(d[0]),"+f"(d[1]),"+f"(d[2]),"+f"(d[3]),"+f"(d[4]),"+f"(d[5]),"+f"(d[6]),"+f"(d[7]),"+f"(d[8]),"+f"(d[9]),"+f"(d[10]),"+f"(d[11]),"+f"(d[12]),"+f"(d[13]),"+f"(d[14]),"+f"(d[15]),"+f"(d[16]),"+f"(d[17]),"+f"(d[18]),"+f"(d[19]),"+f"(d[20]),"+f"(d[21]),"+f"(d[22]),"+f"(d[23]),"+f"(d[24]),"+f"(d[25]),"+f"(d[26]),"+f"(d[27]),"+f"(d[28]),"+f"(d[29]),"+f"(d[30]),"+f"(d[31]),"+f"(d[32]),"+f"(d[33]),"+f"(d[34]),"+f"(d[35]),"+f"(d[36]),"+f"(d[37]),"+f"(d[38]),"+f"(d[39])
    : "l"(da), "l"(db), "r"(sd));
}

struct Maps { CUtensorMap x, xn, wq, k, v, wo, w3[2], xg, xe, out; };
struct Params {
  const __nv_bfloat16 *x, *wr, *wg, *wu, *wd, *k, *v;
  Scratch* s;
};

__device__ __forceinline__ void side_cta(const Params& p, int sc, unsigned epoch, float* sm) {
  const int tid = threadIdx.x, lane = tid & 31, warp = tid >> 5;
  int budget = WAIT_BUDGET;
  float* s_x = sm;
  float* s_red = sm + 1280;
  float* s_h = s_red + 6144;
  uint4* s_c = (uint4*)(s_h + 768);
  uint2* s_st = (uint2*)(s_c + 16);
  constexpr int DEPTH = 7, STEP = 4 * 6144;
  const uint32_t ring = smem_u32(s_st + 512) + tid * 16;
  const int cg = tid % 96, ks = tid / 96, cd = tid % 80, kd = tid / 80;
  const __nv_bfloat16* wp = (cg < 48 ? p.wg : p.wu) + (size_t)(ks * 160) * FF + sc * 384 + (cg % 48) * 8;
  int kf = 0, pitch = FF;
  uint32_t slot = ring;
  auto refill = [&]() {
    if (kf == 40) { wp = p.wd + (size_t)(sc * 384 + kd * 96) * DM + cd * 8; pitch = DM; }
    if (kf < (tid < 320 ? 64 : 40)) {
#pragma unroll
      for (int j = 0; j < 4; j++) asm volatile("cp.async.cg.shared.global.L2::cache_hint [%0], [%1], 16, %2;" ::"r"(slot + j * 6144), "l"(wp + j * pitch), "l"(POL_FIRST) : "memory");
    }
    asm volatile("cp.async.commit_group;" ::: "memory");
    wp += 4 * pitch; kf++;
    slot += STEP; if (slot == ring + DEPTH * STEP) slot = ring;
  };
  auto gemv = [&](int n, const float* x0, const float* x1, float* out) {
    float a[2][8] = {};
#pragma unroll 1
    for (int k = 0; k < n; k += 4) {
      refill();
      asm volatile("cp.async.wait_group %0;" ::"n"(DEPTH - 1) : "memory");
      const float4 f0 = *(const float4*)(x0 + k), f1 = *(const float4*)(x1 + k);
      const float y0[4] = {f0.x, f0.y, f0.z, f0.w}, y1[4] = {f1.x, f1.y, f1.z, f1.w};
#pragma unroll
      for (int j = 0; j < 4; j++) {
        const uint4 v = lds128(slot + j * 6144);
        const uint32_t u[4] = {v.x, v.y, v.z, v.w};
#pragma unroll
        for (int i = 0; i < 4; i++) {
          a[0][2 * i] += y0[j] * bf_lo(u[i]); a[0][2 * i + 1] += y0[j] * bf_hi(u[i]);
          a[1][2 * i] += y1[j] * bf_lo(u[i]); a[1][2 * i + 1] += y1[j] * bf_hi(u[i]);
        }
      }
    }
#pragma unroll
    for (int i = 0; i < 16; i++) out[(i >> 3) * 768 + (i & 7)] = a[i >> 3][i & 7];
  };
  auto load_row = [&](const __nv_bfloat16* r, uint32_t (&v)[10]) {
    const uint4 a = __ldg((const uint4*)r + lane), b = __ldg((const uint4*)r + 32 + lane);
    const uint2 c = __ldg((const uint2*)r + 128 + lane);
    v[0] = a.x; v[1] = a.y; v[2] = a.z; v[3] = a.w; v[4] = b.x; v[5] = b.y; v[6] = b.z; v[7] = b.w; v[8] = c.x; v[9] = c.y;
  };
  uint32_t wr[10], xb[3][10];
  load_row(p.wr, wr);
  auto stat2 = [&](int pair) {
    uint4 v;
    do v = ld_pkt((const uint4*)p.s->stat + pair); while ((((v.x ^ (epoch + 1)) | (v.z ^ (epoch + 1))) & 0xffff) && --budget >= 0);
    return make_uint4(__byte_perm(v.x, 0, 0x3232), v.y, __byte_perm(v.z, 0, 0x3232), v.w);
  };
  if (tid < 256) ((uint4*)s_st)[tid] = stat2(sc * 256 + tid);
  __syncthreads();
#pragma unroll
  for (int b = 0; b < 3; b++) load_row(p.x + (size_t)(sc * 512 + warp + 12 * b) * DM, xb[b]);
#pragma unroll 1
  for (int k = 0; k < DEPTH - 1; k++) refill();
  float v0 = -INFINITY, v1 = -INFINITY; int i0 = 0xfff, i1 = 0xfff;
  auto better = [](float a, int ia, float b, int ib) { return a > b || (a == b && ia < ib); };
  auto push = [&](float v, int i) {
    if (better(v, i, v0, i0)) { v1 = v0; i1 = i0; v0 = v; i0 = i; }
    else if (better(v, i, v1, i1)) { v1 = v; i1 = i; }
  };
  auto push2 = [&](uint4 c) { push(__uint_as_float(c.x), c.y & 0xfff); push(__uint_as_float(c.z), c.w & 0xfff); };
#pragma unroll 1
  for (int l3 = warp; l3 < 512; l3 += 36) {
#pragma unroll
    for (int b = 0; b < 3; b++) {
      const int lr = l3 + 12 * b;
      if (lr >= 512) break;
      const uint2 st = s_st[lr];
      uint32_t v[10];
#pragma unroll
      for (int i = 0; i < 10; i++) v[i] = hsub2(xb[b][i], st.x);
      if (lr + 36 < 512) load_row(p.x + (size_t)(sc * 512 + lr + 36) * DM, xb[b]);
      float r0 = 0.f, r1 = 0.f;
#pragma unroll
      for (int i = 0; i < 10; i++) {
        const uint32_t xn = pack_bf16(bf_lo(v[i]) * __uint_as_float(st.y), bf_hi(v[i]) * __uint_as_float(st.y));
        r0 = fmaf(bf_lo(xn), bf_lo(wr[i]), r0); r1 = fmaf(bf_hi(xn), bf_hi(wr[i]), r1);
      }
      r0 += r1;
#pragma unroll
      for (int o = 16; o > 0; o >>= 1) r0 += __shfl_xor_sync(~0u, r0, o);
      push(rbf(r0), sc * 512 + lr);
    }
  }
  if (lane == 0) s_c[warp] = make_uint4(__float_as_uint(v0), i0, __float_as_uint(v1), i1);
  __syncthreads();
#pragma unroll 1
  for (int w = 1; w < 12; w++) push2(s_c[(warp + w) % 12]);
  const uint32_t tag = (epoch + 1) << 12;
  if (tid == 0) st_pkt(p.s->cand + sc, __float_as_uint(v0), i0 | tag, __float_as_uint(v1), i1);
  {
    uint4 c;
    do c = ld_pkt(p.s->cand + (lane & 3)); while (((c.y ^ tag) >> 12) && --budget >= 0);
#pragma unroll 1
    for (int w = 1; w < 4; w++) { const int o = (sc + w) & 3; push2(make_uint4(__shfl_sync(~0u, c.x, o), __shfl_sync(~0u, c.y, o), __shfl_sync(~0u, c.z, o), __shfl_sync(~0u, c.w, o))); }
  }
  if (i0 >= SQ) i0 = 0;
  if (i1 >= SQ) i1 = (i0 == 0) ? 1 : 0;
  if (tid < 320) {
    const int row = tid < 160 ? i0 : i1;
    const uint2 u = __ldg((const uint2*)(p.x + (size_t)row * DM) + tid % 160);
    const uint4 st = stat2(row >> 1);
    const uint32_t mean2 = row & 1 ? st.z : st.x, d0 = hsub2(u.x, mean2), d1 = hsub2(u.y, mean2);
    const float inv = __uint_as_float(row & 1 ? st.w : st.y);
    ((float4*)s_x)[tid] = make_float4(rbf(bf_lo(d0) * inv), rbf(bf_hi(d0) * inv), rbf(bf_lo(d1) * inv), rbf(bf_hi(d1) * inv));
  }
  __syncthreads();
  gemv(160, s_x + ks * 160, s_x + DM + ks * 160, s_red + ks * 1536 + cg * 8);
  __syncthreads();
#pragma unroll
  for (int t = 0; t < 2; t++) {
    float g = 0.f, u = 0.f;
#pragma unroll
    for (int k = 0; k < 4; k++) { g += s_red[(k * 2 + t) * 768 + tid]; u += s_red[(k * 2 + t) * 768 + 384 + tid]; }
    s_h[t * 384 + tid] = rbf(rbf(silu_f(rbf(g))) * rbf(u));
  }
  __syncthreads();
  if (tid < 320) gemv(96, s_h + kd * 96, s_h + 384 + kd * 96, s_red + kd * 1536 + cd * 8);
  __syncthreads();
  const int o4 = tid + (tid < 160 ? 0 : 32);
  if (tid < 320) {
    const float4 *r = (const float4*)s_red + o4, a = r[0], b = r[384], c = r[768], d = r[1152];
    ((float4*)p.s->ffn)[sc * 320 + tid] = make_float4(a.x + b.x + c.x + d.x, a.y + b.y + c.y + d.y, a.z + b.z + c.z + d.z, a.w + b.w + c.w + d.w);
  }
  __syncthreads();
  if (tid == 0) { __threadfence(); s_c[0].x = (atomicAdd(&p.s->flag[FL_SIDE], 1u) & 3u) == 3u; __threadfence(); }
  __syncthreads();
  if (s_c[0].x) {
    if (tid < 320) {
      const float4 *r = (const float4*)p.s->ffn + tid, a = __ldcg(r), b = __ldcg(r + 320), c = __ldcg(r + 640), d = __ldcg(r + 960), x = ((float4*)s_x)[tid];
      const float rs = rbf(sigmoid_f(tid < 160 ? v0 : v1));
      auto gate = [&](float xn, float y) { return silu_f(rbf(xn + rbf(rbf(y) * rs))); };
      if (tid == 0) { p.s->sel[0] = i0; p.s->sel[1] = i1; }
      ((uint2*)p.s->gsel)[tid] =
          make_uint2(pack_bf16(gate(x.x, a.x + b.x + c.x + d.x), gate(x.y, a.y + b.y + c.y + d.y)), pack_bf16(gate(x.z, a.z + b.z + c.z + d.z), gate(x.w, a.w + b.w + c.w + d.w)));
    }
    __syncthreads();
    if (tid == 0) red_release(&p.s->flag[FL_FFN]);
  }
}

constexpr float SM_C = 0.07216878364870322f * 1.4426950408889634f;

constexpr int LD = 0, LS = 3;
__device__ __forceinline__ void ln_piece(const Params& p, uint32_t (&r)[48], int k, int row, int l16) {
  auto f = [&](int i) { return __uint_as_float(r[i]); };
  if (k == LD) {
#pragma unroll
    for (int i = 0; i < 5; i++) {
      const uint4 v = ldg_nc((const uint4*)(p.x + (size_t)row * DM) + i * 16 + l16);
      r[4 * i] = v.x; r[4 * i + 1] = v.y; r[4 * i + 2] = v.z; r[4 * i + 3] = v.w;
    }
    asm volatile("ld.relaxed.gpu.global.v2.u32 {%0,%1}, [%2];" : "=r"(r[20]), "=r"(r[21]) : "l"(&p.s->done));
  } else if (k == LS || k == LS + 1) {
    if (k == LS) { r[22] = __shfl_sync(~0u, r[0], 0, 16) << 16; r[23] = r[24] = 0; }
    float s0 = f(23), s1 = 0.f, q0 = f(24), q1 = 0.f;
#pragma unroll
    for (int i = 10 * (k - LS); i < 10 * (k - LS) + 10; i++) {
      const float a = bf_lo(r[i]) - f(22), b = bf_hi(r[i]) - f(22);
      s0 += a; s1 += b; q0 = fmaf(a, a, q0); q1 = fmaf(b, b, q1);
    }
    r[23] = __float_as_uint(s0 + s1); r[24] = __float_as_uint(q0 + q1);
  } else if (k == LS + 2) {
    float s0 = f(23), q0 = f(24);
#pragma unroll
    for (int o = 8; o > 0; o >>= 1) { s0 += __shfl_xor_sync(~0u, s0, o); q0 += __shfl_xor_sync(~0u, q0, o); }
    s0 *= 1.f / DM;
    const float mean = f(22) + s0, var = rbf(fmaxf(fmaf(q0, 1.f / DM, -s0 * s0), 0.f));
    float sd; asm("sqrt.approx.ftz.f32 %0, %1;" : "=f"(sd) : "f"(rbf(var + 1e-5f)));
    const float inv = rcp(rbf(sd));
    r[22] = pack_bf16(mean, mean); r[23] = __float_as_uint(inv * SM_C);
    const uint32_t tag = __funnelshift_r(r[20], r[21], 7) + 1;
    if (l16 == 0) st_pkt8(&p.s->stat[row], __byte_perm(tag, r[22], 0x7610), __float_as_uint(inv));
  } else if (k > LS + 2 && k <= LS + 5) {
#pragma unroll
    for (int j = 2 * (k - LS - 3); j < 2 * (k - LS - 3) + 2 && j < 5; j++) {
#pragma unroll
      for (int i = 4 * j; i < 4 * j + 4; i++) { const uint32_t d = hsub2(r[i], r[22]); r[i] = pack_bf16(bf_lo(d) * f(23), bf_hi(d) * f(23)); }
      *((uint4*)(p.s->xn + (size_t)row * DM) + j * 16 + l16) = make_uint4(r[4 * j], r[4 * j + 1], r[4 * j + 2], r[4 * j + 3]);
    }
  }
}

constexpr float SM_HI = 0x1p64f, SM_LO = 0x1p-64f;
__device__ __forceinline__ void exp_block(float (&s)[32], float& l0, float& l1, int from = 0, int to = 32) {
#pragma unroll
  for (int i = from; i < to; i++) { s[i] = ex2(s[i]); if (i & 2) l1 += s[i]; else l0 += s[i]; }
}
__device__ __forceinline__ float quad_sum(float v) { v += __shfl_xor_sync(~0u, v, 1); return v + __shfl_xor_sync(~0u, v, 2); }
__device__ __forceinline__ float quad_max(float v) { v = fmaxf(v, __shfl_xor_sync(~0u, v, 1)); return fmaxf(v, __shfl_xor_sync(~0u, v, 2)); }
__device__ __noinline__ void safe_head(const uint32_t* kp, const uint32_t* vp, uint4* io) {
  uint32_t fq[48];
#pragma unroll
  for (int i = 0; i < 12; i++) { const uint4 v = io[(i >> 1) * 512 + (i & 1) * 32]; fq[4 * i] = v.x; fq[4 * i + 1] = v.y; fq[4 * i + 2] = v.z; fq[4 * i + 3] = v.w; }
  float m0 = -INFINITY, m1 = -INFINITY;
#pragma unroll 1
  for (int pass = 0; pass < 3; pass++) {
    float o[48] = {}, l0 = 0.f, l1 = 0.f;
#pragma unroll 1
    for (int n = 0; n < 64; n++) {
      const uint32_t *kr = kp + n * (8 * DH / 2), *vr = vp + n * (8 * DH / 2) + (pass - 1) * 48;
      float d[4] = {};
#pragma unroll
      for (int t = 0; t < 12; t++)
        asm volatile("mma.sync.aligned.m16n8k16.row.col.f32.bf16.bf16.f32 {%0,%1,%2,%3}, {%4,%5,%6,%7}, {%8,%9}, {%0,%1,%2,%3};"
                     : "+f"(d[0]), "+f"(d[1]), "+f"(d[2]), "+f"(d[3])
                     : "r"(fq[4 * t]), "r"(fq[4 * t + 1]), "r"(fq[4 * t + 2]), "r"(fq[4 * t + 3]), "r"(__ldg(kr + 8 * t)), "r"(__ldg(kr + 8 * t + 4)));
      if (pass == 0) { m0 = fmaxf(m0, fmaxf(d[0], d[1])); m1 = fmaxf(m1, fmaxf(d[2], d[3])); continue; }
      d[0] = ex2(d[0] - m0); d[1] = ex2(d[1] - m0); d[2] = ex2(d[2] - m1); d[3] = ex2(d[3] - m1);
      l0 += d[0] + d[1]; l1 += d[2] + d[3];
      const uint32_t p0 = pack_bf16(d[0], d[1]), p1 = pack_bf16(d[2], d[3]);
#pragma unroll
      for (int c = 0; c < 12; c++)
        asm volatile("{\n.reg .b32 t;\nmovmatrix.sync.aligned.m8n8.trans.b16 t, %6;\n"
                     "mma.sync.aligned.m16n8k8.row.col.f32.bf16.bf16.f32 {%0,%1,%2,%3}, {%4,%5}, {t}, {%0,%1,%2,%3};\n}\n"
                     : "+f"(o[4 * c]), "+f"(o[4 * c + 1]), "+f"(o[4 * c + 2]), "+f"(o[4 * c + 3]) : "r"(p0), "r"(p1), "r"(__ldg(vr + 4 * c)));
    }
    if (pass == 0) { m0 = quad_max(m0); m1 = quad_max(m1); continue; }
    l0 = rcp(quad_sum(l0)); l1 = rcp(quad_sum(l1));
#pragma unroll
    for (int i = 0; i < 6; i++) {
      const float* v = o + 16 * (i >> 1) + 2 * (i & 1);
      const float r = i & 1 ? l1 : l0;
      io[(3 * (pass - 1) + (i >> 1)) * 512 + (i & 1) * 32] =
          make_uint4(pack_bf16(v[0] * r, v[1] * r), pack_bf16(v[4] * r, v[5] * r), pack_bf16(v[8] * r, v[9] * r), pack_bf16(v[12] * r, v[13] * r));
    }
  }
}

__device__ __forceinline__ constexpr int end_stage(int n) { return n < 4 ? n : n < 6 ? n - 4 : n == 6 ? 4 : n % 5; }
__device__ __forceinline__ constexpr int sent(int n) { return n < 8 ? 0 : n < 9 ? 3 : n < 11 ? 5 : n < 13 ? 8 : n < 16 ? 10 : n < 17 ? 14 : 15; }
template <int N> struct IntC { static constexpr int value = N; };
template <int N, int I = 0, class F> __device__ __forceinline__ void static_for(F&& f) { if constexpr (I < N) { f(IntC<I>{}); static_for<N, I + 1>(f); } }

extern __shared__ __align__(1024) uint8_t smem_raw[];
constexpr uint32_t EA = 160, EB = 184;
#define SMEM_LAYOUT                                                                                                          \
  [[maybe_unused]] const uint32_t sb = smem_u32(smem_raw), bar_a = sb + OFF_M, bar_b = bar_a + 40, bar_x = bar_a + 88,      \
      bar_u = bar_a + 96, bar_e = bar_a + 104, bar_o = bar_a + 200, bar_w = bar_a + 208, bar_c = bar_a + 216,                \
      bar_z = bar_a + 288, bar_s = bar_a + 296, bar_d = bar_a + 304, s_stat = bar_a + 512, s_sel = s_stat + 1024;

__device__ __forceinline__ int cluster_role() {
  uint32_t t, n;
  asm("mov.u32 %0, %%smid;" : "=r"(t)); asm("mov.u32 %0, %%nsmid;" : "=r"(n));
  t >>= 1;
  return n != 132 ? blockIdx.x >> 1 : t < 32 ? t : t < 60 ? t + 1 + (((t - 32) * 37) >> 8) : t < 62 ? t + 4 : (t - 58) * 8;
}

__device__ __forceinline__ int k_block(int t, int hg) {
  const int i = (t * 11) >> 5;
  return (((hg | 1) ^ (i & 1)) * 4 + (i >> 1)) * 6 + (t == 3 * i ? 4 : 2 * (t - 3 * i) - 2);
}

__device__ __noinline__ int errands(Scratch* s, const Maps& m, int qt, int hg, int warp, uint32_t tag, int budget) {
  SMEM_LAYOUT
  const int lane = threadIdx.x & 31, kq = hg >> 1, nh = hg & 1;
  if (warp == 1) {
#pragma unroll 1
    for (int u = 0; u < 5; u++) {
      mbar_wait(bar_o, u & 1);
      if (lane == 0) red_release(&s->flag[u ? FL_O + (qt * 8 + hg) * 8 : FL_XN + qt * 32]);
      __syncwarp();
    }
  } else if (warp == 2) {
    mbar_wait(bar_x, 0, budget);
    while ((int)(ld_acquire(&s->flag[FL_FFN]) - tag) < 0 && --budget >= 0) {}
    if (lane < 21) {
      const uint4 v = __ldcg(lane ? (const uint4*)(s->gsel + (lane > 10 ? DM - 80 : 0) + nh * 320 + kq * 80) + lane - 1 : (const uint4*)s->sel);
      asm volatile("st.shared.v4.u32 [%0], {%1,%2,%3,%4};" ::"r"(s_sel + 16 * lane), "r"(v.x), "r"(v.y), "r"(v.z), "r"(v.w) : "memory");
    }
    __syncwarp();
    if (lane == 0) { mbar_arrive(bar_u); asm volatile("red.relaxed.gpu.global.add.u64 [%0], 1;" ::"l"(&s->done) : "memory"); }
    while ((int)(ld_acquire(&s->flag[FL_RD + (qt * 8 + (hg ^ 1)) * 8]) - tag) < 0 && --budget >= 0) {}
    if (lane < 3) mbar_arrive(bar_z);
  } else {
    wait_flag(&s->flag[FL_XN + qt * 32], tag * 8);
    fence_proxy_async();
    mbar_wait(bar_a + EA + 32, 1);
    uint32_t a8 = 0, pha = 1;
    const int kb = (qt * 192 + k_block(lane, hg)) * 512;
#pragma unroll 1
    for (int n = 0; n < 54; n++) {
      const int t = n - 30, ko = __shfl_sync(~0u, kb, t);
      if (t == 0 || t == 18) {
        wait_flag(&s->flag[FL_O + (qt * 8 + (t ? 2 * kq + (lane & 1) : lane & 7)) * 8], tag * 4 - (t ? 0 : 1));
        fence_proxy_async();
      }
      mbar_wait(bar_a + EA + a8, pha);
      const uint32_t fb = bar_a + a8, dst = sb + a8 * (TA >> 3);
      if (elect()) {
        if (t >= 0) {
          mbar_expect_tx(fb, TA);
          bulk_load(dst, s->o + ko, TA, fb);
          if (t == 8) {
            mbar_expect_tx(bar_x, 6 * 3840);
#pragma unroll 1
            for (int e = 0; e < 6; e++) tma2d(sb + OFF_B + TW + e * TB, &m.xg, nh * 320 + kq * 80, qt * 128 + e * 24, bar_x);
            asm volatile("prefetch.tensormap [%0];\nprefetch.tensormap [%1];\nprefetch.tensormap [%2];\nprefetch.tensormap [%3];"
                         ::"l"(m.w3), "l"(m.w3 + 1), "l"(&m.xe), "l"(&m.out) : "memory");
          }
          if (t == 22) asm volatile("red.relaxed.gpu.global.add.u32 [%0], 1;" ::"l"(&s->flag[FL_RD + (qt * 8 + hg) * 8]) : "memory");
        } else if (n >= 10 && pha) mbar_arrive(fb);
        else { mbar_expect_tx(fb, TA); tma2d(dst, &m.xn, 8 * a8 + (pha || (n >= 15 && n < 20) ? 0 : 320), qt * 128, fb); }
      }
      a8 += 8; if (a8 == 40) { a8 = 0; pha ^= 1; }
    }
    if (lane < 3) mbar_arrive(bar_z);
  }
  return budget;
}

__global__ void __launch_bounds__(384, 1) __cluster_dims__(2, 1, 1)
fused_kernel(const Params p, const __grid_constant__ Maps m) {
  SMEM_LAYOUT
  const int wi = __shfl_sync(~0u, threadIdx.x >> 5, 0), wg = wi >> 2;
  const int lane = threadIdx.x & 31;
  const int cl = cluster_role();
  const int rank = blockIdx.x & 1;

  if (cl >= 64) {
    const unsigned epoch = (unsigned)(__ldcg(&p.s->done) >> 7);
    side_cta(p, 2 * cl + rank - 128, epoch, (float*)smem_raw);
    return;
  }
  const int qt = (cl & 7) * 2 + rank, hg = cl >> 3;
  const int kq = hg >> 1, nh = hg & 1;

  const int s0 = qt < 8 ? 0 : 5, kg0 = 10 * ((qt >> 1) & 3);
  if (elect()) {
    const int c = (int)(0x5ff7700000ull >> (4 * wi) & 15) + 1;
    for (int i = 0; i < 4; i++) mbar_init(bar_a + 32 * wi + 8 * i, c);
    asm volatile("fence.mbarrier_init.release.cluster;" ::: "memory");
  }
  __syncwarp();
  cluster_arrive();
  if (wi < 2 && elect()) {
    if (wi) { asm volatile("prefetch.tensormap [%0];" ::"l"(&m.wq) : "memory"); mbar_expect_tx(bar_b, TB); mbar_expect_tx(bar_b + 8, TB); }
    else for (int i = 0; i < 2; i++) { mbar_expect_tx(bar_a + 8 * i, TA); tma2d(sb + i * TA, &m.x, 64 * (s0 + i), qt * 128, bar_a + 8 * i); }
  }
  __syncwarp();
  cluster_wait();
  if (wi == 1 && elect())
    for (int i = 0; i < 2; i++) tma4d_mc(sb + OFF_B + i * TB + rank * (TB / 2), &m.wq, 12 * hg, 8 * (s0 + i) + 4 * rank, bar_b + 8 * i);
  if (wg > 0) {
    const int w = wg - 1;
    const int cw = wi - 4;
    asm volatile("setmaxnreg.inc.sync.aligned.u32 232;");
    uint32_t fr[48];
    reg_fence(fr);
    auto ln_row = [&]() { int v = qt * 128 + hg * 16 + cw * 2 + (lane >> 4); asm volatile("" : "+r"(v)); return v; };
    uint32_t rel_addr;
    asm volatile("mapa.shared::cluster.u32 %0, %1, %2;" : "=r"(rel_addr) : "r"(bar_b + EB), "r"(lane & 1));
    auto rel_a = [&](uint32_t o8) { if (lane == 0) mbar_arrive(bar_a + EA + o8); };
    auto rel_b = [&](uint32_t o8) { if (lane < 2) mbar_arrive_cluster(rel_addr + o8); };
    uint32_t b8 = 0, phb = 0;
    auto next_pair = [&]() { b8 += 16; if (b8 == 48) { b8 = 0; phb ^= 1; } };
    const int g = lane >> 2, q = lane & 3;
    constexpr uint64_t HI_A = desc_hi(16, 1024, 1);
    constexpr uint64_t HI_W = desc_hi(1024, 3072, 1);
    constexpr uint64_t HI_O = desc_hi(2048, 512, 2);
    if (w == 1) asm volatile("bar.arrive 1, 256;" ::: "memory");

    uint32_t zero; asm volatile("mov.u32 %0, %%tid.y;" : "=r"(zero));
    float acc[96];
    uint4* optr = p.s->o + (size_t)(qt * 192 + hg * 24) * 512 + (cw * 16 + g) * 4 + (q ^ ((g >> 1) & 3));
    uint32_t rl[4];
    auto store_o = [&](int pp) {
#pragma unroll
      for (int i = (12 * pp + 8) / 9; i < (12 * (pp + 1) + 8) / 9; i++) {
#pragma unroll
        for (int k = 4 * i; k < 4 * i + 4; k++)
          asm volatile("{\n.reg .b32 t;\nmul.rn.bf16x2 t, %0, %2;\nfma.rn.bf16x2 %0, %0, %1, t;\n}\n" : "+r"(fr[k]) : "r"(rl[i & 1]), "r"(rl[2 + (i & 1)]));
        fr[4 * i] &= ~1u;
        optr[(i >> 1) * 512 + (i & 1) * 32] = make_uint4(fr[4 * i], fr[4 * i + 1], fr[4 * i + 2], fr[4 * i + 3]);
      }
      if (pp == 8) optr += 6 * 512;
    };
    auto fresh = [&]() { uint32_t v = sb; asm volatile("" : "+r"(v)); return v; };
    reg_fence(rl);

#pragma unroll 1
    for (int u = 0; u < 4; u++) {
      const uint32_t sq = fresh();
      const uint64_t dA = mkdesc(sq + w * 8192, HI_A), dB0 = mkdesc(sq + OFF_B, HI_W);
      uint32_t pb8 = 0;
#pragma unroll
      for (int s = 0; s < 10; s++) {
        const uint32_t o8 = b8 + 8 * (s & 1);
        const uint64_t dW = dB0 + o8 * (TB >> 7);
        mbar_wait(bar_a + 8 * (s % 5), s / 5);
        mbar_wait(bar_b + o8, phb);
        if (s == 9 || (s >= LS && u == 0)) asm volatile("bar.sync %0, 256;" ::"r"(1 + w) : "memory");
        WG_FENCE();
#pragma unroll
        for (int kk = 0; kk < 4; kk++) wg_ss192t(acc, dA + ((s % 5) * (TA >> 4) + kk * 2), dW + kk * 384, kk != 0 || s != 0);
        WG_COMMIT();
        if (s >= LS && (s == 9) == (u > 0)) asm volatile("bar.arrive %0, 256;" ::"r"(2 - w) : "memory");
        if (s > 0) { WG_WAIT(1); rel_a(8 * ((s - 1) % 5)); rel_b(pb8); }
        if (s < 9) {
          if (u > 0) store_o(s);
          else { if (s == 6 && lane == 0) mbar_arrive(bar_c); ln_piece(p, fr, s, ln_row(), lane & 15); }
        }
        if (s == 8) { __syncwarp(); if (lane == 0) mbar_arrive(bar_o); }
        pb8 = o8;
        if (s & 1) next_pair();
      }
      if (u == 0) {
        mbar_wait(bar_s, 0);
        const uint2 s0 = lds64(s_stat + (cw * 16 + g) * 8), s1 = lds64(s_stat + 64 + (cw * 16 + g) * 8);
        const uint32_t msk = q == 0 ? 0xffffffffu : q == 1 ? 0xffffu : 0u;
        const float c0 = SM_C * __uint_as_float(s0.y), c1 = SM_C * __uint_as_float(s1.y);
        uint32_t am[4] = {(s0.x ^ 0x80008000u) & msk, (s1.x ^ 0x80008000u) & msk, 0, 0};
        reg_fence(am);
        WG_FENCE();
        wg_rs192t(acc, am[0], am[1], am[2], am[3], mkdesc(sb, desc_hi(1024, 0, 1)), 1);
        WG_COMMIT();
        asm volatile("bar.arrive %0, 256;" ::"r"(2 - w) : "memory");
        WG_WAIT(0);
        reg_fence(acc);
#pragma unroll
        for (int i = 0; i < 24; i++) { acc[4 * i] *= c0; acc[4 * i + 1] *= c0; acc[4 * i + 2] *= c1; acc[4 * i + 3] *= c1; }
      } else { WG_WAIT(0); reg_fence(acc); }
      rel_b(pb8);
      rel_a(32);
#pragma unroll
      for (int i = 0; i < 48; i++) fr[i] = pack_bf16(acc[2 * i], acc[2 * i + 1]);
      reg_fence(fr);
      float sc[32], l0 = 0.f, l1 = 0.f;
      uint32_t pf[16], k8;
      auto pack_p = [&](const float (&s_)[32], int from = 0, int to = 16) {
#pragma unroll
        for (int i = from; i < to; i++) pf[i] = pack_bf16(s_[2 * i], s_[2 * i + 1]);
      };
      auto scores = [&](int j, int pass = 11) {
        k8 = b8 + 8;
        mbar_wait(bar_b + k8, phb);
        next_pair();
        mbar_wait(bar_b + b8, phb);
        const uint64_t dk = mkdesc(sb + OFF_B, HI_W) + k8 * (TB >> 7);
        asm volatile("bar.sync %0, 256;" ::"r"(1 + w) : "memory");
        WG_FENCE();
#pragma unroll
        for (int t = 0; t < 12; t++) {
          wg_rs64(sc, fr[4 * t], fr[4 * t + 1], fr[4 * t + 2], fr[4 * t + 3], dk + (t >> 2) * 64 + (t & 3) * 2, t != 0);
          if (t == 11) WG_COMMIT();
          if (t == pass) asm volatile("bar.arrive %0, 256;" ::"r"(2 - w) : "memory");
        }
      };
      auto pv = [&](int add) {
        const uint64_t dv = mkdesc(sb + OFF_B, HI_W) + b8 * (TB >> 7);
#pragma unroll
        for (int kk = 0; kk < 4; kk++) wg_rs192t(acc, pf[4 * kk], pf[4 * kk + 1], pf[4 * kk + 2], pf[4 * kk + 3], dv + kk * 384, kk != 0 || add);
        WG_COMMIT();
      };
      auto finish = [&]() {
        WG_WAIT(1);
        reg_fence(sc);
        exp_block(sc, l0, l1);
        rel_b(k8 + (__float_as_uint(l0) & __float_as_uint(l1) & zero));
        WG_WAIT(0);
        reg_fence(acc); reg_fence(pf);
        rel_b(b8);
        pack_p(sc);
      };
      {
        mbar_wait(bar_b + b8, phb);
        const uint64_t dk = mkdesc(sb + OFF_B, HI_W) + b8 * (TB >> 7);
        asm volatile("bar.sync %0, 256;" ::"r"(1 + w) : "memory");
#pragma unroll
        for (int t = 0; t < 12; t++) {
          if (t == 0) WG_FENCE();
          wg_rs64(sc, fr[4 * t], fr[4 * t + 1], fr[4 * t + 2], fr[4 * t + 3], dk + (t >> 2) * 64 + (t & 3) * 2, t != 0);
          if (t == 7) asm volatile("bar.arrive %0, 256;" ::"r"(2 - w) : "memory");
        }
        WG_COMMIT();
        WG_WAIT(0);
        reg_fence(sc);
        constexpr int NE = 8;
        float s0[32];
#pragma unroll
        for (int i = 0; i < 32; i++) s0[i] = i < NE ? sc[i] : __uint_as_float(__float_as_uint(sc[i]) ^ zero);
        exp_block(s0, l0, l1, 0, NE);
        pack_p(s0, 0, NE / 2);
#pragma unroll
        for (int i = NE; i < 32; i++) asm volatile("" : "+f"(s0[i])::"memory");
#pragma unroll
        for (int i = 0; i < NE / 2; i++) asm volatile("" : "+r"(pf[i])::"memory");
        rel_b(b8);
        scores(1, 8);
        const uint32_t z = lds32(s_stat) & zero;
#pragma unroll
        for (int i = NE; i < 32; i++) {
          asm("{\n.reg .pred p;\nsetp.eq.u32 p, %1, 0;\n@p ex2.approx.ftz.f32 %0, %0;\n}\n" : "+f"(s0[i]) : "r"(z));
          if (i & 2) l1 += s0[i]; else l0 += s0[i];
        }
        pack_p(s0, NE / 2, 16);
        reg_fence(pf);
        WG_FENCE();
        pv(0);
        finish();
      }
#pragma unroll 1
      for (int j = 2; j < 8; j++) { scores(j); pv(1); finish(); }
      const uint32_t v8 = b8 + 8;
      mbar_wait(bar_b + v8, phb);
      next_pair();
      {
        const uint64_t dv = mkdesc(sb + OFF_B, HI_W) + v8 * (TB >> 7);
        asm volatile("bar.sync %0, 256;" ::"r"(1 + w) : "memory");
        WG_FENCE();
#pragma unroll
        for (int kk = 0; kk < 4; kk++) {
          wg_rs192t(acc, pf[4 * kk], pf[4 * kk + 1], pf[4 * kk + 2], pf[4 * kk + 3], dv + kk * 384, 1);
          if (kk == 1 && (u < 3 || w == 0)) asm volatile("bar.arrive %0, 256;" ::"r"(2 - w) : "memory");
        }
        WG_COMMIT();
      }
      l0 = quad_sum(l0); l1 = quad_sum(l1);
      const bool unsafe = __any_sync(~0u, !(l0 >= SM_LO && l1 >= SM_LO && l0 + l1 <= SM_HI));
      l0 = rcp(l0); l1 = rcp(l1);
      rl[0] = pack_bf16(l0, l0); rl[1] = pack_bf16(l1, l1);
      l0 -= bf_lo(rl[0]); l1 -= bf_lo(rl[1]);
      rl[2] = pack_bf16(l0, l0); rl[3] = pack_bf16(l1, l1);
      WG_WAIT(0);
      reg_fence(acc);
      rel_b(v8);
      if (__builtin_expect(unsafe, 0)) {
        int o = hg * 4 + u; asm volatile("" : "+r"(o));
        o = (o * SKC + (SKC - WIN) + g) * (DH / 2) + q;
#pragma unroll
        for (int i = 0; i < 12; i++) optr[(i >> 1) * 512 + (i & 1) * 32] = make_uint4(fr[4 * i], fr[4 * i + 1], fr[4 * i + 2], fr[4 * i + 3]);
        safe_head((const uint32_t*)p.k + o, (const uint32_t*)p.v + o, optr);
#pragma unroll
        for (int i = 0; i < 12; i++) { const uint4 v = optr[(i >> 1) * 512 + (i & 1) * 32]; fr[4 * i] = v.x; fr[4 * i + 1] = v.y; fr[4 * i + 2] = v.z; fr[4 * i + 3] = v.w; }
        rl[0] = rl[1] = 0x3f803f80u; rl[2] = rl[3] = 0;
      } else {
#pragma unroll
        for (int i = 0; i < 24; i++) {
          fr[8 * (i >> 2) + (i & 3)] = pack_bf16(acc[4 * i], acc[4 * i + 1]);
          fr[8 * (i >> 2) + 4 + (i & 3)] = pack_bf16(acc[4 * i + 2], acc[4 * i + 3]);
        }
      }
    }

    float aF[80], aS[80];
    uint32_t pha = 0, a8 = 0, pa8 = 0, pb8 = 0;
#pragma unroll 1
    for (int s = 0; s < 19; s++) {
      const uint64_t d0 = mkdesc(sb, HI_O), dO = d0 + (a8 * (TA >> 7) + w * 256), dB = d0 + ((OFF_B >> 4) + b8 * (TB >> 7));
      mbar_wait(bar_a + a8, pha);
      mbar_wait(bar_b + b8, phb);
      WG_FENCE();
#pragma unroll
      for (int kk = 0; kk < 4; kk++) wg_ss160t(aF, dO + ((kk >> 1) * 512 + (kk & 1) * 2), dB + ((kk >> 1) * 640 + (kk & 1) * 64), kk != 0 || s != 0);
      WG_COMMIT();
      mbar_wait(bar_b + b8 + 8, phb);
      WG_WAIT(1);
      if (s > 0) { rel_a(pa8); rel_b(pb8 + 8); }
      WG_FENCE();
#pragma unroll
      for (int kk = 0; kk < 4; kk++) wg_ss160t(aS, dO + ((kk >> 1) * 512 + (kk & 1) * 2), dB + ((TB >> 4) + (kk >> 1) * 640 + (kk & 1) * 64), kk != 0 || s != 0);
      WG_COMMIT();
      if (s < 9) {
#pragma unroll
        for (int pp = 0; pp < 9; pp++) if (s == pp) store_o(pp);
        if (s == 8) { __syncwarp(); if (lane == 0) mbar_arrive(bar_o); }
      } else if (s < 15) {
        const int b = 2 * cw + ((lane >> 3) & 1);
        uint32_t ga = sb + OFF_B + TW + ((b * 11) >> 5) * (TB - 3840) + b * 1280 + (lane & 7) * 160 + (lane >> 4) * 16;
        if (s < 14) {
          mbar_wait(bar_x, 0);
          ga += 32 * (s - 9);
          ldsm4(ga, fr);
#pragma unroll
          for (int i = 0; i < 4; i++) {
            const uint2 st = lds64(s_stat + (cw * 16 + g + 8 * (i & 1)) * 8);
            const uint32_t d = hsub2(fr[i], st.x), xn = pack_bf16(bf_lo(d) * __uint_as_float(st.y), bf_hi(d) * __uint_as_float(st.y));
            fr[i] = pack_bf16(silu_f(bf_lo(xn)), silu_f(bf_hi(xn)));
          }
          stsm4(ga, fr);
        } else {
          mbar_wait(bar_u, 0);
          const uint2 sel = lds64(s_sel);
          const uint32_t row = qt * 128 + cw * 16 + (lane & 15);
          if (row == sel.x || row == sel.y) ga = s_sel + 16 + (row == sel.y ? 160 : 0) + (lane >> 4) * 16;
#pragma unroll
          for (int k = 0; k < 5; k++) ldsm4(ga + 32 * k, fr + 4 * k);
        }
      }
      WG_WAIT(1);
      rel_b(b8);
      pa8 = a8; a8 += 8; if (a8 == 40) { a8 = 0; pha ^= 1; }
      pb8 = b8; next_pair();
    }
    const int t128 = threadIdx.x & 127;
    uint4* const xbase = p.s->o + (size_t)(qt * 192 + nh * 24 + 10) * 512 + w * 640 + t128;
    uint4* const dst = xbase + kq * (48 * 512);
    float q1[40], q2[40], oth[40], own[40];
    auto take = [&](float (&x)[40], const float* a, uint32_t z) {
#pragma unroll
      for (int k = 0; k < 40; k++) x[k] = __uint_as_float(__float_as_uint(a[k]) ^ z);
      reg_fence(x);
    };
    reg_fence(aF);
    take(q1, aF, zero);
    auto fa = [&](int i) { return mbar_try(bar_a + 8 * ((4 + i) % 5), i == 0); };
    auto fb = [&](int e) { return mbar_try(bar_b + 8 * (e % 6), (e / 6) & 1); };
    auto send = [&](int m) {
      const float* v = (m < 5 ? q1 : m < 10 ? q2 : oth) + 8 * (m % 5);
      st_pkt(dst + (m / 5) * 1280 + (m % 5) * 128, pack_bf16(v[0], v[1]) | 1, pack_bf16(v[2], v[3]), pack_bf16(v[4], v[5]), pack_bf16(v[6], v[7]));
    };
    static_for<20>([&](auto n_) {
      constexpr int n = n_.value, i = end_stage(n), e = 142 + n / 2, qi = n == 4 ? 1 : n == 6 ? 0 : n / 5;
      float (&acc_)[40] = qi == 0 ? q1 : qi == 1 ? q2 : qi == 2 ? oth : own;
      if (n == 0) while (!(fa(0) & fa(1) & fb(142) & fb(143))) {}
      if (n == 2) while (!(fa(2) & fa(3) & fb(144))) {}
      if (n == 6) while (!(fa(4) & fb(145) & fb(146) & mbar_try(bar_z, 0))) {}
      if (n == 10) while (!(fb(147) & fb(148) & fb(149))) {}
      const uint64_t d0 = mkdesc(fresh(), HI_O), dw = d0 + w * 256;
      WG_FENCE();
#pragma unroll
      for (int kk = 0; kk < 4; kk++)
        wg_ss80t(acc_, dw + (((4 + i) % 5) * (TA >> 4) + (kk >> 1) * 512 + (kk & 1) * 2),
                 d0 + ((OFF_B >> 4) + (e % 6) * (TB >> 4) + (n & 1) * 768 + (kk >> 1) * 384 + (kk & 1) * 64), 1);
      WG_COMMIT();
      if ((!(n & 1) && n <= 16) || n == 15 || n == 7) WG_WAIT(1);
      if (n == 0) rel_a(24);
      if (!(n & 1) && n <= 8) rel_b(8 * ((e - 1) % 6));
      if (n == 0) take(q2, aF + 40, lds32(s_stat) & zero);
      if (n == 10 || n == 12 || n == 14 || n == 16) rel_a(4u * n - 40);
      if (n == 7) reg_fence(q1);
      if (n == 10) reg_fence(q2);
      if (n == 15) reg_fence(oth);
      if (n == 14 || n == 17) while (!fb(n == 14 ? 150 : 151)) {}
      static_for<sent(n + 1) - sent(n)>([&](auto k_) { send(sent(n) + k_.value); });
      if (n == 8) {
        reg_fence(aS);
#pragma unroll
        for (int k = 0; k < 40; k++) oth[k] = kq & 1 ? aS[k] : aS[40 + k];
        reg_fence(oth);
      }
      if (n == 10) {
        reg_fence(aS);
        const bool odd = (kq ^ (lds32(s_stat) & zero)) & 1;
#pragma unroll
        for (int k = 0; k < 40; k++) own[k] = odd ? aS[40 + k] : aS[k];
        reg_fence(own);
      }
    });
    {
      auto poll = [&](int e, uint4 (&v)[5]) {
#pragma unroll
        for (int i = 0; i < 5; i++) v[i] = ld_pkt(xbase + (kq ^ (e < 2 ? 2 + e : 1)) * (48 * 512) + (e < 2 ? kq & 1 : 2) * 1280 + i * 128);
      };
      auto check = [&](int e, uint4 (&v)[5]) {
        auto tags = [&]() { uint32_t t; asm("{\n.reg .b32 t;\nlop3.b32 t, %1, %2, %3, 0x80;\nlop3.b32 %0, t, %4, %5, 0x80;\n}\n" : "=r"(t) : "r"(v[0].x), "r"(v[1].x), "r"(v[2].x), "r"(v[3].x), "r"(v[4].x)); return t & 1; };
        while (!__all_sync(~0u, tags())) poll(e, v);
      };
      auto add = [&](const uint4 (&v)[5]) {
#pragma unroll
        for (int i = 0; i < 5; i++) {
          float* o = own + 8 * i;
          o[0] += bf_lo(v[i].x); o[1] += bf_hi(v[i].x); o[2] += bf_lo(v[i].y); o[3] += bf_hi(v[i].y);
          o[4] += bf_lo(v[i].z); o[5] += bf_hi(v[i].z); o[6] += bf_lo(v[i].w); o[7] += bf_hi(v[i].w);
        }
      };
      uint4 v[2][5];
#pragma unroll
      for (int e = 0; e < 2; e++) {
        mbar_wait(bar_e + 16 * e + 8 * w, 0);
#pragma unroll
        for (int i = 0; i < 5; i++) v[e][i] = lds128(sb + OFF_B + (2 + e) * TB + (w * 640 + i * 128 + t128) * 16);
      }
      check(0, v[0]); check(1, v[1]);
#pragma unroll
      for (int i = 0; i < 5; i++) v[0][i] = make_uint4(hadd2(v[0][i].x, v[1][i].x), hadd2(v[0][i].y, v[1][i].y), hadd2(v[0][i].z, v[1][i].z), hadd2(v[0][i].w, v[1][i].w));
      uint32_t xr[20];
      const uint32_t xs = sb + OFF_B + 4 * TB + cw * 2560, xa = xs + (lane & 15) * 160 + (lane >> 4) * 16;
      mbar_wait(bar_e + 32, 0);
#pragma unroll
      for (int k = 0; k < 5; k++) ldsm4(xa + 32 * k, xr + 4 * k);
      WG_WAIT(0);
      reg_fence(own);
      poll(2, v[1]);
      add(v[0]);
      reg_fence(own);
      check(2, v[1]); add(v[1]);
      if (lane == 0) mbar_arrive(bar_w);
      cluster_arrive();
#pragma unroll
      for (int i = 0; i < 20; i++) xr[i] = hadd2(xr[i], hmul2(pack_bf16(own[2 * i], own[2 * i + 1]), fr[i]));
#pragma unroll
      for (int k = 0; k < 5; k++) stsm4(xa + 32 * k, xr + 4 * k);
      asm volatile("fence.proxy.async.shared::cta;" ::: "memory");
      __syncwarp();
      if (elect()) {
        tma2d_store(&m.out, xs, nh * 320 + kq * 80, qt * 128 + cw * 16);
        asm volatile("cp.async.bulk.commit_group;\ncp.async.bulk.wait_group.read 0;" ::: "memory");
      }
      __syncwarp();
    }
    cluster_wait();
  } else {
    asm volatile("setmaxnreg.dec.sync.aligned.u32 40;");
    uint32_t tid_; asm volatile("mov.u32 %0, %%tid.x;" : "=r"(tid_));
    const int warp = __shfl_sync(~0u, tid_ >> 5, 0);
    auto is_warp = [&](int k) { uint32_t e; asm volatile("{\n.reg .pred q;\nsetp.eq.u32 q, %1, %2;\nselp.u32 %0, 1, 0, q;\n}" : "=r"(e) : "r"(warp), "r"(k)); return e != 0; };
    if (warp > 0) {
      const unsigned epoch = (unsigned)(__ldcg(&p.s->done) >> 7);
      int budget = WAIT_BUDGET;
      const uint32_t tag = epoch + 1;
      mbar_wait(bar_b + (kg0 & ~7), 0, budget); mbar_wait(bar_b + (kg0 & ~7) + 8, 0, budget);
      float cs0 = 0.f, cs1 = 0.f;
      const int n = rank * 96 + (warp - 1) * 32;
#pragma unroll 1
      for (int kg = kg0 + (lane >> 4) * 5, e = kg + 5; kg < e; kg++) {
        const uint32_t ad = sb + OFF_B + kg * 3072 + (n >> 6) * 1024 + (n & 63) * 2 + (lane & 15) * 4;
#pragma unroll
        for (int k = 0; k < 8; k++) { const uint32_t v = lds32(ad ^ (k * 0x90)); cs0 += bf_lo(v); cs1 += bf_hi(v); }
      }
      cs0 += __shfl_xor_sync(~0u, cs0, 16); cs1 += __shfl_xor_sync(~0u, cs1, 16);
      if (lane < 16) st_pkt8((uint2*)(p.s->cs + (hg * 4 + (qt >> 2)) * 96 + (n >> 1) + lane) + ((qt >> 1) & 1), (__float_as_uint(cs0) & ~3u) | (tag & 3), __float_as_uint(cs1));
      if (lane < 2) { uint32_t a; asm volatile("mapa.shared::cluster.u32 %0, %1, %2;" : "=r"(a) : "r"(bar_d), "r"(lane)); mbar_arrive_cluster(a); }
      mbar_wait(bar_c, 0, budget);
      uint4 v[5];
      while (true) {
        uint32_t bad = 0;
#pragma unroll
        for (int i = 0; i < 5; i++) v[i] = ld_pkt(i < 4 ? p.s->cs + (hg * 4 + i) * 96 + (tid_ - 32) : (const uint4*)p.s->stat + qt * 64 + (tid_ & 63));
#pragma unroll
        for (int i = 0; i < 5; i++) bad |= (v[i].x ^ tag) | (v[i].z ^ tag);
        if (!__any_sync(~0u, bad & 3) || --budget < 0) break;
      }
      asm volatile("st.shared.v4.u32 [%0], {%1,%2,%3,%4};" ::"r"(s_stat + (tid_ & 63) * 16), "r"(__byte_perm(v[4].x, 0, 0x3232)), "r"(v[4].y), "r"(__byte_perm(v[4].z, 0, 0x3232)), "r"(v[4].w) : "memory");
      cs0 = cs1 = 0.f;
#pragma unroll
      for (int i = 0; i < 4; i++) { cs0 += __uint_as_float(v[i].x & ~3u) + __uint_as_float(v[i].z & ~3u); cs1 += __uint_as_float(v[i].y) + __uint_as_float(v[i].w); }
#pragma unroll
      for (int k = 0; k < 8; k++) {
        const uint32_t t = k < 3 ? pack_bf16(cs0, cs1) : 0;
        sts32((sb + (warp - 1) * 1024 + lane * 4) ^ (k * 0x90), t);
        cs0 -= bf_lo(t); cs1 -= bf_hi(t);
      }
      asm volatile("fence.proxy.async.shared::cta;" ::: "memory");
      __syncwarp();
      if (lane < 2) mbar_arrive(bar_s);
      budget = errands(p.s, m, qt, hg, warp, tag, budget);
      if (is_warp(2)) {
        mbar_wait(bar_w, 0, budget);
        if (budget < 0) asm volatile("st.global.u32 [%0], %1;" ::"l"(0ull), "r"(budget) : "memory");
      }
    } else {
      uint32_t fb = bar_b + 16, dst = sb + OFF_B + 2 * TB, ph = 1;
      auto next = [&]() { fb += 8; dst += TB; if (fb == bar_b + 48) { fb = bar_b; dst = sb + OFF_B; ph ^= 1; } };
#pragma unroll 1
      for (int u = 0; u < 4; u++) {
        const int h = hg * 4 + u;
        int s = u ? (u == 2 ? 5 : 0) : s0 + 2;
#pragma unroll 1
        for (int i = u ? 0 : 2; i < 10; i++) {
          if (u == 0) {
            const uint32_t a8 = 8 * (i < 5 ? i : i - 5);
            mbar_wait(bar_a + 8 * (i < 7 ? i - 2 : i - 7), i >= 7);
            mbar_wait(bar_a + EA + a8, i < 5);
            if (elect()) { mbar_expect_tx(bar_a + a8, TA); tma2d(sb + a8 * (TA >> 3), &m.x, 64 * s, qt * 128, bar_a + a8); }
            if (i == 6 + (kg0 >> 3)) mbar_wait(bar_d, 0);
          }
          mbar_wait(fb + EB, ph);
          if (elect()) { mbar_expect_tx(fb, TB); tma4d_mc(dst + rank * (TB / 2), &m.wq, 3 * h, 8 * s + 4 * rank, fb); }
          next();
          if (++s == 10) s = 0;
        }
        const int kv0 = (h * SKC + (SKC - WIN)) / 8 + 4 * rank;
#pragma unroll 1
        for (int i = 0; i < 16; i++) {
          const bool isk = (0x2AAB >> i) & 1;
          mbar_wait(fb + EB, ph);
          if (elect()) { mbar_expect_tx(fb, TB); tma4d_mc(dst + rank * (TB / 2), isk ? &m.k : &m.v, 0, kv0 + 8 * (isk ? (i + 1) >> 1 : (i - 1) >> 1), fb); }
          next();
        }
      }
      const int cF = 10 * nh + 5 - 5 * (kq >> 1), cS = 10 * nh + 5 * (kq >> 1);
      const int kb = 4 * (k_block(lane, hg) + rank);
#pragma unroll 1
      for (int n = 0; n < 38; n++) {
        const int c2 = __shfl_sync(~0u, kb, n >> 1);
        mbar_wait(fb + EB, ph);
        if (elect()) { mbar_expect_tx(fb, TW); tma5d_mc(dst + rank * (TW / 2), &m.wo, c2, n & 1 ? cS : cF, fb); }
        next();
      }
      const int odd = ((0x7fb0 ^ (kq & 1 ? 0xffc00 : 0)) >> lane) & 1;
      const int tq = __shfl_sync(~0u, kb, 19 + end_stage(lane)) << 16 | odd << 7 | ((lane < 10 ? cF : cS) + 2 * odd);
#pragma unroll 1
      for (int n = 0; n < 20; n += 2) {
        const int t0 = __shfl_sync(~0u, tq, n), t1 = __shfl_sync(~0u, tq, n + 1);
        mbar_wait(fb + EB, ph);
        if (elect()) {
          mbar_expect_tx(fb, TB);
          tma5d_mc(dst + rank * (TB / 4), (const CUtensorMap*)((const char*)m.w3 + (t0 & 128)), t0 >> 16, t0 & 31, fb);
          tma5d_mc(dst + TB / 2 + rank * (TB / 4), (const CUtensorMap*)((const char*)m.w3 + (t1 & 128)), t1 >> 16, t1 & 31, fb);
        }
        next();
      }
      mbar_wait(bar_a + EA + 16, 0);
      if (elect()) { mbar_expect_tx(bar_e + 32, TW); tma2d(sb + OFF_B + 4 * TB, &m.xe, nh * 320 + kq * 80, qt * 128, bar_e + 32); }
    }
    if (warp & 1) {
      const int e = warp >> 1, ms = 2 * e + ((lane >> 2) & 1);
      const uint4* src = p.s->o + (size_t)(qt * 192 + nh * 24 + 10 + (kq ^ (2 + e)) * 48) * 512 + (kq & 1) * 1280 + (ms & 1) * 640;
      uint32_t todo = 0xff;
      bool ok = lane >= 8;
      mbar_wait(bar_z, 0);
#pragma unroll 1
      while (todo) {
        if (!ok) ok = ld_pkt(src + 4 * 128 + (lane & 3) * 32 + 31).x & 1;
        const uint32_t got = __ballot_sync(~0u, ok) & todo, go = __ballot_sync(~0u, ((got >> (lane & 28)) & 15) == 15);
        if (go) mbar_wait(bar_a + EA + 8 * e, 0);
        if ((go & 0x11) >> lane & 1) {
          mbar_expect_tx(bar_e + 8 * ms, TW / 2); bulk_load(sb + OFF_B + (2 + e) * TB + (ms & 1) * (TW / 2), src, TW / 2, bar_e + 8 * ms);
        }
        todo &= ~go;
      }
    }
    cluster_sync();
  }
}

typedef CUresult (*EncodeFn)(CUtensorMap*, CUtensorMapDataType, cuuint32_t, void*, const cuuint64_t*, const cuuint64_t*,
                             const cuuint32_t*, const cuuint32_t*, CUtensorMapInterleave, CUtensorMapSwizzle,
                             CUtensorMapL2promotion, CUtensorMapFloatOOBfill);

void encode(EncodeFn fn, CUtensorMap* tm, void* base, int rank, const cuuint64_t* dims, const cuuint64_t* strides,
            const cuuint32_t* box, CUtensorMapSwizzle sw) {
  const cuuint32_t es[5] = {1, 1, 1, 1, 1};
  fn(tm, CU_TENSOR_MAP_DATA_TYPE_BFLOAT16, rank, base, dims, strides, box, es, CU_TENSOR_MAP_INTERLEAVE_NONE, sw,
     CU_TENSOR_MAP_L2_PROMOTION_L2_128B, CU_TENSOR_MAP_FLOAT_OOB_FILL_NONE);
}

}

extern "C" void kernel_launch(void* const* d_in, const int* in_sizes, int n_in, void* d_out, int out_size) {
  static EncodeFn fn = nullptr;
  static Scratch* scr = nullptr;
  if (!fn) {
    void* f = nullptr;
    cudaDriverEntryPointQueryResult st;
    cudaGetDriverEntryPoint("cuTensorMapEncodeTiled", &f, cudaEnableDefault, &st);
    fn = (EncodeFn)f;
    cudaGetSymbolAddress((void**)&scr, g_scratch);
    cudaFuncSetAttribute(fused_kernel, cudaFuncAttributeMaxDynamicSharedMemorySize, SMEM_BYTES);
  }
  Maps m;
  { const cuuint64_t d[2] = {DM, SQ}, s[1] = {DM * 2}; const cuuint32_t b[2] = {64, 128};
    encode(fn, &m.x, d_in[0], 2, d, s, b, CU_TENSOR_MAP_SWIZZLE_128B);
    encode(fn, &m.xn, scr->xn, 2, d, s, b, CU_TENSOR_MAP_SWIZZLE_128B); }
  { const cuuint64_t d[4] = {64, 8, QD / 64, DM / 8}, s[3] = {QD * 2, 128, 8 * QD * 2}; const cuuint32_t b[4] = {64, 8, 3, 4};
    encode(fn, &m.wq, d_in[3], 4, d, s, b, CU_TENSOR_MAP_SWIZZLE_128B); }
  { const cuuint64_t d[4] = {64, 8, 3, NH * SKC / 8}, s[3] = {DH * 2, 128, 8 * DH * 2}; const cuuint32_t b[4] = {64, 8, 3, 4};
    encode(fn, &m.k, d_in[1], 4, d, s, b, CU_TENSOR_MAP_SWIZZLE_128B);
    encode(fn, &m.v, d_in[2], 4, d, s, b, CU_TENSOR_MAP_SWIZZLE_128B); }
  {
    const cuuint64_t d[5] = {32, 2, QD / 8, 4, DM / 32}, s[4] = {DM * 2, 8 * DM * 2, 2 * DM * 2, 64}; const cuuint32_t b[5] = {32, 2, 4, 4, 5};
    encode(fn, &m.wo, d_in[4], 5, d, s, b, CU_TENSOR_MAP_SWIZZLE_64B);
    const cuuint32_t b3[5] = {32, 2, 4, 4, 3};
    encode(fn, &m.w3[0], d_in[4], 5, d, s, b3, CU_TENSOR_MAP_SWIZZLE_64B);
    encode(fn, &m.w3[1], (char*)d_in[4] + 32, 5, d, s, b3, CU_TENSOR_MAP_SWIZZLE_64B); }
  { const cuuint64_t d[2] = {DM, SQ}, s[1] = {DM * 2}; const cuuint32_t bg[2] = {80, 24}, bx[2] = {80, 128}, bo[2] = {80, 16};
    encode(fn, &m.xg, d_in[0], 2, d, s, bg, CU_TENSOR_MAP_SWIZZLE_NONE);
    encode(fn, &m.xe, d_in[0], 2, d, s, bx, CU_TENSOR_MAP_SWIZZLE_NONE);
    encode(fn, &m.out, d_out, 2, d, s, bo, CU_TENSOR_MAP_SWIZZLE_NONE); }
  Params p;
  p.x = (const __nv_bfloat16*)d_in[0]; p.wr = (const __nv_bfloat16*)d_in[6]; p.wg = (const __nv_bfloat16*)d_in[7];
  p.wu = (const __nv_bfloat16*)d_in[8]; p.wd = (const __nv_bfloat16*)d_in[9];

  p.k = (const __nv_bfloat16*)d_in[1]; p.v = (const __nv_bfloat16*)d_in[2]; p.s = scr;
  cudaLaunchConfig_t cfg = {};
  cfg.gridDim = dim3(132); cfg.blockDim = dim3(384); cfg.dynamicSmemBytes = SMEM_BYTES; cfg.stream = cudaStreamPerThread;
  cudaLaunchKernelEx(&cfg, fused_kernel, p, m);
}
```

```cpp
#include <cuda_runtime.h>
#include <cuda_bf16.h>
#include <cuda.h>
#include <stdint.h>

namespace {

constexpr int SQ = 2048, DM = 640, NH = 32, DH = 192, SKC = 2048, WIN = 512, FF = 1536;
constexpr int QD = NH * DH;
constexpr uint32_t TA = 16384, TB = 24576, TW = 20480, OFF_B = 5 * TA, OFF_M = OFF_B + 6 * TB, SMEM_BYTES = OFF_M + 3072;
constexpr int WAIT_BUDGET = 1 << 20;

constexpr int FL_XN = 0;
constexpr int FL_O = 512;
constexpr int FL_RD = FL_O + 1024;
constexpr int FL_FFN = FL_RD + 1024;
constexpr int FL_SIDE = FL_FFN + 32;
struct __align__(1024) Scratch {
  unsigned long long done, pad0[15];
  unsigned flag[FL_SIDE + 32];
  uint4 cand[8];
  float ffn[4 * 2 * DM];
  int sel[4];
  __nv_bfloat16 gsel[2 * DM];
  uint4 cs[8 * 4 * DH / 2];
  uint2 stat[SQ];
  __align__(1024) __nv_bfloat16 xn[SQ * DM];
  __align__(1024) uint4 o[SQ * QD / 8];
};
__device__ Scratch g_scratch;

__device__ __forceinline__ uint32_t smem_u32(const void* p) { return (uint32_t)__cvta_generic_to_shared(p); }
__device__ __forceinline__ void mbar_init(uint32_t bar, int cnt) { asm volatile("mbarrier.init.shared::cta.b64 [%0], %1;" ::"r"(bar), "r"(cnt)); }
__device__ __forceinline__ void mbar_expect_tx(uint32_t bar, uint32_t bytes) {
  asm volatile("mbarrier.arrive.expect_tx.shared::cta.b64 _, [%0], %1;" ::"r"(bar), "r"(bytes) : "memory");
}
__device__ __forceinline__ void mbar_arrive(uint32_t bar) { asm volatile("mbarrier.arrive.shared::cta.b64 _, [%0];" ::"r"(bar) : "memory"); }
__device__ __forceinline__ void mbar_arrive_cluster(uint32_t addr) { asm volatile("mbarrier.arrive.shared::cluster.b64 _, [%0];" ::"r"(addr) : "memory"); }
__device__ __forceinline__ bool mbar_try(uint32_t bar, uint32_t parity) {
  uint32_t ok;
  asm volatile("{\n.reg .pred p;\nmbarrier.try_wait.parity.shared::cta.b64 p, [%1], %2;\nselp.u32 %0, 1, 0, p;\n}\n" : "=r"(ok) : "r"(bar), "r"(parity) : "memory");
  return ok;
}
__device__ __forceinline__ void mbar_wait(uint32_t bar, uint32_t parity, int& budget) {
#pragma unroll 1
  while (!mbar_try(bar, parity)) { if (--budget < 0) break; }
}
__device__ __forceinline__ void mbar_wait(uint32_t bar, uint32_t parity) {
#pragma unroll 1
  while (!mbar_try(bar, parity)) {}
}
__device__ __forceinline__ unsigned ld_acquire(const unsigned* p) { unsigned v; asm volatile("ld.acquire.gpu.global.u32 %0, [%1];" : "=r"(v) : "l"(p) : "memory"); return v; }
__device__ __forceinline__ void wait_flag(const unsigned* p, unsigned target) {
#pragma unroll 1
  while (__any_sync(~0u, (int)(ld_acquire(p) - target) < 0)) {}
}
__device__ __forceinline__ void red_release(unsigned* p) { asm volatile("red.release.gpu.global.add.u32 [%0], 1;" ::"l"(p) : "memory"); }
__device__ __forceinline__ void fence_proxy_async() { asm volatile("fence.proxy.async.global;" ::: "memory"); }
__device__ __forceinline__ bool elect() {
  uint32_t p;
  asm volatile("{\n.reg .pred P;\nelect.sync _|P, 0xffffffff;\nselp.u32 %0, 1, 0, P;\n}\n" : "=r"(p));
  return p;
}
__device__ __forceinline__ void cluster_arrive() { asm volatile("barrier.cluster.arrive.relaxed.aligned;" ::: "memory"); }
__device__ __forceinline__ void cluster_wait() { asm volatile("barrier.cluster.wait.aligned;" ::: "memory"); }
__device__ __forceinline__ void cluster_sync() { cluster_arrive(); cluster_wait(); }
__device__ __forceinline__ void tma2d(uint32_t dst, const CUtensorMap* tm, int c0, int c1, uint32_t bar) {
  asm volatile("cp.async.bulk.tensor.2d.shared::cluster.global.mbarrier::complete_tx::bytes [%0], [%1, {%3, %4}], [%2];"
               ::"r"(dst), "l"(tm), "r"(bar), "r"(c0), "r"(c1) : "memory");
}
constexpr uint64_t POL_FIRST = 0x12F0000000000000ull;
__device__ __forceinline__ void tma4d_mc(uint32_t dst, const CUtensorMap* tm, int c2, int c3, uint32_t bar) {
  asm volatile("cp.async.bulk.tensor.4d.shared::cluster.global.mbarrier::complete_tx::bytes.multicast::cluster.L2::cache_hint [%0], [%1, {%3, %3, %4, %5}], [%2], %6, %7;"
               ::"r"(dst), "l"(tm), "r"(bar), "r"(0), "r"(c2), "r"(c3), "h"((uint16_t)3), "l"(POL_FIRST) : "memory");
}
__device__ __forceinline__ void tma5d_mc(uint32_t dst, const CUtensorMap* tm, int c2, int c4, uint32_t bar) {
  asm volatile("cp.async.bulk.tensor.5d.shared::cluster.global.mbarrier::complete_tx::bytes.multicast::cluster.L2::cache_hint [%0], [%1, {%3, %3, %4, %3, %5}], [%2], %6, %7;"
               ::"r"(dst), "l"(tm), "r"(bar), "r"(0), "r"(c2), "r"(c4), "h"((uint16_t)3), "l"(POL_FIRST) : "memory");
}
__device__ __forceinline__ void bulk_load(uint32_t dst, const void* src, uint32_t bytes, uint32_t bar) {
  asm volatile("cp.async.bulk.shared::cluster.global.mbarrier::complete_tx::bytes.L2::cache_hint [%0], [%1], %2, [%3], %4;" ::"r"(dst), "l"(src), "r"(bytes), "r"(bar), "l"(POL_FIRST) : "memory");
}
__device__ __forceinline__ void tma2d_store(const CUtensorMap* tm, uint32_t src, int c0, int c1) {
  asm volatile("cp.async.bulk.tensor.2d.global.shared::cta.bulk_group [%0, {%2, %3}], [%1];" ::"l"(tm), "r"(src), "r"(c0), "r"(c1) : "memory");
}
__device__ __forceinline__ uint32_t lds32(uint32_t a) { uint32_t v; asm volatile("ld.shared.u32 %0, [%1];" : "=r"(v) : "r"(a) : "memory"); return v; }
__device__ __forceinline__ uint2 lds64(uint32_t a) { uint2 v; asm volatile("ld.shared.v2.u32 {%0,%1}, [%2];" : "=r"(v.x), "=r"(v.y) : "r"(a) : "memory"); return v; }
__device__ __forceinline__ uint4 lds128(uint32_t a) { uint4 v; asm volatile("ld.shared.v4.u32 {%0,%1,%2,%3}, [%4];" : "=r"(v.x), "=r"(v.y), "=r"(v.z), "=r"(v.w) : "r"(a) : "memory"); return v; }
__device__ __forceinline__ void ldsm4(uint32_t a, uint32_t* v) {
  asm volatile("ldmatrix.sync.aligned.m8n8.x4.shared.b16 {%0,%1,%2,%3}, [%4];" : "=r"(v[0]), "=r"(v[1]), "=r"(v[2]), "=r"(v[3]) : "r"(a) : "memory");
}
__device__ __forceinline__ void stsm4(uint32_t a, const uint32_t* v) {
  asm volatile("stmatrix.sync.aligned.m8n8.x4.shared.b16 [%0], {%1,%2,%3,%4};" ::"r"(a), "r"(v[0]), "r"(v[1]), "r"(v[2]), "r"(v[3]) : "memory");
}
__device__ __forceinline__ void sts32(uint32_t a, uint32_t v) { asm volatile("st.shared.u32 [%0], %1;" ::"r"(a), "r"(v) : "memory"); }
__device__ __forceinline__ void st_pkt(uint4* p, uint32_t a, uint32_t b, uint32_t c, uint32_t d) {
  asm volatile("st.relaxed.gpu.global.v4.b32 [%0], {%1, %2, %3, %4};" ::"l"(p), "r"(a), "r"(b), "r"(c), "r"(d) : "memory");
}
__device__ __forceinline__ void st_pkt8(void* p, uint32_t a, uint32_t b) {
  asm volatile("{\n.reg .b64 v;\nmov.b64 v, {%1, %2};\nst.relaxed.gpu.global.b64 [%0], v;\n}\n" ::"l"(p), "r"(a), "r"(b) : "memory");
}
__device__ __forceinline__ uint4 ld_pkt(const uint4* p) {
  uint4 v;
  asm volatile("{\n.reg .b128 v;\nld.relaxed.gpu.global.b128 v, [%4];\nmov.b128 {%0, %1, %2, %3}, v;\n}\n" : "=r"(v.x), "=r"(v.y), "=r"(v.z), "=r"(v.w) : "l"(p) : "memory");
  return v;
}
__device__ __forceinline__ uint4 ldg_nc(const void* p) {
  uint4 v;
  asm volatile("ld.global.nc.v4.u32 {%0,%1,%2,%3}, [%4];" : "=r"(v.x), "=r"(v.y), "=r"(v.z), "=r"(v.w) : "l"(p));
  return v;
}
#define WG_FENCE() asm volatile("wgmma.fence.sync.aligned;" ::: "memory")
#define WG_COMMIT() asm volatile("wgmma.commit_group.sync.aligned;" ::: "memory")
#define WG_WAIT(n) asm volatile("wgmma.wait_group.sync.aligned " #n ";" ::: "memory")
template <int N> __device__ __forceinline__ void reg_fence(float (&d)[N]) {
#pragma unroll
  for (int i = 0; i < N; i++) asm volatile("" : "+f"(d[i])::"memory");
}
template <int N> __device__ __forceinline__ void reg_fence(uint32_t (&d)[N]) {
#pragma unroll
  for (int i = 0; i < N; i++) asm volatile("" : "+r"(d[i])::"memory");
}
__device__ __forceinline__ constexpr uint64_t desc_hi(uint32_t lbo, uint32_t sbo, uint64_t sw) {
  return ((uint64_t)(lbo >> 4) << 16) | ((uint64_t)(sbo >> 4) << 32) | (sw << 62);
}
__device__ __forceinline__ uint64_t mkdesc(uint32_t addr, uint64_t hi) { return hi | (uint64_t)((addr & 0x3FFFF) >> 4); }
__device__ __forceinline__ uint32_t pack_bf16(float lo, float hi) { uint32_t r; asm("cvt.rn.bf16x2.f32 %0, %1, %2;" : "=r"(r) : "f"(hi), "f"(lo)); return r; }
__device__ __forceinline__ float bf_lo(uint32_t v) { return __uint_as_float(v << 16); }
__device__ __forceinline__ float bf_hi(uint32_t v) { return __uint_as_float(v & 0xffff0000u); }
__device__ __forceinline__ uint32_t hadd2(uint32_t a, uint32_t b) { uint32_t r; asm("add.rn.bf16x2 %0, %1, %2;" : "=r"(r) : "r"(a), "r"(b)); return r; }
__device__ __forceinline__ uint32_t hsub2(uint32_t a, uint32_t b) { uint32_t r; asm("sub.rn.bf16x2 %0, %1, %2;" : "=r"(r) : "r"(a), "r"(b)); return r; }
__device__ __forceinline__ uint32_t hmul2(uint32_t a, uint32_t b) { uint32_t r; asm("mul.rn.bf16x2 %0, %1, %2;" : "=r"(r) : "r"(a), "r"(b)); return r; }
__device__ __forceinline__ float rbf(float x) { return __bfloat162float(__float2bfloat16_rn(x)); }
__device__ __forceinline__ float ex2(float x) { float y; asm("ex2.approx.ftz.f32 %0, %1;" : "=f"(y) : "f"(x)); return y; }
__device__ __forceinline__ float rcp(float x) { float y; asm("rcp.approx.ftz.f32 %0, %1;" : "=f"(y) : "f"(x)); return y; }
__device__ __forceinline__ float sigmoid_f(float x) { return rcp(1.f + ex2(x * -1.4426950408889634f)); }
__device__ __forceinline__ float silu_f(float x) { return x * sigmoid_f(x); }

__device__ __forceinline__ void wg_ss192t(float (&d)[96], uint64_t da, uint64_t db, int sd) {
  asm volatile("{\n.reg .pred p;\nsetp.ne.b32 p, %98, 0;\n"
    "wgmma.mma_async.sync.aligned.m64n192k16.f32.bf16.bf16 {%0,%1,%2,%3,%4,%5,%6,%7,%8,%9,%10,%11,%12,%13,%14,%15,%16,%17,%18,%19,%20,%21,%22,%23,%24,%25,%26,%27,%28,%29,%30,%31,%32,%33,%34,%35,%36,%37,%38,%39,%40,%41,%42,%43,%44,%45,%46,%47,%48,%49,%50,%51,%52,%53,%54,%55,%56,%57,%58,%59,%60,%61,%62,%63,%64,%65,%66,%67,%68,%69,%70,%71,%72,%73,%74,%75,%76,%77,%78,%79,%80,%81,%82,%83,%84,%85,%86,%87,%88,%89,%90,%91,%92,%93,%94,%95}, %96, %97, p, 1, 1, 0, 1;\n}\n"
    : "+f"(d[0]),"+f"(d[1]),"+f"(d[2]),"+f"(d[3]),"+f"(d[4]),"+f"(d[5]),"+f"(d[6]),"+f"(d[7]),"+f"(d[8]),"+f"(d[9]),"+f"(d[10]),"+f"(d[11]),"+f"(d[12]),"+f"(d[13]),"+f"(d[14]),"+f"(d[15]),"+f"(d[16]),"+f"(d[17]),"+f"(d[18]),"+f"(d[19]),"+f"(d[20]),"+f"(d[21]),"+f"(d[22]),"+f"(d[23]),"+f"(d[24]),"+f"(d[25]),"+f"(d[26]),"+f"(d[27]),"+f"(d[28]),"+f"(d[29]),"+f"(d[30]),"+f"(d[31]),"+f"(d[32]),"+f"(d[33]),"+f"(d[34]),"+f"(d[35]),"+f"(d[36]),"+f"(d[37]),"+f"(d[38]),"+f"(d[39]),"+f"(d[40]),"+f"(d[41]),"+f"(d[42]),"+f"(d[43]),"+f"(d[44]),"+f"(d[45]),"+f"(d[46]),"+f"(d[47]),"+f"(d[48]),"+f"(d[49]),"+f"(d[50]),"+f"(d[51]),"+f"(d[52]),"+f"(d[53]),"+f"(d[54]),"+f"(d[55]),"+f"(d[56]),"+f"(d[57]),"+f"(d[58]),"+f"(d[59]),"+f"(d[60]),"+f"(d[61]),"+f"(d[62]),"+f"(d[63]),"+f"(d[64]),"+f"(d[65]),"+f"(d[66]),"+f"(d[67]),"+f"(d[68]),"+f"(d[69]),"+f"(d[70]),"+f"(d[71]),"+f"(d[72]),"+f"(d[73]),"+f"(d[74]),"+f"(d[75]),"+f"(d[76]),"+f"(d[77]),"+f"(d[78]),"+f"(d[79]),"+f"(d[80]),"+f"(d[81]),"+f"(d[82]),"+f"(d[83]),"+f"(d[84]),"+f"(d[85]),"+f"(d[86]),"+f"(d[87]),"+f"(d[88]),"+f"(d[89]),"+f"(d[90]),"+f"(d[91]),"+f"(d[92]),"+f"(d[93]),"+f"(d[94]),"+f"(d[95])
    : "l"(da), "l"(db), "r"(sd));
}
__device__ __forceinline__ void wg_rs64(float (&d)[32], uint32_t a0, uint32_t a1, uint32_t a2, uint32_t a3, uint64_t db, int sd) {
  asm volatile("{\n.reg .pred p;\nsetp.ne.b32 p, %37, 0;\n"
    "wgmma.mma_async.sync.aligned.m64n64k16.f32.bf16.bf16 {%0,%1,%2,%3,%4,%5,%6,%7,%8,%9,%10,%11,%12,%13,%14,%15,%16,%17,%18,%19,%20,%21,%22,%23,%24,%25,%26,%27,%28,%29,%30,%31}, {%32,%33,%34,%35}, %36, p, 1, 1, 0;\n}\n"
    : "+f"(d[0]),"+f"(d[1]),"+f"(d[2]),"+f"(d[3]),"+f"(d[4]),"+f"(d[5]),"+f"(d[6]),"+f"(d[7]),"+f"(d[8]),"+f"(d[9]),"+f"(d[10]),"+f"(d[11]),"+f"(d[12]),"+f"(d[13]),"+f"(d[14]),"+f"(d[15]),"+f"(d[16]),"+f"(d[17]),"+f"(d[18]),"+f"(d[19]),"+f"(d[20]),"+f"(d[21]),"+f"(d[22]),"+f"(d[23]),"+f"(d[24]),"+f"(d[25]),"+f"(d[26]),"+f"(d[27]),"+f"(d[28]),"+f"(d[29]),"+f"(d[30]),"+f"(d[31])
    : "r"(a0), "r"(a1), "r"(a2), "r"(a3), "l"(db), "r"(sd));
}
__device__ __forceinline__ void wg_rs192t(float (&d)[96], uint32_t a0, uint32_t a1, uint32_t a2, uint32_t a3, uint64_t db, int sd) {
  asm volatile("{\n.reg .pred p;\nsetp.ne.b32 p, %101, 0;\n"
    "wgmma.mma_async.sync.aligned.m64n192k16.f32.bf16.bf16 {%0,%1,%2,%3,%4,%5,%6,%7,%8,%9,%10,%11,%12,%13,%14,%15,%16,%17,%18,%19,%20,%21,%22,%23,%24,%25,%26,%27,%28,%29,%30,%31,%32,%33,%34,%35,%36,%37,%38,%39,%40,%41,%42,%43,%44,%45,%46,%47,%48,%49,%50,%51,%52,%53,%54,%55,%56,%57,%58,%59,%60,%61,%62,%63,%64,%65,%66,%67,%68,%69,%70,%71,%72,%73,%74,%75,%76,%77,%78,%79,%80,%81,%82,%83,%84,%85,%86,%87,%88,%89,%90,%91,%92,%93,%94,%95}, {%96,%97,%98,%99}, %100, p, 1, 1, 1;\n}\n"
    : "+f"(d[0]),"+f"(d[1]),"+f"(d[2]),"+f"(d[3]),"+f"(d[4]),"+f"(d[5]),"+f"(d[6]),"+f"(d[7]),"+f"(d[8]),"+f"(d[9]),"+f"(d[10]),"+f"(d[11]),"+f"(d[12]),"+f"(d[13]),"+f"(d[14]),"+f"(d[15]),"+f"(d[16]),"+f"(d[17]),"+f"(d[18]),"+f"(d[19]),"+f"(d[20]),"+f"(d[21]),"+f"(d[22]),"+f"(d[23]),"+f"(d[24]),"+f"(d[25]),"+f"(d[26]),"+f"(d[27]),"+f"(d[28]),"+f"(d[29]),"+f"(d[30]),"+f"(d[31]),"+f"(d[32]),"+f"(d[33]),"+f"(d[34]),"+f"(d[35]),"+f"(d[36]),"+f"(d[37]),"+f"(d[38]),"+f"(d[39]),"+f"(d[40]),"+f"(d[41]),"+f"(d[42]),"+f"(d[43]),"+f"(d[44]),"+f"(d[45]),"+f"(d[46]),"+f"(d[47]),"+f"(d[48]),"+f"(d[49]),"+f"(d[50]),"+f"(d[51]),"+f"(d[52]),"+f"(d[53]),"+f"(d[54]),"+f"(d[55]),"+f"(d[56]),"+f"(d[57]),"+f"(d[58]),"+f"(d[59]),"+f"(d[60]),"+f"(d[61]),"+f"(d[62]),"+f"(d[63]),"+f"(d[64]),"+f"(d[65]),"+f"(d[66]),"+f"(d[67]),"+f"(d[68]),"+f"(d[69]),"+f"(d[70]),"+f"(d[71]),"+f"(d[72]),"+f"(d[73]),"+f"(d[74]),"+f"(d[75]),"+f"(d[76]),"+f"(d[77]),"+f"(d[78]),"+f"(d[79]),"+f"(d[80]),"+f"(d[81]),"+f"(d[82]),"+f"(d[83]),"+f"(d[84]),"+f"(d[85]),"+f"(d[86]),"+f"(d[87]),"+f"(d[88]),"+f"(d[89]),"+f"(d[90]),"+f"(d[91]),"+f"(d[92]),"+f"(d[93]),"+f"(d[94]),"+f"(d[95])
    : "r"(a0), "r"(a1), "r"(a2), "r"(a3), "l"(db), "r"(sd));
}
__device__ __forceinline__ void wg_ss160t(float (&d)[80], uint64_t da, uint64_t db, int sd) {
  asm volatile("{\n.reg .pred p;\nsetp.ne.b32 p, %82, 0;\n"
    "wgmma.mma_async.sync.aligned.m64n160k16.f32.bf16.bf16 {%0,%1,%2,%3,%4,%5,%6,%7,%8,%9,%10,%11,%12,%13,%14,%15,%16,%17,%18,%19,%20,%21,%22,%23,%24,%25,%26,%27,%28,%29,%30,%31,%32,%33,%34,%35,%36,%37,%38,%39,%40,%41,%42,%43,%44,%45,%46,%47,%48,%49,%50,%51,%52,%53,%54,%55,%56,%57,%58,%59,%60,%61,%62,%63,%64,%65,%66,%67,%68,%69,%70,%71,%72,%73,%74,%75,%76,%77,%78,%79}, %80, %81, p, 1, 1, 0, 1;\n}\n"
    : "+f"(d[0]),"+f"(d[1]),"+f"(d[2]),"+f"(d[3]),"+f"(d[4]),"+f"(d[5]),"+f"(d[6]),"+f"(d[7]),"+f"(d[8]),"+f"(d[9]),"+f"(d[10]),"+f"(d[11]),"+f"(d[12]),"+f"(d[13]),"+f"(d[14]),"+f"(d[15]),"+f"(d[16]),"+f"(d[17]),"+f"(d[18]),"+f"(d[19]),"+f"(d[20]),"+f"(d[21]),"+f"(d[22]),"+f"(d[23]),"+f"(d[24]),"+f"(d[25]),"+f"(d[26]),"+f"(d[27]),"+f"(d[28]),"+f"(d[29]),"+f"(d[30]),"+f"(d[31]),"+f"(d[32]),"+f"(d[33]),"+f"(d[34]),"+f"(d[35]),"+f"(d[36]),"+f"(d[37]),"+f"(d[38]),"+f"(d[39]),"+f"(d[40]),"+f"(d[41]),"+f"(d[42]),"+f"(d[43]),"+f"(d[44]),"+f"(d[45]),"+f"(d[46]),"+f"(d[47]),"+f"(d[48]),"+f"(d[49]),"+f"(d[50]),"+f"(d[51]),"+f"(d[52]),"+f"(d[53]),"+f"(d[54]),"+f"(d[55]),"+f"(d[56]),"+f"(d[57]),"+f"(d[58]),"+f"(d[59]),"+f"(d[60]),"+f"(d[61]),"+f"(d[62]),"+f"(d[63]),"+f"(d[64]),"+f"(d[65]),"+f"(d[66]),"+f"(d[67]),"+f"(d[68]),"+f"(d[69]),"+f"(d[70]),"+f"(d[71]),"+f"(d[72]),"+f"(d[73]),"+f"(d[74]),"+f"(d[75]),"+f"(d[76]),"+f"(d[77]),"+f"(d[78]),"+f"(d[79])
    : "l"(da), "l"(db), "r"(sd));
}
__device__ __forceinline__ void wg_ss80t(float (&d)[40], uint64_t da, uint64_t db, int sd) {
  asm volatile("{\n.reg .pred p;\nsetp.ne.b32 p, %42, 0;\n"
    "wgmma.mma_async.sync.aligned.m64n80k16.f32.bf16.bf16 {%0,%1,%2,%3,%4,%5,%6,%7,%8,%9,%10,%11,%12,%13,%14,%15,%16,%17,%18,%19,%20,%21,%22,%23,%24,%25,%26,%27,%28,%29,%30,%31,%32,%33,%34,%35,%36,%37,%38,%39}, %40, %41, p, 1, 1, 0, 1;\n}\n"
    : "+f"(d[0]),"+f"(d[1]),"+f"(d[2]),"+f"(d[3]),"+f"(d[4]),"+f"(d[5]),"+f"(d[6]),"+f"(d[7]),"+f"(d[8]),"+f"(d[9]),"+f"(d[10]),"+f"(d[11]),"+f"(d[12]),"+f"(d[13]),"+f"(d[14]),"+f"(d[15]),"+f"(d[16]),"+f"(d[17]),"+f"(d[18]),"+f"(d[19]),"+f"(d[20]),"+f"(d[21]),"+f"(d[22]),"+f"(d[23]),"+f"(d[24]),"+f"(d[25]),"+f"(d[26]),"+f"(d[27]),"+f"(d[28]),"+f"(d[29]),"+f"(d[30]),"+f"(d[31]),"+f"(d[32]),"+f"(d[33]),"+f"(d[34]),"+f"(d[35]),"+f"(d[36]),"+f"(d[37]),"+f"(d[38]),"+f"(d[39])
    : "l"(da), "l"(db), "r"(sd));
}

struct Maps { CUtensorMap x, xn, wq, k, v, wo, w3[2], xg, xe, out; };
struct Params {
  const __nv_bfloat16 *x, *wr, *wg, *wu, *wd, *k, *v;
  Scratch* s;
};

__device__ __forceinline__ void side_cta(const Params& p, int sc, unsigned epoch, float* sm) {
  const int tid = threadIdx.x, lane = tid & 31, warp = tid >> 5;
  int budget = WAIT_BUDGET;
  float* s_x = sm;
  float* s_red = sm + 1280;
  float* s_h = s_red + 6144;
  uint4* s_c = (uint4*)(s_h + 768);
  uint2* s_st = (uint2*)(s_c + 16);
  constexpr int DEPTH = 7, STEP = 4 * 6144;
  const uint32_t ring = smem_u32(s_st + 512) + tid * 16;
  const int cg = tid % 96, ks = tid / 96, cd = tid % 80, kd = tid / 80;
  const __nv_bfloat16* wp = (cg < 48 ? p.wg : p.wu) + (size_t)(ks * 160) * FF + sc * 384 + (cg % 48) * 8;
  int kf = 0, pitch = FF;
  uint32_t slot = ring;
  auto refill = [&]() {
    if (kf == 40) { wp = p.wd + (size_t)(sc * 384 + kd * 96) * DM + cd * 8; pitch = DM; }
    if (kf < (tid < 320 ? 64 : 40)) {
#pragma unroll
      for (int j = 0; j < 4; j++) asm volatile("cp.async.cg.shared.global.L2::cache_hint [%0], [%1], 16, %2;" ::"r"(slot + j * 6144), "l"(wp + j * pitch), "l"(POL_FIRST) : "memory");
    }
    asm volatile("cp.async.commit_group;" ::: "memory");
    wp += 4 * pitch; kf++;
    slot += STEP; if (slot == ring + DEPTH * STEP) slot = ring;
  };
  auto gemv = [&](int n, const float* x0, const float* x1, float* out) {
    float a[2][8] = {};
#pragma unroll 1
    for (int k = 0; k < n; k += 4) {
      refill();
      asm volatile("cp.async.wait_group %0;" ::"n"(DEPTH - 1) : "memory");
      const float4 f0 = *(const float4*)(x0 + k), f1 = *(const float4*)(x1 + k);
      const float y0[4] = {f0.x, f0.y, f0.z, f0.w}, y1[4] = {f1.x, f1.y, f1.z, f1.w};
#pragma unroll
      for (int j = 0; j < 4; j++) {
        const uint4 v = lds128(slot + j * 6144);
        const uint32_t u[4] = {v.x, v.y, v.z, v.w};
#pragma unroll
        for (int i = 0; i < 4; i++) {
          a[0][2 * i] += y0[j] * bf_lo(u[i]); a[0][2 * i + 1] += y0[j] * bf_hi(u[i]);
          a[1][2 * i] += y1[j] * bf_lo(u[i]); a[1][2 * i + 1] += y1[j] * bf_hi(u[i]);
        }
      }
    }
#pragma unroll
    for (int i = 0; i < 16; i++) out[(i >> 3) * 768 + (i & 7)] = a[i >> 3][i & 7];
  };
  auto load_row = [&](const __nv_bfloat16* r, uint32_t (&v)[10]) {
    const uint4 a = __ldg((const uint4*)r + lane), b = __ldg((const uint4*)r + 32 + lane);
    const uint2 c = __ldg((const uint2*)r + 128 + lane);
    v[0] = a.x; v[1] = a.y; v[2] = a.z; v[3] = a.w; v[4] = b.x; v[5] = b.y; v[6] = b.z; v[7] = b.w; v[8] = c.x; v[9] = c.y;
  };
  uint32_t wr[10], xb[3][10];
  load_row(p.wr, wr);
  auto stat2 = [&](int pair) {
    uint4 v;
    do v = ld_pkt((const uint4*)p.s->stat + pair); while ((((v.x ^ (epoch + 1)) | (v.z ^ (epoch + 1))) & 0xffff) && --budget >= 0);
    return make_uint4(__byte_perm(v.x, 0, 0x3232), v.y, __byte_perm(v.z, 0, 0x3232), v.w);
  };
  if (tid < 256) ((uint4*)s_st)[tid] = stat2(sc * 256 + tid);
  __syncthreads();
#pragma unroll
  for (int b = 0; b < 3; b++) load_row(p.x + (size_t)(sc * 512 + warp + 12 * b) * DM, xb[b]);
#pragma unroll 1
  for (int k = 0; k < DEPTH - 1; k++) refill();
  float v0 = -INFINITY, v1 = -INFINITY; int i0 = 0xfff, i1 = 0xfff;
  auto better = [](float a, int ia, float b, int ib) { return a > b || (a == b && ia < ib); };
  auto push = [&](float v, int i) {
    if (better(v, i, v0, i0)) { v1 = v0; i1 = i0; v0 = v; i0 = i; }
    else if (better(v, i, v1, i1)) { v1 = v; i1 = i; }
  };
  auto push2 = [&](uint4 c) { push(__uint_as_float(c.x), c.y & 0xfff); push(__uint_as_float(c.z), c.w & 0xfff); };
#pragma unroll 1
  for (int l3 = warp; l3 < 512; l3 += 36) {
#pragma unroll
    for (int b = 0; b < 3; b++) {
      const int lr = l3 + 12 * b;
      if (lr >= 512) break;
      const uint2 st = s_st[lr];
      uint32_t v[10];
#pragma unroll
      for (int i = 0; i < 10; i++) v[i] = hsub2(xb[b][i], st.x);
      if (lr + 36 < 512) load_row(p.x + (size_t)(sc * 512 + lr + 36) * DM, xb[b]);
      float r0 = 0.f, r1 = 0.f;
#pragma unroll
      for (int i = 0; i < 10; i++) {
        const uint32_t xn = pack_bf16(bf_lo(v[i]) * __uint_as_float(st.y), bf_hi(v[i]) * __uint_as_float(st.y));
        r0 = fmaf(bf_lo(xn), bf_lo(wr[i]), r0); r1 = fmaf(bf_hi(xn), bf_hi(wr[i]), r1);
      }
      r0 += r1;
#pragma unroll
      for (int o = 16; o > 0; o >>= 1) r0 += __shfl_xor_sync(~0u, r0, o);
      push(rbf(r0), sc * 512 + lr);
    }
  }
  if (lane == 0) s_c[warp] = make_uint4(__float_as_uint(v0), i0, __float_as_uint(v1), i1);
  __syncthreads();
#pragma unroll 1
  for (int w = 1; w < 12; w++) push2(s_c[(warp + w) % 12]);
  const uint32_t tag = (epoch + 1) << 12;
  if (tid == 0) st_pkt(p.s->cand + sc, __float_as_uint(v0), i0 | tag, __float_as_uint(v1), i1);
  {
    uint4 c;
    do c = ld_pkt(p.s->cand + (lane & 3)); while (((c.y ^ tag) >> 12) && --budget >= 0);
#pragma unroll 1
    for (int w = 1; w < 4; w++) { const int o = (sc + w) & 3; push2(make_uint4(__shfl_sync(~0u, c.x, o), __shfl_sync(~0u, c.y, o), __shfl_sync(~0u, c.z, o), __shfl_sync(~0u, c.w, o))); }
  }
  if (i0 >= SQ) i0 = 0;
  if (i1 >= SQ) i1 = (i0 == 0) ? 1 : 0;
  if (tid < 320) {
    const int row = tid < 160 ? i0 : i1;
    const uint2 u = __ldg((const uint2*)(p.x + (size_t)row * DM) + tid % 160);
    const uint4 st = stat2(row >> 1);
    const uint32_t mean2 = row & 1 ? st.z : st.x, d0 = hsub2(u.x, mean2), d1 = hsub2(u.y, mean2);
    const float inv = __uint_as_float(row & 1 ? st.w : st.y);
    ((float4*)s_x)[tid] = make_float4(rbf(bf_lo(d0) * inv), rbf(bf_hi(d0) * inv), rbf(bf_lo(d1) * inv), rbf(bf_hi(d1) * inv));
  }
  __syncthreads();
  gemv(160, s_x + ks * 160, s_x + DM + ks * 160, s_red + ks * 1536 + cg * 8);
  __syncthreads();
#pragma unroll
  for (int t = 0; t < 2; t++) {
    float g = 0.f, u = 0.f;
#pragma unroll
    for (int k = 0; k < 4; k++) { g += s_red[(k * 2 + t) * 768 + tid]; u += s_red[(k * 2 + t) * 768 + 384 + tid]; }
    s_h[t * 384 + tid] = rbf(rbf(silu_f(rbf(g))) * rbf(u));
  }
  __syncthreads();
  if (tid < 320) gemv(96, s_h + kd * 96, s_h + 384 + kd * 96, s_red + kd * 1536 + cd * 8);
  __syncthreads();
  const int o4 = tid + (tid < 160 ? 0 : 32);
  if (tid < 320) {
    const float4 *r = (const float4*)s_red + o4, a = r[0], b = r[384], c = r[768], d = r[1152];
    ((float4*)p.s->ffn)[sc * 320 + tid] = make_float4(a.x + b.x + c.x + d.x, a.y + b.y + c.y + d.y, a.z + b.z + c.z + d.z, a.w + b.w + c.w + d.w);
  }
  __syncthreads();
  if (tid == 0) { __threadfence(); s_c[0].x = (atomicAdd(&p.s->flag[FL_SIDE], 1u) & 3u) == 3u; __threadfence(); }
  __syncthreads();
  if (s_c[0].x) {
    if (tid < 320) {
      const float4 *r = (const float4*)p.s->ffn + tid, a = __ldcg(r), b = __ldcg(r + 320), c = __ldcg(r + 640), d = __ldcg(r + 960), x = ((float4*)s_x)[tid];
      const float rs = rbf(sigmoid_f(tid < 160 ? v0 : v1));
      auto gate = [&](float xn, float y) { return silu_f(rbf(xn + rbf(rbf(y) * rs))); };
      if (tid == 0) { p.s->sel[0] = i0; p.s->sel[1] = i1; }
      ((uint2*)p.s->gsel)[tid] =
          make_uint2(pack_bf16(gate(x.x, a.x + b.x + c.x + d.x), gate(x.y, a.y + b.y + c.y + d.y)), pack_bf16(gate(x.z, a.z + b.z + c.z + d.z), gate(x.w, a.w + b.w + c.w + d.w)));
    }
    __syncthreads();
    if (tid == 0) red_release(&p.s->flag[FL_FFN]);
  }
}

constexpr float SM_C = 0.07216878364870322f * 1.4426950408889634f;

constexpr int LD = 0, LS = 3;
__device__ __forceinline__ void ln_piece(const Params& p, uint32_t (&r)[48], int k, int row, int l16) {
  auto f = [&](int i) { return __uint_as_float(r[i]); };
  if (k == LD) {
#pragma unroll
    for (int i = 0; i < 5; i++) {
      const uint4 v = ldg_nc((const uint4*)(p.x + (size_t)row * DM) + i * 16 + l16);
      r[4 * i] = v.x; r[4 * i + 1] = v.y; r[4 * i + 2] = v.z; r[4 * i + 3] = v.w;
    }
    asm volatile("ld.relaxed.gpu.global.v2.u32 {%0,%1}, [%2];" : "=r"(r[20]), "=r"(r[21]) : "l"(&p.s->done));
  } else if (k == LS || k == LS + 1) {
    if (k == LS) { r[22] = __shfl_sync(~0u, r[0], 0, 16) << 16; r[23] = r[24] = 0; }
    float s0 = f(23), s1 = 0.f, q0 = f(24), q1 = 0.f;
#pragma unroll
    for (int i = 10 * (k - LS); i < 10 * (k - LS) + 10; i++) {
      const float a = bf_lo(r[i]) - f(22), b = bf_hi(r[i]) - f(22);
      s0 += a; s1 += b; q0 = fmaf(a, a, q0); q1 = fmaf(b, b, q1);
    }
    r[23] = __float_as_uint(s0 + s1); r[24] = __float_as_uint(q0 + q1);
  } else if (k == LS + 2) {
    float s0 = f(23), q0 = f(24);
#pragma unroll
    for (int o = 8; o > 0; o >>= 1) { s0 += __shfl_xor_sync(~0u, s0, o); q0 += __shfl_xor_sync(~0u, q0, o); }
    s0 *= 1.f / DM;
    const float mean = f(22) + s0, var = rbf(fmaxf(fmaf(q0, 1.f / DM, -s0 * s0), 0.f));
    float sd; asm("sqrt.approx.ftz.f32 %0, %1;" : "=f"(sd) : "f"(rbf(var + 1e-5f)));
    const float inv = rcp(rbf(sd));
    r[22] = pack_bf16(mean, mean); r[23] = __float_as_uint(inv * SM_C);
    const uint32_t tag = __funnelshift_r(r[20], r[21], 7) + 1;
    if (l16 == 0) st_pkt8(&p.s->stat[row], __byte_perm(tag, r[22], 0x7610), __float_as_uint(inv));
  } else if (k > LS + 2 && k <= LS + 5) {
#pragma unroll
    for (int j = 2 * (k - LS - 3); j < 2 * (k - LS - 3) + 2 && j < 5; j++) {
#pragma unroll
      for (int i = 4 * j; i < 4 * j + 4; i++) { const uint32_t d = hsub2(r[i], r[22]); r[i] = pack_bf16(bf_lo(d) * f(23), bf_hi(d) * f(23)); }
      *((uint4*)(p.s->xn + (size_t)row * DM) + j * 16 + l16) = make_uint4(r[4 * j], r[4 * j + 1], r[4 * j + 2], r[4 * j + 3]);
    }
  }
}

constexpr float SM_HI = 0x1p64f, SM_LO = 0x1p-64f;
__device__ __forceinline__ void exp_block(float (&s)[32], float& l0, float& l1, int from = 0, int to = 32) {
#pragma unroll
  for (int i = from; i < to; i++) { s[i] = ex2(s[i]); if (i & 2) l1 += s[i]; else l0 += s[i]; }
}
__device__ __forceinline__ float quad_sum(float v) { v += __shfl_xor_sync(~0u, v, 1); return v + __shfl_xor_sync(~0u, v, 2); }
__device__ __forceinline__ float quad_max(float v) { v = fmaxf(v, __shfl_xor_sync(~0u, v, 1)); return fmaxf(v, __shfl_xor_sync(~0u, v, 2)); }
__device__ __noinline__ void safe_head(const uint32_t* kp, const uint32_t* vp, uint4* io) {
  uint32_t fq[48];
#pragma unroll
  for (int i = 0; i < 12; i++) { const uint4 v = io[(i >> 1) * 512 + (i & 1) * 32]; fq[4 * i] = v.x; fq[4 * i + 1] = v.y; fq[4 * i + 2] = v.z; fq[4 * i + 3] = v.w; }
  float m0 = -INFINITY, m1 = -INFINITY;
#pragma unroll 1
  for (int pass = 0; pass < 3; pass++) {
    float o[48] = {}, l0 = 0.f, l1 = 0.f;
#pragma unroll 1
    for (int n = 0; n < 64; n++) {
      const uint32_t *kr = kp + n * (8 * DH / 2), *vr = vp + n * (8 * DH / 2) + (pass - 1) * 48;
      float d[4] = {};
#pragma unroll
      for (int t = 0; t < 12; t++)
        asm volatile("mma.sync.aligned.m16n8k16.row.col.f32.bf16.bf16.f32 {%0,%1,%2,%3}, {%4,%5,%6,%7}, {%8,%9}, {%0,%1,%2,%3};"
                     : "+f"(d[0]), "+f"(d[1]), "+f"(d[2]), "+f"(d[3])
                     : "r"(fq[4 * t]), "r"(fq[4 * t + 1]), "r"(fq[4 * t + 2]), "r"(fq[4 * t + 3]), "r"(__ldg(kr + 8 * t)), "r"(__ldg(kr + 8 * t + 4)));
      if (pass == 0) { m0 = fmaxf(m0, fmaxf(d[0], d[1])); m1 = fmaxf(m1, fmaxf(d[2], d[3])); continue; }
      d[0] = ex2(d[0] - m0); d[1] = ex2(d[1] - m0); d[2] = ex2(d[2] - m1); d[3] = ex2(d[3] - m1);
      l0 += d[0] + d[1]; l1 += d[2] + d[3];
      const uint32_t p0 = pack_bf16(d[0], d[1]), p1 = pack_bf16(d[2], d[3]);
#pragma unroll
      for (int c = 0; c < 12; c++)
        asm volatile("{\n.reg .b32 t;\nmovmatrix.sync.aligned.m8n8.trans.b16 t, %6;\n"
                     "mma.sync.aligned.m16n8k8.row.col.f32.bf16.bf16.f32 {%0,%1,%2,%3}, {%4,%5}, {t}, {%0,%1,%2,%3};\n}\n"
                     : "+f"(o[4 * c]), "+f"(o[4 * c + 1]), "+f"(o[4 * c + 2]), "+f"(o[4 * c + 3]) : "r"(p0), "r"(p1), "r"(__ldg(vr + 4 * c)));
    }
    if (pass == 0) { m0 = quad_max(m0); m1 = quad_max(m1); continue; }
    l0 = rcp(quad_sum(l0)); l1 = rcp(quad_sum(l1));
#pragma unroll
    for (int i = 0; i < 6; i++) {
      const float* v = o + 16 * (i >> 1) + 2 * (i & 1);
      const float r = i & 1 ? l1 : l0;
      io[(3 * (pass - 1) + (i >> 1)) * 512 + (i & 1) * 32] =
          make_uint4(pack_bf16(v[0] * r, v[1] * r), pack_bf16(v[4] * r, v[5] * r), pack_bf16(v[8] * r, v[9] * r), pack_bf16(v[12] * r, v[13] * r));
    }
  }
}

__device__ __forceinline__ constexpr int end_stage(int n) { return n < 4 ? n : n < 6 ? n - 4 : n == 6 ? 4 : n % 5; }
__device__ __forceinline__ constexpr int sent(int n) { return n < 8 ? 0 : n < 9 ? 3 : n < 11 ? 5 : n < 16 ? 10 : n < 17 ? 14 : 15; }
template <int N> struct IntC { static constexpr int value = N; };
template <int N, int I = 0, class F> __device__ __forceinline__ void static_for(F&& f) { if constexpr (I < N) { f(IntC<I>{}); static_for<N, I + 1>(f); } }

extern __shared__ __align__(1024) uint8_t smem_raw[];
constexpr uint32_t EA = 160, EB = 184;
#define SMEM_LAYOUT                                                                                                          \
  [[maybe_unused]] const uint32_t sb = smem_u32(smem_raw), bar_a = sb + OFF_M, bar_b = bar_a + 40, bar_x = bar_a + 88,      \
      bar_u = bar_a + 96, bar_e = bar_a + 104, bar_o = bar_a + 200, bar_w = bar_a + 208, bar_c = bar_a + 216,                \
      bar_z = bar_a + 288, bar_s = bar_a + 296, bar_d = bar_a + 304, s_stat = bar_a + 512, s_sel = s_stat + 1024;

__device__ __forceinline__ int cluster_role() {
  uint32_t t, n;
  asm("mov.u32 %0, %%smid;" : "=r"(t)); asm("mov.u32 %0, %%nsmid;" : "=r"(n));
  t >>= 1;
  return n != 132 ? blockIdx.x >> 1 : t < 32 ? t : t < 60 ? t + 1 + (((t - 32) * 37) >> 8) : t < 62 ? t + 4 : (t - 58) * 8;
}

__device__ __forceinline__ int k_block(int t, int hg) {
  const int i = (t * 11) >> 5;
  return (((hg | 1) ^ (i & 1)) * 4 + (i >> 1)) * 6 + (t == 3 * i ? 4 : 2 * (t - 3 * i) - 2);
}

__device__ __noinline__ int errands(Scratch* s, const Maps& m, int qt, int hg, int warp, uint32_t tag, int budget) {
  SMEM_LAYOUT
  const int lane = threadIdx.x & 31, kq = hg >> 1, nh = hg & 1;
  if (warp == 1) {
#pragma unroll 1
    for (int u = 0; u < 5; u++) {
      mbar_wait(bar_o, u & 1);
      if (lane == 0) red_release(&s->flag[u ? FL_O + (qt * 8 + hg) * 8 : FL_XN + qt * 32]);
      __syncwarp();
    }
  } else if (warp == 2) {
    mbar_wait(bar_x, 0, budget);
    while ((int)(ld_acquire(&s->flag[FL_FFN]) - tag) < 0 && --budget >= 0) {}
    if (lane < 21) {
      const uint4 v = __ldcg(lane ? (const uint4*)(s->gsel + (lane > 10 ? DM - 80 : 0) + nh * 320 + kq * 80) + lane - 1 : (const uint4*)s->sel);
      asm volatile("st.shared.v4.u32 [%0], {%1,%2,%3,%4};" ::"r"(s_sel + 16 * lane), "r"(v.x), "r"(v.y), "r"(v.z), "r"(v.w) : "memory");
    }
    __syncwarp();
    if (lane == 0) { mbar_arrive(bar_u); asm volatile("red.relaxed.gpu.global.add.u64 [%0], 1;" ::"l"(&s->done) : "memory"); }
    while ((int)(ld_acquire(&s->flag[FL_RD + (qt * 8 + (hg ^ 1)) * 8]) - tag) < 0 && --budget >= 0) {}
    if (lane < 3) mbar_arrive(bar_z);
  } else {
    wait_flag(&s->flag[FL_XN + qt * 32], tag * 8);
    fence_proxy_async();
    mbar_wait(bar_a + EA + 32, 1);
    uint32_t a8 = 0, pha = 1;
    const int kb = (qt * 192 + k_block(lane, hg)) * 512;
#pragma unroll 1
    for (int n = 0; n < 54; n++) {
      const int t = n - 30, ko = __shfl_sync(~0u, kb, t);
      if (t == 0 || t == 18) {
        wait_flag(&s->flag[FL_O + (qt * 8 + (t ? 2 * kq + (lane & 1) : lane & 7)) * 8], tag * 4 - (t ? 0 : 1));
        fence_proxy_async();
      }
      mbar_wait(bar_a + EA + a8, pha);
      const uint32_t fb = bar_a + a8, dst = sb + a8 * (TA >> 3);
      if (elect()) {
        if (t >= 0) {
          mbar_expect_tx(fb, TA);
          bulk_load(dst, s->o + ko, TA, fb);
          if (t == 5) {
            mbar_expect_tx(bar_x, 6 * 3840);
#pragma unroll 1
            for (int e = 0; e < 6; e++) tma2d(sb + OFF_B + TW + e * TB, &m.xg, nh * 320 + kq * 80, qt * 128 + e * 24, bar_x);
            asm volatile("prefetch.tensormap [%0];\nprefetch.tensormap [%1];\nprefetch.tensormap [%2];\nprefetch.tensormap [%3];"
                         ::"l"(m.w3), "l"(m.w3 + 1), "l"(&m.xe), "l"(&m.out) : "memory");
          }
          if (t == 22) asm volatile("red.relaxed.gpu.global.add.u32 [%0], 1;" ::"l"(&s->flag[FL_RD + (qt * 8 + hg) * 8]) : "memory");
        } else if (n >= 10 && pha) mbar_arrive(fb);
        else { mbar_expect_tx(fb, TA); tma2d(dst, &m.xn, 8 * a8 + (pha || (n >= 15 && n < 20) ? 0 : 320), qt * 128, fb); }
      }
      a8 += 8; if (a8 == 40) { a8 = 0; pha ^= 1; }
    }
    if (lane < 3) mbar_arrive(bar_z);
  }
  return budget;
}

__global__ void __launch_bounds__(384, 1) __cluster_dims__(2, 1, 1)
fused_kernel(const Params p, const __grid_constant__ Maps m) {
  SMEM_LAYOUT
  const int wi = __shfl_sync(~0u, threadIdx.x >> 5, 0), wg = wi >> 2;
  const int lane = threadIdx.x & 31;
  const int cl = cluster_role();
  const int rank = blockIdx.x & 1;

  if (cl >= 64) {
    const unsigned epoch = (unsigned)(__ldcg(&p.s->done) >> 7);
    side_cta(p, 2 * cl + rank - 128, epoch, (float*)smem_raw);
    return;
  }
  const int qt = (cl & 7) * 2 + rank, hg = cl >> 3;
  const int kq = hg >> 1, nh = hg & 1;

  const int s0 = qt < 8 ? 0 : 5, kg0 = 10 * ((qt >> 1) & 3);
  if (elect()) {
    const int c = (int)(0x5ff7700000ull >> (4 * wi) & 15) + 1;
    for (int i = 0; i < 4; i++) mbar_init(bar_a + 32 * wi + 8 * i, c);
    asm volatile("fence.mbarrier_init.release.cluster;" ::: "memory");
  }
  __syncwarp();
  cluster_arrive();
  if (wi < 2 && elect()) {
    if (wi) { asm volatile("prefetch.tensormap [%0];" ::"l"(&m.wq) : "memory"); mbar_expect_tx(bar_b, TB); mbar_expect_tx(bar_b + 8, TB); }
    else for (int i = 0; i < 2; i++) { mbar_expect_tx(bar_a + 8 * i, TA); tma2d(sb + i * TA, &m.x, 64 * (s0 + i), qt * 128, bar_a + 8 * i); }
  }
  __syncwarp();
  cluster_wait();
  if (wi == 1 && elect())
    for (int i = 0; i < 2; i++) tma4d_mc(sb + OFF_B + i * TB + rank * (TB / 2), &m.wq, 12 * hg, 8 * (s0 + i) + 4 * rank, bar_b + 8 * i);
  if (wg > 0) {
    const int w = wg - 1;
    const int cw = wi - 4;
    asm volatile("setmaxnreg.inc.sync.aligned.u32 232;");
    uint32_t fr[48];
    reg_fence(fr);
    auto ln_row = [&]() { int v = qt * 128 + hg * 16 + cw * 2 + (lane >> 4); asm volatile("" : "+r"(v)); return v; };
    uint32_t rel_addr;
    asm volatile("mapa.shared::cluster.u32 %0, %1, %2;" : "=r"(rel_addr) : "r"(bar_b + EB), "r"(lane & 1));
    auto rel_a = [&](uint32_t o8) { if (lane == 0) mbar_arrive(bar_a + EA + o8); };
    auto rel_b = [&](uint32_t o8) { if (lane < 2) mbar_arrive_cluster(rel_addr + o8); };
    uint32_t b8 = 0, phb = 0;
    auto next_pair = [&]() { b8 += 16; if (b8 == 48) { b8 = 0; phb ^= 1; } };
    const int g = lane >> 2, q = lane & 3;
    constexpr uint64_t HI_A = desc_hi(16, 1024, 1);
    constexpr uint64_t HI_W = desc_hi(1024, 3072, 1);
    constexpr uint64_t HI_O = desc_hi(2048, 512, 2);
    if (w == 1) asm volatile("bar.arrive 1, 256;" ::: "memory");

    uint32_t zero; asm volatile("mov.u32 %0, %%tid.y;" : "=r"(zero));
    float acc[96];
    uint4* optr = p.s->o + (size_t)(qt * 192 + hg * 24) * 512 + (cw * 16 + g) * 4 + (q ^ ((g >> 1) & 3));
    uint32_t rl[4];
    auto store_o = [&](int pp) {
#pragma unroll
      for (int i = (12 * pp + 8) / 9; i < (12 * (pp + 1) + 8) / 9; i++) {
#pragma unroll
        for (int k = 4 * i; k < 4 * i + 4; k++)
          asm volatile("{\n.reg .b32 t;\nmul.rn.bf16x2 t, %0, %2;\nfma.rn.bf16x2 %0, %0, %1, t;\n}\n" : "+r"(fr[k]) : "r"(rl[i & 1]), "r"(rl[2 + (i & 1)]));
        fr[4 * i] &= ~1u;
        optr[(i >> 1) * 512 + (i & 1) * 32] = make_uint4(fr[4 * i], fr[4 * i + 1], fr[4 * i + 2], fr[4 * i + 3]);
      }
      if (pp == 8) optr += 6 * 512;
    };
    auto fresh = [&]() { uint32_t v = sb; asm volatile("" : "+r"(v)); return v; };
    reg_fence(rl);

#pragma unroll 1
    for (int u = 0; u < 4; u++) {
      const uint32_t sq = fresh();
      const uint64_t dA = mkdesc(sq + w * 8192, HI_A), dB0 = mkdesc(sq + OFF_B, HI_W);
      uint32_t pb8 = 0;
#pragma unroll
      for (int s = 0; s < 10; s++) {
        const uint32_t o8 = b8 + 8 * (s & 1);
        const uint64_t dW = dB0 + o8 * (TB >> 7);
        mbar_wait(bar_a + 8 * (s % 5), s / 5);
        mbar_wait(bar_b + o8, phb);
        if (s == 9 || (s >= LS && u == 0)) asm volatile("bar.sync %0, 256;" ::"r"(1 + w) : "memory");
        WG_FENCE();
#pragma unroll
        for (int kk = 0; kk < 4; kk++) wg_ss192t(acc, dA + ((s % 5) * (TA >> 4) + kk * 2), dW + kk * 384, kk != 0 || s != 0);
        WG_COMMIT();
        if (s >= LS && (s == 9) == (u > 0)) asm volatile("bar.arrive %0, 256;" ::"r"(2 - w) : "memory");
        if (s > 0) { WG_WAIT(1); rel_a(8 * ((s - 1) % 5)); rel_b(pb8); }
        if (s < 9) {
          if (u > 0) store_o(s);
          else { if (s == 6 && lane == 0) mbar_arrive(bar_c); ln_piece(p, fr, s, ln_row(), lane & 15); }
        }
        if (s == 8) { __syncwarp(); if (lane == 0) mbar_arrive(bar_o); }
        pb8 = o8;
        if (s & 1) next_pair();
      }
      if (u == 0) {
        mbar_wait(bar_s, 0);
        const uint2 s0 = lds64(s_stat + (cw * 16 + g) * 8), s1 = lds64(s_stat + 64 + (cw * 16 + g) * 8);
        const uint32_t msk = q == 0 ? 0xffffffffu : q == 1 ? 0xffffu : 0u;
        const float c0 = SM_C * __uint_as_float(s0.y), c1 = SM_C * __uint_as_float(s1.y);
        uint32_t am[4] = {(s0.x ^ 0x80008000u) & msk, (s1.x ^ 0x80008000u) & msk, 0, 0};
        reg_fence(am);
        WG_FENCE();
        wg_rs192t(acc, am[0], am[1], am[2], am[3], mkdesc(sb, desc_hi(1024, 0, 1)), 1);
        WG_COMMIT();
        asm volatile("bar.arrive %0, 256;" ::"r"(2 - w) : "memory");
        WG_WAIT(0);
        reg_fence(acc);
#pragma unroll
        for (int i = 0; i < 24; i++) { acc[4 * i] *= c0; acc[4 * i + 1] *= c0; acc[4 * i + 2] *= c1; acc[4 * i + 3] *= c1; }
      } else { WG_WAIT(0); reg_fence(acc); }
      rel_b(pb8);
      rel_a(32);
#pragma unroll
      for (int i = 0; i < 48; i++) fr[i] = pack_bf16(acc[2 * i], acc[2 * i + 1]);
      reg_fence(fr);
      float sc[32], l0 = 0.f, l1 = 0.f;
      uint32_t pf[16], k8;
      auto pack_p = [&](const float (&s_)[32], int from = 0, int to = 16) {
#pragma unroll
        for (int i = from; i < to; i++) pf[i] = pack_bf16(s_[2 * i], s_[2 * i + 1]);
      };
      auto scores = [&](int j, int pass = 11) {
        k8 = b8 + 8;
        mbar_wait(bar_b + k8, phb);
        next_pair();
        mbar_wait(bar_b + b8, phb);
        const uint64_t dk = mkdesc(sb + OFF_B, HI_W) + k8 * (TB >> 7);
        asm volatile("bar.sync %0, 256;" ::"r"(1 + w) : "memory");
        WG_FENCE();
#pragma unroll
        for (int t = 0; t < 12; t++) {
          wg_rs64(sc, fr[4 * t], fr[4 * t + 1], fr[4 * t + 2], fr[4 * t + 3], dk + (t >> 2) * 64 + (t & 3) * 2, t != 0);
          if (t == 11) WG_COMMIT();
          if (t == pass) asm volatile("bar.arrive %0, 256;" ::"r"(2 - w) : "memory");
        }
      };
      auto pv = [&](int add) {
        const uint64_t dv = mkdesc(sb + OFF_B, HI_W) + b8 * (TB >> 7);
#pragma unroll
        for (int kk = 0; kk < 4; kk++) wg_rs192t(acc, pf[4 * kk], pf[4 * kk + 1], pf[4 * kk + 2], pf[4 * kk + 3], dv + kk * 384, kk != 0 || add);
        WG_COMMIT();
      };
      auto finish = [&]() {
        WG_WAIT(1);
        reg_fence(sc);
        exp_block(sc, l0, l1);
        rel_b(k8 + (__float_as_uint(l0) & __float_as_uint(l1) & zero));
        WG_WAIT(0);
        reg_fence(acc); reg_fence(pf);
        rel_b(b8);
        pack_p(sc);
      };
      {
        mbar_wait(bar_b + b8, phb);
        const uint64_t dk = mkdesc(sb + OFF_B, HI_W) + b8 * (TB >> 7);
        asm volatile("bar.sync %0, 256;" ::"r"(1 + w) : "memory");
#pragma unroll
        for (int t = 0; t < 12; t++) {
          if (t == 0) WG_FENCE();
          wg_rs64(sc, fr[4 * t], fr[4 * t + 1], fr[4 * t + 2], fr[4 * t + 3], dk + (t >> 2) * 64 + (t & 3) * 2, t != 0);
          if (t == 7) asm volatile("bar.arrive %0, 256;" ::"r"(2 - w) : "memory");
        }
        WG_COMMIT();
        WG_WAIT(0);
        reg_fence(sc);
        constexpr int NE = 8;
        float s0[32];
#pragma unroll
        for (int i = 0; i < 32; i++) s0[i] = i < NE ? sc[i] : __uint_as_float(__float_as_uint(sc[i]) ^ zero);
        exp_block(s0, l0, l1, 0, NE);
        pack_p(s0, 0, NE / 2);
#pragma unroll
        for (int i = NE; i < 32; i++) asm volatile("" : "+f"(s0[i])::"memory");
#pragma unroll
        for (int i = 0; i < NE / 2; i++) asm volatile("" : "+r"(pf[i])::"memory");
        rel_b(b8);
        scores(1, 8);
        const uint32_t z = lds32(s_stat) & zero;
#pragma unroll
        for (int i = NE; i < 32; i++) {
          asm("{\n.reg .pred p;\nsetp.eq.u32 p, %1, 0;\n@p ex2.approx.ftz.f32 %0, %0;\n}\n" : "+f"(s0[i]) : "r"(z));
          if (i & 2) l1 += s0[i]; else l0 += s0[i];
        }
        pack_p(s0, NE / 2, 16);
        reg_fence(pf);
        WG_FENCE();
        pv(0);
        finish();
      }
#pragma unroll 1
      for (int j = 2; j < 8; j++) { scores(j); pv(1); finish(); }
      const uint32_t v8 = b8 + 8;
      mbar_wait(bar_b + v8, phb);
      next_pair();
      {
        const uint64_t dv = mkdesc(sb + OFF_B, HI_W) + v8 * (TB >> 7);
        asm volatile("bar.sync %0, 256;" ::"r"(1 + w) : "memory");
        WG_FENCE();
#pragma unroll
        for (int kk = 0; kk < 4; kk++) {
          wg_rs192t(acc, pf[4 * kk], pf[4 * kk + 1], pf[4 * kk + 2], pf[4 * kk + 3], dv + kk * 384, 1);
          if (kk == 1 && (u < 3 || w == 0)) asm volatile("bar.arrive %0, 256;" ::"r"(2 - w) : "memory");
        }
        WG_COMMIT();
      }
      l0 = quad_sum(l0); l1 = quad_sum(l1);
      const bool unsafe = __any_sync(~0u, !(l0 >= SM_LO && l1 >= SM_LO && l0 + l1 <= SM_HI));
      l0 = rcp(l0); l1 = rcp(l1);
      rl[0] = pack_bf16(l0, l0); rl[1] = pack_bf16(l1, l1);
      l0 -= bf_lo(rl[0]); l1 -= bf_lo(rl[1]);
      rl[2] = pack_bf16(l0, l0); rl[3] = pack_bf16(l1, l1);
      WG_WAIT(0);
      reg_fence(acc);
      rel_b(v8);
      if (__builtin_expect(unsafe, 0)) {
        int o = hg * 4 + u; asm volatile("" : "+r"(o));
        o = (o * SKC + (SKC - WIN) + g) * (DH / 2) + q;
#pragma unroll
        for (int i = 0; i < 12; i++) optr[(i >> 1) * 512 + (i & 1) * 32] = make_uint4(fr[4 * i], fr[4 * i + 1], fr[4 * i + 2], fr[4 * i + 3]);
        safe_head((const uint32_t*)p.k + o, (const uint32_t*)p.v + o, optr);
#pragma unroll
        for (int i = 0; i < 12; i++) { const uint4 v = optr[(i >> 1) * 512 + (i & 1) * 32]; fr[4 * i] = v.x; fr[4 * i + 1] = v.y; fr[4 * i + 2] = v.z; fr[4 * i + 3] = v.w; }
        rl[0] = rl[1] = 0x3f803f80u; rl[2] = rl[3] = 0;
      } else {
#pragma unroll
        for (int i = 0; i < 24; i++) {
          fr[8 * (i >> 2) + (i & 3)] = pack_bf16(acc[4 * i], acc[4 * i + 1]);
          fr[8 * (i >> 2) + 4 + (i & 3)] = pack_bf16(acc[4 * i + 2], acc[4 * i + 3]);
        }
      }
    }

    float aF[80], aS[80];
    uint32_t pha = 0, a8 = 0, pa8 = 0, pb8 = 0;
#pragma unroll 1
    for (int s = 0; s < 19; s++) {
      const uint64_t d0 = mkdesc(sb, HI_O), dO = d0 + (a8 * (TA >> 7) + w * 256), dB = d0 + ((OFF_B >> 4) + b8 * (TB >> 7));
      mbar_wait(bar_a + a8, pha);
      mbar_wait(bar_b + b8, phb);
      WG_FENCE();
#pragma unroll
      for (int kk = 0; kk < 4; kk++) wg_ss160t(aF, dO + ((kk >> 1) * 512 + (kk & 1) * 2), dB + ((kk >> 1) * 640 + (kk & 1) * 64), kk != 0 || s != 0);
      WG_COMMIT();
      mbar_wait(bar_b + b8 + 8, phb);
      WG_WAIT(1);
      if (s > 0) { rel_a(pa8); rel_b(pb8 + 8); }
      WG_FENCE();
#pragma unroll
      for (int kk = 0; kk < 4; kk++) wg_ss160t(aS, dO + ((kk >> 1) * 512 + (kk & 1) * 2), dB + ((TB >> 4) + (kk >> 1) * 640 + (kk & 1) * 64), kk != 0 || s != 0);
      WG_COMMIT();
      if (s < 9) {
#pragma unroll
        for (int pp = 0; pp < 9; pp++) if (s == pp) store_o(pp);
        if (s == 8) { __syncwarp(); if (lane == 0) mbar_arrive(bar_o); }
      } else if (s < 15) {
        const int b = 2 * cw + ((lane >> 3) & 1);
        uint32_t ga = sb + OFF_B + TW + ((b * 11) >> 5) * (TB - 3840) + b * 1280 + (lane & 7) * 160 + (lane >> 4) * 16;
        if (s < 14) {
          mbar_wait(bar_x, 0);
          ga += 32 * (s - 9);
          ldsm4(ga, fr);
#pragma unroll
          for (int i = 0; i < 4; i++) {
            const uint2 st = lds64(s_stat + (cw * 16 + g + 8 * (i & 1)) * 8);
            const uint32_t d = hsub2(fr[i], st.x), xn = pack_bf16(bf_lo(d) * __uint_as_float(st.y), bf_hi(d) * __uint_as_float(st.y));
            fr[i] = pack_bf16(silu_f(bf_lo(xn)), silu_f(bf_hi(xn)));
          }
          stsm4(ga, fr);
        } else {
          mbar_wait(bar_u, 0);
          const uint2 sel = lds64(s_sel);
          const uint32_t row = qt * 128 + cw * 16 + (lane & 15);
          if (row == sel.x || row == sel.y) ga = s_sel + 16 + (row == sel.y ? 160 : 0) + (lane >> 4) * 16;
#pragma unroll
          for (int k = 0; k < 5; k++) ldsm4(ga + 32 * k, fr + 4 * k);
        }
      }
      WG_WAIT(1);
      rel_b(b8);
      pa8 = a8; a8 += 8; if (a8 == 40) { a8 = 0; pha ^= 1; }
      pb8 = b8; next_pair();
    }
    const int t128 = threadIdx.x & 127;
    uint4* const xbase = p.s->o + (size_t)(qt * 192 + nh * 24 + 10) * 512 + w * 640 + t128;
    uint4* const dst = xbase + kq * (48 * 512);
    float q1[40], q2[40], oth[40], own[40];
    auto take = [&](float (&x)[40], const float* a, uint32_t z) {
#pragma unroll
      for (int k = 0; k < 40; k++) x[k] = __uint_as_float(__float_as_uint(a[k]) ^ z);
      reg_fence(x);
    };
    reg_fence(aF);
    take(q1, aF, zero);
    auto fa = [&](int i) { return mbar_try(bar_a + 8 * ((4 + i) % 5), i == 0); };
    auto fb = [&](int e) { return mbar_try(bar_b + 8 * (e % 6), (e / 6) & 1); };
    auto send = [&](int m) {
      const float* v = (m < 5 ? q1 : m < 10 ? q2 : oth) + 8 * (m % 5);
      st_pkt(dst + (m / 5) * 1280 + (m % 5) * 128, pack_bf16(v[0], v[1]) | 1, pack_bf16(v[2], v[3]), pack_bf16(v[4], v[5]), pack_bf16(v[6], v[7]));
    };
    static_for<20>([&](auto n_) {
      constexpr int n = n_.value, i = end_stage(n), e = 142 + n / 2, qi = n == 4 ? 1 : n == 6 ? 0 : n / 5;
      float (&acc_)[40] = qi == 0 ? q1 : qi == 1 ? q2 : qi == 2 ? oth : own;
      if (n == 0) while (!(fa(0) & fa(1) & fb(142) & fb(143))) {}
      if (n == 2) while (!(fa(2) & fa(3) & fb(144))) {}
      if (n == 6) while (!(fa(4) & fb(145) & fb(146) & mbar_try(bar_z, 0))) {}
      if (n == 10) while (!(fb(147) & fb(148) & fb(149))) {}
      const uint64_t d0 = mkdesc(fresh(), HI_O), dw = d0 + w * 256;
      WG_FENCE();
#pragma unroll
      for (int kk = 0; kk < 4; kk++)
        wg_ss80t(acc_, dw + (((4 + i) % 5) * (TA >> 4) + (kk >> 1) * 512 + (kk & 1) * 2),
                 d0 + ((OFF_B >> 4) + (e % 6) * (TB >> 4) + (n & 1) * 768 + (kk >> 1) * 384 + (kk & 1) * 64), 1);
      WG_COMMIT();
      if ((!(n & 1) && n <= 16 && n != 12) || n == 15 || n == 7) WG_WAIT(1);
      if (n == 0) rel_a(24);
      if (!(n & 1) && n <= 8) rel_b(8 * ((e - 1) % 6));
      if (n == 0) take(q2, aF + 40, lds32(s_stat) & zero);
      if (n == 10 || n == 14 || n == 16) rel_a(4u * n - 40);
      if (n == 7) reg_fence(q1);
      if (n == 10) reg_fence(q2);
      if (n == 15) reg_fence(oth);
      if (n == 14 || n == 17) while (!fb(n == 14 ? 150 : 151)) {}
      static_for<sent(n + 1) - sent(n)>([&](auto k_) { send(sent(n) + k_.value); });
      if (n == 8) {
        reg_fence(aS);
#pragma unroll
        for (int k = 0; k < 40; k++) oth[k] = kq & 1 ? aS[k] : aS[40 + k];
        reg_fence(oth);
      }
      if (n == 10) {
        reg_fence(aS);
        const bool odd = (kq ^ (lds32(s_stat) & zero)) & 1;
#pragma unroll
        for (int k = 0; k < 40; k++) own[k] = odd ? aS[40 + k] : aS[k];
        reg_fence(own);
      }
    });
    {
      auto poll = [&](int e, uint4 (&v)[5]) {
#pragma unroll
        for (int i = 0; i < 5; i++) v[i] = ld_pkt(xbase + (kq ^ (e < 2 ? 2 + e : 1)) * (48 * 512) + (e < 2 ? kq & 1 : 2) * 1280 + i * 128);
      };
      auto check = [&](int e, uint4 (&v)[5]) {
        auto tags = [&]() { uint32_t t; asm("{\n.reg .b32 t;\nlop3.b32 t, %1, %2, %3, 0x80;\nlop3.b32 %0, t, %4, %5, 0x80;\n}\n" : "=r"(t) : "r"(v[0].x), "r"(v[1].x), "r"(v[2].x), "r"(v[3].x), "r"(v[4].x)); return t & 1; };
        while (!__all_sync(~0u, tags())) poll(e, v);
      };
      auto add = [&](const uint4 (&v)[5]) {
#pragma unroll
        for (int i = 0; i < 5; i++) {
          float* o = own + 8 * i;
          o[0] += bf_lo(v[i].x); o[1] += bf_hi(v[i].x); o[2] += bf_lo(v[i].y); o[3] += bf_hi(v[i].y);
          o[4] += bf_lo(v[i].z); o[5] += bf_hi(v[i].z); o[6] += bf_lo(v[i].w); o[7] += bf_hi(v[i].w);
        }
      };
      uint4 v[2][5];
      uint32_t xr[20];
      const uint32_t xs = sb + OFF_B + 2 * TB + cw * 2560, xa = xs + (lane & 15) * 160 + (lane >> 4) * 16;
      while (!(mbar_try(bar_e, 0) & mbar_try(bar_e + 8, 0))) {}
#pragma unroll
      for (int i = 0; i < 10; i++) v[i / 5][i % 5] = lds128(sb + OFF_B + (3 + i / 5) * TB + (w * 640 + i % 5 * 128 + t128) * 16);
#pragma unroll
      for (int k = 0; k < 5; k++) ldsm4(xa + 32 * k, xr + 4 * k);
      check(0, v[0]); check(1, v[1]);
#pragma unroll
      for (int i = 0; i < 5; i++) v[0][i] = make_uint4(hadd2(v[0][i].x, v[1][i].x), hadd2(v[0][i].y, v[1][i].y), hadd2(v[0][i].z, v[1][i].z), hadd2(v[0][i].w, v[1][i].w));
      WG_WAIT(0);
      reg_fence(own);
      poll(2, v[1]);
      add(v[0]);
      reg_fence(own);
      check(2, v[1]);
      add(v[1]);
      if (lane == 0) mbar_arrive(bar_w);
      cluster_arrive();
#pragma unroll
      for (int i = 0; i < 20; i++) xr[i] = hadd2(xr[i], hmul2(pack_bf16(own[2 * i], own[2 * i + 1]), fr[i]));
#pragma unroll
      for (int k = 0; k < 5; k++) stsm4(xa + 32 * k, xr + 4 * k);
      asm volatile("fence.proxy.async.shared::cta;" ::: "memory");
      __syncwarp();
      if (elect()) {
        tma2d_store(&m.out, xs, nh * 320 + kq * 80, qt * 128 + cw * 16);
        asm volatile("cp.async.bulk.commit_group;\ncp.async.bulk.wait_group.read 0;" ::: "memory");
      }
      __syncwarp();
    }
    cluster_wait();
  } else {
    asm volatile("setmaxnreg.dec.sync.aligned.u32 40;");
    uint32_t tid_; asm volatile("mov.u32 %0, %%tid.x;" : "=r"(tid_));
    const int warp = __shfl_sync(~0u, tid_ >> 5, 0);
    auto is_warp = [&](int k) { uint32_t e; asm volatile("{\n.reg .pred q;\nsetp.eq.u32 q, %1, %2;\nselp.u32 %0, 1, 0, q;\n}" : "=r"(e) : "r"(warp), "r"(k)); return e != 0; };
    if (warp > 0) {
      const unsigned epoch = (unsigned)(__ldcg(&p.s->done) >> 7);
      int budget = WAIT_BUDGET;
      const uint32_t tag = epoch + 1;
      mbar_wait(bar_b + (kg0 & ~7), 0, budget); mbar_wait(bar_b + (kg0 & ~7) + 8, 0, budget);
      float cs0 = 0.f, cs1 = 0.f;
      const int n = rank * 96 + (warp - 1) * 32;
#pragma unroll 1
      for (int kg = kg0 + (lane >> 4) * 5, e = kg + 5; kg < e; kg++) {
        const uint32_t ad = sb + OFF_B + kg * 3072 + (n >> 6) * 1024 + (n & 63) * 2 + (lane & 15) * 4;
#pragma unroll
        for (int k = 0; k < 8; k++) { const uint32_t v = lds32(ad ^ (k * 0x90)); cs0 += bf_lo(v); cs1 += bf_hi(v); }
      }
      cs0 += __shfl_xor_sync(~0u, cs0, 16); cs1 += __shfl_xor_sync(~0u, cs1, 16);
      if (lane < 16) st_pkt8((uint2*)(p.s->cs + (hg * 4 + (qt >> 2)) * 96 + (n >> 1) + lane) + ((qt >> 1) & 1), (__float_as_uint(cs0) & ~3u) | (tag & 3), __float_as_uint(cs1));
      if (lane < 2) { uint32_t a; asm volatile("mapa.shared::cluster.u32 %0, %1, %2;" : "=r"(a) : "r"(bar_d), "r"(lane)); mbar_arrive_cluster(a); }
      mbar_wait(bar_c, 0, budget);
      uint4 v[5];
      while (true) {
        uint32_t bad = 0;
#pragma unroll
        for (int i = 0; i < 5; i++) v[i] = ld_pkt(i < 4 ? p.s->cs + (hg * 4 + i) * 96 + (tid_ - 32) : (const uint4*)p.s->stat + qt * 64 + (tid_ & 63));
#pragma unroll
        for (int i = 0; i < 5; i++) bad |= (v[i].x ^ tag) | (v[i].z ^ tag);
        if (!__any_sync(~0u, bad & 3) || --budget < 0) break;
      }
      asm volatile("st.shared.v4.u32 [%0], {%1,%2,%3,%4};" ::"r"(s_stat + (tid_ & 63) * 16), "r"(__byte_perm(v[4].x, 0, 0x3232)), "r"(v[4].y), "r"(__byte_perm(v[4].z, 0, 0x3232)), "r"(v[4].w) : "memory");
      cs0 = cs1 = 0.f;
#pragma unroll
      for (int i = 0; i < 4; i++) { cs0 += __uint_as_float(v[i].x & ~3u) + __uint_as_float(v[i].z & ~3u); cs1 += __uint_as_float(v[i].y) + __uint_as_float(v[i].w); }
#pragma unroll
      for (int k = 0; k < 8; k++) {
        const uint32_t t = k < 3 ? pack_bf16(cs0, cs1) : 0;
        sts32((sb + (warp - 1) * 1024 + lane * 4) ^ (k * 0x90), t);
        cs0 -= bf_lo(t); cs1 -= bf_hi(t);
      }
      asm volatile("fence.proxy.async.shared::cta;" ::: "memory");
      __syncwarp();
      if (lane < 2) mbar_arrive(bar_s);
      budget = errands(p.s, m, qt, hg, warp, tag, budget);
      if (is_warp(2)) {
        mbar_wait(bar_w, 0, budget);
        if (budget < 0) asm volatile("st.global.u32 [%0], %1;" ::"l"(0ull), "r"(budget) : "memory");
      }
    } else {
      uint32_t fb = bar_b + 16, dst = sb + OFF_B + 2 * TB, ph = 1;
      auto next = [&]() { fb += 8; dst += TB; if (fb == bar_b + 48) { fb = bar_b; dst = sb + OFF_B; ph ^= 1; } };
#pragma unroll 1
      for (int u = 0; u < 4; u++) {
        const int h = hg * 4 + u;
        int s = u ? (u == 2 ? 5 : 0) : s0 + 2;
#pragma unroll 1
        for (int i = u ? 0 : 2; i < 10; i++) {
          if (u == 0) {
            const uint32_t a8 = 8 * (i < 5 ? i : i - 5);
            mbar_wait(bar_a + 8 * (i < 7 ? i - 2 : i - 7), i >= 7);
            mbar_wait(bar_a + EA + a8, i < 5);
            if (elect()) { mbar_expect_tx(bar_a + a8, TA); tma2d(sb + a8 * (TA >> 3), &m.x, 64 * s, qt * 128, bar_a + a8); }
            if (i == 6 + (kg0 >> 3)) mbar_wait(bar_d, 0);
          }
          mbar_wait(fb + EB, ph);
          if (elect()) { mbar_expect_tx(fb, TB); tma4d_mc(dst + rank * (TB / 2), &m.wq, 3 * h, 8 * s + 4 * rank, fb); }
          next();
          if (++s == 10) s = 0;
        }
        const int kv0 = (h * SKC + (SKC - WIN)) / 8 + 4 * rank;
#pragma unroll 1
        for (int i = 0; i < 16; i++) {
          const bool isk = (0x2AAB >> i) & 1;
          mbar_wait(fb + EB, ph);
          if (elect()) { mbar_expect_tx(fb, TB); tma4d_mc(dst + rank * (TB / 2), isk ? &m.k : &m.v, 0, kv0 + 8 * (isk ? (i + 1) >> 1 : (i - 1) >> 1), fb); }
          next();
        }
      }
      const int cF = 10 * nh + 5 - 5 * (kq >> 1), cS = 10 * nh + 5 * (kq >> 1);
      const int kb = 4 * (k_block(lane, hg) + rank);
#pragma unroll 1
      for (int n = 0; n < 38; n++) {
        const int c2 = __shfl_sync(~0u, kb, n >> 1);
        mbar_wait(fb + EB, ph);
        if (elect()) { mbar_expect_tx(fb, TW); tma5d_mc(dst + rank * (TW / 2), &m.wo, c2, n & 1 ? cS : cF, fb); }
        next();
      }
      const int odd = ((0x7fb0 ^ (kq & 1 ? 0xffc00 : 0)) >> lane) & 1;
      const int tq = __shfl_sync(~0u, kb, 19 + end_stage(lane)) << 16 | odd << 7 | ((lane < 10 ? cF : cS) + 2 * odd);
#pragma unroll 1
      for (int n = 0; n < 20; n += 2) {
        const int t0 = __shfl_sync(~0u, tq, n), t1 = __shfl_sync(~0u, tq, n + 1);
        mbar_wait(fb + EB, ph);
        if (elect()) {
          mbar_expect_tx(fb, TB);
          tma5d_mc(dst + rank * (TB / 4), (const CUtensorMap*)((const char*)m.w3 + (t0 & 128)), t0 >> 16, t0 & 31, fb);
          tma5d_mc(dst + TB / 2 + rank * (TB / 4), (const CUtensorMap*)((const char*)m.w3 + (t1 & 128)), t1 >> 16, t1 & 31, fb);
        }
        next();
      }
      mbar_wait(bar_a + EA, 0);
      if (elect()) { mbar_expect_tx(bar_e, TW); tma2d(sb + OFF_B + 2 * TB, &m.xe, nh * 320 + kq * 80, qt * 128, bar_e); }
      const uint4* src = p.s->o + (size_t)(qt * 192 + nh * 24 + 10 + (kq ^ 2) * 48) * 512 + (kq & 1) * 1280;
      mbar_wait(bar_a + EA + 16, 0);
      if (elect()) {
        mbar_expect_tx(bar_e + 8, 2 * TW);
        bulk_load(sb + OFF_B + 3 * TB, src, TW, bar_e + 8);
        bulk_load(sb + OFF_B + 4 * TB, src + (kq & 1 ? -48 * 512 : 48 * 512), TW, bar_e + 8);
      }
    }
    cluster_sync();
  }
}

typedef CUresult (*EncodeFn)(CUtensorMap*, CUtensorMapDataType, cuuint32_t, void*, const cuuint64_t*, const cuuint64_t*,
                             const cuuint32_t*, const cuuint32_t*, CUtensorMapInterleave, CUtensorMapSwizzle,
                             CUtensorMapL2promotion, CUtensorMapFloatOOBfill);

void encode(EncodeFn fn, CUtensorMap* tm, void* base, int rank, const cuuint64_t* dims, const cuuint64_t* strides,
            const cuuint32_t* box, CUtensorMapSwizzle sw) {
  const cuuint32_t es[5] = {1, 1, 1, 1, 1};
  fn(tm, CU_TENSOR_MAP_DATA_TYPE_BFLOAT16, rank, base, dims, strides, box, es, CU_TENSOR_MAP_INTERLEAVE_NONE, sw,
     CU_TENSOR_MAP_L2_PROMOTION_L2_128B, CU_TENSOR_MAP_FLOAT_OOB_FILL_NONE);
}

}

extern "C" void kernel_launch(void* const* d_in, const int* in_sizes, int n_in, void* d_out, int out_size) {
  static EncodeFn fn = nullptr;
  static Scratch* scr = nullptr;
  if (!fn) {
    void* f = nullptr;
    cudaDriverEntryPointQueryResult st;
    cudaGetDriverEntryPoint("cuTensorMapEncodeTiled", &f, cudaEnableDefault, &st);
    fn = (EncodeFn)f;
    cudaGetSymbolAddress((void**)&scr, g_scratch);
    cudaFuncSetAttribute(fused_kernel, cudaFuncAttributeMaxDynamicSharedMemorySize, SMEM_BYTES);
  }
  Maps m;
  { const cuuint64_t d[2] = {DM, SQ}, s[1] = {DM * 2}; const cuuint32_t b[2] = {64, 128};
    encode(fn, &m.x, d_in[0], 2, d, s, b, CU_TENSOR_MAP_SWIZZLE_128B);
    encode(fn, &m.xn, scr->xn, 2, d, s, b, CU_TENSOR_MAP_SWIZZLE_128B); }
  { const cuuint64_t d[4] = {64, 8, QD / 64, DM / 8}, s[3] = {QD * 2, 128, 8 * QD * 2}; const cuuint32_t b[4] = {64, 8, 3, 4};
    encode(fn, &m.wq, d_in[3], 4, d, s, b, CU_TENSOR_MAP_SWIZZLE_128B); }
  { const cuuint64_t d[4] = {64, 8, 3, NH * SKC / 8}, s[3] = {DH * 2, 128, 8 * DH * 2}; const cuuint32_t b[4] = {64, 8, 3, 4};
    encode(fn, &m.k, d_in[1], 4, d, s, b, CU_TENSOR_MAP_SWIZZLE_128B);
    encode(fn, &m.v, d_in[2], 4, d, s, b, CU_TENSOR_MAP_SWIZZLE_128B); }
  {
    const cuuint64_t d[5] = {32, 2, QD / 8, 4, DM / 32}, s[4] = {DM * 2, 8 * DM * 2, 2 * DM * 2, 64}; const cuuint32_t b[5] = {32, 2, 4, 4, 5};
    encode(fn, &m.wo, d_in[4], 5, d, s, b, CU_TENSOR_MAP_SWIZZLE_64B);
    const cuuint32_t b3[5] = {32, 2, 4, 4, 3};
    encode(fn, &m.w3[0], d_in[4], 5, d, s, b3, CU_TENSOR_MAP_SWIZZLE_64B);
    encode(fn, &m.w3[1], (char*)d_in[4] + 32, 5, d, s, b3, CU_TENSOR_MAP_SWIZZLE_64B); }
  { const cuuint64_t d[2] = {DM, SQ}, s[1] = {DM * 2}; const cuuint32_t bg[2] = {80, 24}, bx[2] = {80, 128}, bo[2] = {80, 16};
    encode(fn, &m.xg, d_in[0], 2, d, s, bg, CU_TENSOR_MAP_SWIZZLE_NONE);
    encode(fn, &m.xe, d_in[0], 2, d, s, bx, CU_TENSOR_MAP_SWIZZLE_NONE);
    encode(fn, &m.out, d_out, 2, d, s, bo, CU_TENSOR_MAP_SWIZZLE_NONE); }
  Params p;
  p.x = (const __nv_bfloat16*)d_in[0]; p.wr = (const __nv_bfloat16*)d_in[6]; p.wg = (const __nv_bfloat16*)d_in[7];
  p.wu = (const __nv_bfloat16*)d_in[8]; p.wd = (const __nv_bfloat16*)d_in[9];

  p.k = (const __nv_bfloat16*)d_in[1]; p.v = (const __nv_bfloat16*)d_in[2]; p.s = scr;
  cudaLaunchConfig_t cfg = {};
  cfg.gridDim = dim3(132); cfg.blockDim = dim3(384); cfg.dynamicSmemBytes = SMEM_BYTES; cfg.stream = cudaStreamPerThread;
  cudaLaunchKernelEx(&cfg, fused_kernel, p, m);
}
```

```cpp
#include <cuda_runtime.h>
#include <cuda_bf16.h>
#include <cuda.h>
#include <stdint.h>

namespace {

constexpr int SQ = 2048, DM = 640, NH = 32, DH = 192, SKC = 2048, WIN = 512, FF = 1536;
constexpr int QD = NH * DH;
constexpr uint32_t TA = 16384, TB = 24576, TW = 20480, OFF_B = 5 * TA, OFF_M = OFF_B + 6 * TB, SMEM_BYTES = OFF_M + 3072;
constexpr int WAIT_BUDGET = 1 << 20;

constexpr int FL_XN = 0;
constexpr int FL_O = 512;
constexpr int FL_RD = FL_O + 1024;
constexpr int FL_FFN = FL_RD + 1024;
constexpr int FL_SIDE = FL_FFN + 32;
struct __align__(1024) Scratch {
  unsigned long long done, pad0[15];
  unsigned flag[FL_SIDE + 32];
  uint4 cand[8];
  float ffn[4 * 2 * DM];
  int sel[4];
  __nv_bfloat16 gsel[2 * DM];
  uint4 cs[8 * 4 * DH / 2];
  uint2 stat[SQ];
  __align__(1024) __nv_bfloat16 xn[SQ * DM];
  __align__(1024) uint4 o[SQ * QD / 8];
};
__device__ Scratch g_scratch;

__device__ __forceinline__ uint32_t smem_u32(const void* p) { return (uint32_t)__cvta_generic_to_shared(p); }
__device__ __forceinline__ void mbar_init(uint32_t bar, int cnt) { asm volatile("mbarrier.init.shared::cta.b64 [%0], %1;" ::"r"(bar), "r"(cnt)); }
__device__ __forceinline__ void mbar_expect_tx(uint32_t bar, uint32_t bytes) {
  asm volatile("mbarrier.arrive.expect_tx.shared::cta.b64 _, [%0], %1;" ::"r"(bar), "r"(bytes) : "memory");
}
__device__ __forceinline__ void mbar_arrive(uint32_t bar) { asm volatile("mbarrier.arrive.shared::cta.b64 _, [%0];" ::"r"(bar) : "memory"); }
__device__ __forceinline__ void mbar_arrive_cluster(uint32_t addr) { asm volatile("mbarrier.arrive.shared::cluster.b64 _, [%0];" ::"r"(addr) : "memory"); }
__device__ __forceinline__ bool mbar_try(uint32_t bar, uint32_t parity) {
  uint32_t ok;
  asm volatile("{\n.reg .pred p;\nmbarrier.try_wait.parity.shared::cta.b64 p, [%1], %2;\nselp.u32 %0, 1, 0, p;\n}\n" : "=r"(ok) : "r"(bar), "r"(parity) : "memory");
  return ok;
}
__device__ __forceinline__ void mbar_wait(uint32_t bar, uint32_t parity, int& budget) {
#pragma unroll 1
  while (!mbar_try(bar, parity)) { if (--budget < 0) break; }
}
__device__ __forceinline__ void mbar_wait(uint32_t bar, uint32_t parity) {
#pragma unroll 1
  while (!mbar_try(bar, parity)) {}
}
__device__ __forceinline__ unsigned ld_acquire(const unsigned* p) { unsigned v; asm volatile("ld.acquire.gpu.global.u32 %0, [%1];" : "=r"(v) : "l"(p) : "memory"); return v; }
__device__ __forceinline__ void wait_flag(const unsigned* p, unsigned target) {
#pragma unroll 1
  while (__any_sync(~0u, (int)(ld_acquire(p) - target) < 0)) {}
}
__device__ __forceinline__ void red_release(unsigned* p) { asm volatile("red.release.gpu.global.add.u32 [%0], 1;" ::"l"(p) : "memory"); }
__device__ __forceinline__ void fence_proxy_async() { asm volatile("fence.proxy.async.global;" ::: "memory"); }
__device__ __forceinline__ bool elect() {
  uint32_t p;
  asm volatile("{\n.reg .pred P;\nelect.sync _|P, 0xffffffff;\nselp.u32 %0, 1, 0, P;\n}\n" : "=r"(p));
  return p;
}
__device__ __forceinline__ void cluster_arrive() { asm volatile("barrier.cluster.arrive.relaxed.aligned;" ::: "memory"); }
__device__ __forceinline__ void cluster_wait() { asm volatile("barrier.cluster.wait.aligned;" ::: "memory"); }
__device__ __forceinline__ void cluster_sync() { cluster_arrive(); cluster_wait(); }
__device__ __forceinline__ void tma2d(uint32_t dst, const CUtensorMap* tm, int c0, int c1, uint32_t bar) {
  asm volatile("cp.async.bulk.tensor.2d.shared::cluster.global.mbarrier::complete_tx::bytes [%0], [%1, {%3, %4}], [%2];"
               ::"r"(dst), "l"(tm), "r"(bar), "r"(c0), "r"(c1) : "memory");
}
constexpr uint64_t POL_FIRST = 0x12F0000000000000ull;
__device__ __forceinline__ void tma4d_mc(uint32_t dst, const CUtensorMap* tm, int c2, int c3, uint32_t bar) {
  asm volatile("cp.async.bulk.tensor.4d.shared::cluster.global.mbarrier::complete_tx::bytes.multicast::cluster.L2::cache_hint [%0], [%1, {%3, %3, %4, %5}], [%2], %6, %7;"
               ::"r"(dst), "l"(tm), "r"(bar), "r"(0), "r"(c2), "r"(c3), "h"((uint16_t)3), "l"(POL_FIRST) : "memory");
}
__device__ __forceinline__ void tma5d_mc(uint32_t dst, const CUtensorMap* tm, int c2, int c4, uint32_t bar) {
  asm volatile("cp.async.bulk.tensor.5d.shared::cluster.global.mbarrier::complete_tx::bytes.multicast::cluster.L2::cache_hint [%0], [%1, {%3, %3, %4, %3, %5}], [%2], %6, %7;"
               ::"r"(dst), "l"(tm), "r"(bar), "r"(0), "r"(c2), "r"(c4), "h"((uint16_t)3), "l"(POL_FIRST) : "memory");
}
__device__ __forceinline__ void bulk_load(uint32_t dst, const void* src, uint32_t bytes, uint32_t bar) {
  asm volatile("cp.async.bulk.shared::cluster.global.mbarrier::complete_tx::bytes.L2::cache_hint [%0], [%1], %2, [%3], %4;" ::"r"(dst), "l"(src), "r"(bytes), "r"(bar), "l"(POL_FIRST) : "memory");
}
__device__ __forceinline__ void tma2d_store(const CUtensorMap* tm, uint32_t src, int c0, int c1) {
  asm volatile("cp.async.bulk.tensor.2d.global.shared::cta.bulk_group [%0, {%2, %3}], [%1];" ::"l"(tm), "r"(src), "r"(c0), "r"(c1) : "memory");
}
__device__ __forceinline__ uint32_t lds32(uint32_t a) { uint32_t v; asm volatile("ld.shared.u32 %0, [%1];" : "=r"(v) : "r"(a) : "memory"); return v; }
__device__ __forceinline__ uint2 lds64(uint32_t a) { uint2 v; asm volatile("ld.shared.v2.u32 {%0,%1}, [%2];" : "=r"(v.x), "=r"(v.y) : "r"(a) : "memory"); return v; }
__device__ __forceinline__ uint4 lds128(uint32_t a) { uint4 v; asm volatile("ld.shared.v4.u32 {%0,%1,%2,%3}, [%4];" : "=r"(v.x), "=r"(v.y), "=r"(v.z), "=r"(v.w) : "r"(a) : "memory"); return v; }
__device__ __forceinline__ void ldsm4(uint32_t a, uint32_t* v) {
  asm volatile("ldmatrix.sync.aligned.m8n8.x4.shared.b16 {%0,%1,%2,%3}, [%4];" : "=r"(v[0]), "=r"(v[1]), "=r"(v[2]), "=r"(v[3]) : "r"(a) : "memory");
}
__device__ __forceinline__ void stsm4(uint32_t a, const uint32_t* v) {
  asm volatile("stmatrix.sync.aligned.m8n8.x4.shared.b16 [%0], {%1,%2,%3,%4};" ::"r"(a), "r"(v[0]), "r"(v[1]), "r"(v[2]), "r"(v[3]) : "memory");
}
__device__ __forceinline__ void sts32(uint32_t a, uint32_t v) { asm volatile("st.shared.u32 [%0], %1;" ::"r"(a), "r"(v) : "memory"); }
__device__ __forceinline__ void st_pkt(uint4* p, uint32_t a, uint32_t b, uint32_t c, uint32_t d) {
  asm volatile("st.relaxed.gpu.global.v4.b32 [%0], {%1, %2, %3, %4};" ::"l"(p), "r"(a), "r"(b), "r"(c), "r"(d) : "memory");
}
__device__ __forceinline__ void st_pkt8(void* p, uint32_t a, uint32_t b) {
  asm volatile("{\n.reg .b64 v;\nmov.b64 v, {%1, %2};\nst.relaxed.gpu.global.b64 [%0], v;\n}\n" ::"l"(p), "r"(a), "r"(b) : "memory");
}
__device__ __forceinline__ uint4 ld_pkt(const uint4* p) {
  uint4 v;
  asm volatile("{\n.reg .b128 v;\nld.relaxed.gpu.global.b128 v, [%4];\nmov.b128 {%0, %1, %2, %3}, v;\n}\n" : "=r"(v.x), "=r"(v.y), "=r"(v.z), "=r"(v.w) : "l"(p) : "memory");
  return v;
}
__device__ __forceinline__ uint4 ldg_nc(const void* p) {
  uint4 v;
  asm volatile("ld.global.nc.v4.u32 {%0,%1,%2,%3}, [%4];" : "=r"(v.x), "=r"(v.y), "=r"(v.z), "=r"(v.w) : "l"(p));
  return v;
}
#define WG_FENCE() asm volatile("wgmma.fence.sync.aligned;" ::: "memory")
#define WG_COMMIT() asm volatile("wgmma.commit_group.sync.aligned;" ::: "memory")
#define WG_WAIT(n) asm volatile("wgmma.wait_group.sync.aligned " #n ";" ::: "memory")
template <int N> __device__ __forceinline__ void reg_fence(float (&d)[N]) {
#pragma unroll
  for (int i = 0; i < N; i++) asm volatile("" : "+f"(d[i])::"memory");
}
template <int N> __device__ __forceinline__ void reg_fence(uint32_t (&d)[N]) {
#pragma unroll
  for (int i = 0; i < N; i++) asm volatile("" : "+r"(d[i])::"memory");
}
__device__ __forceinline__ constexpr uint64_t desc_hi(uint32_t lbo, uint32_t sbo, uint64_t sw) {
  return ((uint64_t)(lbo >> 4) << 16) | ((uint64_t)(sbo >> 4) << 32) | (sw << 62);
}
__device__ __forceinline__ uint64_t mkdesc(uint32_t addr, uint64_t hi) { return hi | (uint64_t)((addr & 0x3FFFF) >> 4); }
__device__ __forceinline__ uint32_t pack_bf16(float lo, float hi) { uint32_t r; asm("cvt.rn.bf16x2.f32 %0, %1, %2;" : "=r"(r) : "f"(hi), "f"(lo)); return r; }
__device__ __forceinline__ float bf_lo(uint32_t v) { return __uint_as_float(v << 16); }
__device__ __forceinline__ float bf_hi(uint32_t v) { return __uint_as_float(v & 0xffff0000u); }
__device__ __forceinline__ uint32_t hadd2(uint32_t a, uint32_t b) { uint32_t r; asm("add.rn.bf16x2 %0, %1, %2;" : "=r"(r) : "r"(a), "r"(b)); return r; }
__device__ __forceinline__ uint32_t hsub2(uint32_t a, uint32_t b) { uint32_t r; asm("sub.rn.bf16x2 %0, %1, %2;" : "=r"(r) : "r"(a), "r"(b)); return r; }
__device__ __forceinline__ uint32_t hmul2(uint32_t a, uint32_t b) { uint32_t r; asm("mul.rn.bf16x2 %0, %1, %2;" : "=r"(r) : "r"(a), "r"(b)); return r; }
__device__ __forceinline__ float rbf(float x) { return __bfloat162float(__float2bfloat16_rn(x)); }
__device__ __forceinline__ float ex2(float x) { float y; asm("ex2.approx.ftz.f32 %0, %1;" : "=f"(y) : "f"(x)); return y; }
__device__ __forceinline__ float rcp(float x) { float y; asm("rcp.approx.ftz.f32 %0, %1;" : "=f"(y) : "f"(x)); return y; }
__device__ __forceinline__ float sigmoid_f(float x) { return rcp(1.f + ex2(x * -1.4426950408889634f)); }
__device__ __forceinline__ float silu_f(float x) { return x * sigmoid_f(x); }

__device__ __forceinline__ void wg_ss192t(float (&d)[96], uint64_t da, uint64_t db, int sd) {
  asm volatile("{\n.reg .pred p;\nsetp.ne.b32 p, %98, 0;\n"
    "wgmma.mma_async.sync.aligned.m64n192k16.f32.bf16.bf16 {%0,%1,%2,%3,%4,%5,%6,%7,%8,%9,%10,%11,%12,%13,%14,%15,%16,%17,%18,%19,%20,%21,%22,%23,%24,%25,%26,%27,%28,%29,%30,%31,%32,%33,%34,%35,%36,%37,%38,%39,%40,%41,%42,%43,%44,%45,%46,%47,%48,%49,%50,%51,%52,%53,%54,%55,%56,%57,%58,%59,%60,%61,%62,%63,%64,%65,%66,%67,%68,%69,%70,%71,%72,%73,%74,%75,%76,%77,%78,%79,%80,%81,%82,%83,%84,%85,%86,%87,%88,%89,%90,%91,%92,%93,%94,%95}, %96, %97, p, 1, 1, 0, 1;\n}\n"
    : "+f"(d[0]),"+f"(d[1]),"+f"(d[2]),"+f"(d[3]),"+f"(d[4]),"+f"(d[5]),"+f"(d[6]),"+f"(d[7]),"+f"(d[8]),"+f"(d[9]),"+f"(d[10]),"+f"(d[11]),"+f"(d[12]),"+f"(d[13]),"+f"(d[14]),"+f"(d[15]),"+f"(d[16]),"+f"(d[17]),"+f"(d[18]),"+f"(d[19]),"+f"(d[20]),"+f"(d[21]),"+f"(d[22]),"+f"(d[23]),"+f"(d[24]),"+f"(d[25]),"+f"(d[26]),"+f"(d[27]),"+f"(d[28]),"+f"(d[29]),"+f"(d[30]),"+f"(d[31]),"+f"(d[32]),"+f"(d[33]),"+f"(d[34]),"+f"(d[35]),"+f"(d[36]),"+f"(d[37]),"+f"(d[38]),"+f"(d[39]),"+f"(d[40]),"+f"(d[41]),"+f"(d[42]),"+f"(d[43]),"+f"(d[44]),"+f"(d[45]),"+f"(d[46]),"+f"(d[47]),"+f"(d[48]),"+f"(d[49]),"+f"(d[50]),"+f"(d[51]),"+f"(d[52]),"+f"(d[53]),"+f"(d[54]),"+f"(d[55]),"+f"(d[56]),"+f"(d[57]),"+f"(d[58]),"+f"(d[59]),"+f"(d[60]),"+f"(d[61]),"+f"(d[62]),"+f"(d[63]),"+f"(d[64]),"+f"(d[65]),"+f"(d[66]),"+f"(d[67]),"+f"(d[68]),"+f"(d[69]),"+f"(d[70]),"+f"(d[71]),"+f"(d[72]),"+f"(d[73]),"+f"(d[74]),"+f"(d[75]),"+f"(d[76]),"+f"(d[77]),"+f"(d[78]),"+f"(d[79]),"+f"(d[80]),"+f"(d[81]),"+f"(d[82]),"+f"(d[83]),"+f"(d[84]),"+f"(d[85]),"+f"(d[86]),"+f"(d[87]),"+f"(d[88]),"+f"(d[89]),"+f"(d[90]),"+f"(d[91]),"+f"(d[92]),"+f"(d[93]),"+f"(d[94]),"+f"(d[95])
    : "l"(da), "l"(db), "r"(sd));
}
__device__ __forceinline__ void wg_rs64(float (&d)[32], uint32_t a0, uint32_t a1, uint32_t a2, uint32_t a3, uint64_t db, int sd) {
  asm volatile("{\n.reg .pred p;\nsetp.ne.b32 p, %37, 0;\n"
    "wgmma.mma_async.sync.aligned.m64n64k16.f32.bf16.bf16 {%0,%1,%2,%3,%4,%5,%6,%7,%8,%9,%10,%11,%12,%13,%14,%15,%16,%17,%18,%19,%20,%21,%22,%23,%24,%25,%26,%27,%28,%29,%30,%31}, {%32,%33,%34,%35}, %36, p, 1, 1, 0;\n}\n"
    : "+f"(d[0]),"+f"(d[1]),"+f"(d[2]),"+f"(d[3]),"+f"(d[4]),"+f"(d[5]),"+f"(d[6]),"+f"(d[7]),"+f"(d[8]),"+f"(d[9]),"+f"(d[10]),"+f"(d[11]),"+f"(d[12]),"+f"(d[13]),"+f"(d[14]),"+f"(d[15]),"+f"(d[16]),"+f"(d[17]),"+f"(d[18]),"+f"(d[19]),"+f"(d[20]),"+f"(d[21]),"+f"(d[22]),"+f"(d[23]),"+f"(d[24]),"+f"(d[25]),"+f"(d[26]),"+f"(d[27]),"+f"(d[28]),"+f"(d[29]),"+f"(d[30]),"+f"(d[31])
    : "r"(a0), "r"(a1), "r"(a2), "r"(a3), "l"(db), "r"(sd));
}
__device__ __forceinline__ void wg_rs192t(float (&d)[96], uint32_t a0, uint32_t a1, uint32_t a2, uint32_t a3, uint64_t db, int sd) {
  asm volatile("{\n.reg .pred p;\nsetp.ne.b32 p, %101, 0;\n"
    "wgmma.mma_async.sync.aligned.m64n192k16.f32.bf16.bf16 {%0,%1,%2,%3,%4,%5,%6,%7,%8,%9,%10,%11,%12,%13,%14,%15,%16,%17,%18,%19,%20,%21,%22,%23,%24,%25,%26,%27,%28,%29,%30,%31,%32,%33,%34,%35,%36,%37,%38,%39,%40,%41,%42,%43,%44,%45,%46,%47,%48,%49,%50,%51,%52,%53,%54,%55,%56,%57,%58,%59,%60,%61,%62,%63,%64,%65,%66,%67,%68,%69,%70,%71,%72,%73,%74,%75,%76,%77,%78,%79,%80,%81,%82,%83,%84,%85,%86,%87,%88,%89,%90,%91,%92,%93,%94,%95}, {%96,%97,%98,%99}, %100, p, 1, 1, 1;\n}\n"
    : "+f"(d[0]),"+f"(d[1]),"+f"(d[2]),"+f"(d[3]),"+f"(d[4]),"+f"(d[5]),"+f"(d[6]),"+f"(d[7]),"+f"(d[8]),"+f"(d[9]),"+f"(d[10]),"+f"(d[11]),"+f"(d[12]),"+f"(d[13]),"+f"(d[14]),"+f"(d[15]),"+f"(d[16]),"+f"(d[17]),"+f"(d[18]),"+f"(d[19]),"+f"(d[20]),"+f"(d[21]),"+f"(d[22]),"+f"(d[23]),"+f"(d[24]),"+f"(d[25]),"+f"(d[26]),"+f"(d[27]),"+f"(d[28]),"+f"(d[29]),"+f"(d[30]),"+f"(d[31]),"+f"(d[32]),"+f"(d[33]),"+f"(d[34]),"+f"(d[35]),"+f"(d[36]),"+f"(d[37]),"+f"(d[38]),"+f"(d[39]),"+f"(d[40]),"+f"(d[41]),"+f"(d[42]),"+f"(d[43]),"+f"(d[44]),"+f"(d[45]),"+f"(d[46]),"+f"(d[47]),"+f"(d[48]),"+f"(d[49]),"+f"(d[50]),"+f"(d[51]),"+f"(d[52]),"+f"(d[53]),"+f"(d[54]),"+f"(d[55]),"+f"(d[56]),"+f"(d[57]),"+f"(d[58]),"+f"(d[59]),"+f"(d[60]),"+f"(d[61]),"+f"(d[62]),"+f"(d[63]),"+f"(d[64]),"+f"(d[65]),"+f"(d[66]),"+f"(d[67]),"+f"(d[68]),"+f"(d[69]),"+f"(d[70]),"+f"(d[71]),"+f"(d[72]),"+f"(d[73]),"+f"(d[74]),"+f"(d[75]),"+f"(d[76]),"+f"(d[77]),"+f"(d[78]),"+f"(d[79]),"+f"(d[80]),"+f"(d[81]),"+f"(d[82]),"+f"(d[83]),"+f"(d[84]),"+f"(d[85]),"+f"(d[86]),"+f"(d[87]),"+f"(d[88]),"+f"(d[89]),"+f"(d[90]),"+f"(d[91]),"+f"(d[92]),"+f"(d[93]),"+f"(d[94]),"+f"(d[95])
    : "r"(a0), "r"(a1), "r"(a2), "r"(a3), "l"(db), "r"(sd));
}
__device__ __forceinline__ void wg_ss160t(float (&d)[80], uint64_t da, uint64_t db, int sd) {
  asm volatile("{\n.reg .pred p;\nsetp.ne.b32 p, %82, 0;\n"
    "wgmma.mma_async.sync.aligned.m64n160k16.f32.bf16.bf16 {%0,%1,%2,%3,%4,%5,%6,%7,%8,%9,%10,%11,%12,%13,%14,%15,%16,%17,%18,%19,%20,%21,%22,%23,%24,%25,%26,%27,%28,%29,%30,%31,%32,%33,%34,%35,%36,%37,%38,%39,%40,%41,%42,%43,%44,%45,%46,%47,%48,%49,%50,%51,%52,%53,%54,%55,%56,%57,%58,%59,%60,%61,%62,%63,%64,%65,%66,%67,%68,%69,%70,%71,%72,%73,%74,%75,%76,%77,%78,%79}, %80, %81, p, 1, 1, 0, 1;\n}\n"
    : "+f"(d[0]),"+f"(d[1]),"+f"(d[2]),"+f"(d[3]),"+f"(d[4]),"+f"(d[5]),"+f"(d[6]),"+f"(d[7]),"+f"(d[8]),"+f"(d[9]),"+f"(d[10]),"+f"(d[11]),"+f"(d[12]),"+f"(d[13]),"+f"(d[14]),"+f"(d[15]),"+f"(d[16]),"+f"(d[17]),"+f"(d[18]),"+f"(d[19]),"+f"(d[20]),"+f"(d[21]),"+f"(d[22]),"+f"(d[23]),"+f"(d[24]),"+f"(d[25]),"+f"(d[26]),"+f"(d[27]),"+f"(d[28]),"+f"(d[29]),"+f"(d[30]),"+f"(d[31]),"+f"(d[32]),"+f"(d[33]),"+f"(d[34]),"+f"(d[35]),"+f"(d[36]),"+f"(d[37]),"+f"(d[38]),"+f"(d[39]),"+f"(d[40]),"+f"(d[41]),"+f"(d[42]),"+f"(d[43]),"+f"(d[44]),"+f"(d[45]),"+f"(d[46]),"+f"(d[47]),"+f"(d[48]),"+f"(d[49]),"+f"(d[50]),"+f"(d[51]),"+f"(d[52]),"+f"(d[53]),"+f"(d[54]),"+f"(d[55]),"+f"(d[56]),"+f"(d[57]),"+f"(d[58]),"+f"(d[59]),"+f"(d[60]),"+f"(d[61]),"+f"(d[62]),"+f"(d[63]),"+f"(d[64]),"+f"(d[65]),"+f"(d[66]),"+f"(d[67]),"+f"(d[68]),"+f"(d[69]),"+f"(d[70]),"+f"(d[71]),"+f"(d[72]),"+f"(d[73]),"+f"(d[74]),"+f"(d[75]),"+f"(d[76]),"+f"(d[77]),"+f"(d[78]),"+f"(d[79])
    : "l"(da), "l"(db), "r"(sd));
}
__device__ __forceinline__ void wg_ss80t(float (&d)[40], uint64_t da, uint64_t db, int sd) {
  asm volatile("{\n.reg .pred p;\nsetp.ne.b32 p, %42, 0;\n"
    "wgmma.mma_async.sync.aligned.m64n80k16.f32.bf16.bf16 {%0,%1,%2,%3,%4,%5,%6,%7,%8,%9,%10,%11,%12,%13,%14,%15,%16,%17,%18,%19,%20,%21,%22,%23,%24,%25,%26,%27,%28,%29,%30,%31,%32,%33,%34,%35,%36,%37,%38,%39}, %40, %41, p, 1, 1, 0, 1;\n}\n"
    : "+f"(d[0]),"+f"(d[1]),"+f"(d[2]),"+f"(d[3]),"+f"(d[4]),"+f"(d[5]),"+f"(d[6]),"+f"(d[7]),"+f"(d[8]),"+f"(d[9]),"+f"(d[10]),"+f"(d[11]),"+f"(d[12]),"+f"(d[13]),"+f"(d[14]),"+f"(d[15]),"+f"(d[16]),"+f"(d[17]),"+f"(d[18]),"+f"(d[19]),"+f"(d[20]),"+f"(d[21]),"+f"(d[22]),"+f"(d[23]),"+f"(d[24]),"+f"(d[25]),"+f"(d[26]),"+f"(d[27]),"+f"(d[28]),"+f"(d[29]),"+f"(d[30]),"+f"(d[31]),"+f"(d[32]),"+f"(d[33]),"+f"(d[34]),"+f"(d[35]),"+f"(d[36]),"+f"(d[37]),"+f"(d[38]),"+f"(d[39])
    : "l"(da), "l"(db), "r"(sd));
}

struct Maps { CUtensorMap x, xn, wq, k, v, wo, w3[2], xg, xe, out; };
struct Params {
  const __nv_bfloat16 *x, *wr, *wg, *wu, *wd, *k, *v;
  Scratch* s;
};

__device__ __forceinline__ void side_cta(const Params& p, int sc, unsigned epoch, float* sm) {
  const int tid = threadIdx.x, lane = tid & 31, warp = tid >> 5;
  int budget = WAIT_BUDGET;
  float* s_x = sm;
  float* s_red = sm + 1280;
  float* s_h = s_red + 6144;
  uint4* s_c = (uint4*)(s_h + 768);
  uint2* s_st = (uint2*)(s_c + 16);
  constexpr int DEPTH = 7, STEP = 4 * 6144;
  const uint32_t ring = smem_u32(s_st + 512) + tid * 16;
  const int cg = tid % 96, ks = tid / 96, cd = tid % 80, kd = tid / 80;
  const __nv_bfloat16* wp = (cg < 48 ? p.wg : p.wu) + (size_t)(ks * 160) * FF + sc * 384 + (cg % 48) * 8;
  int kf = 0, pitch = FF;
  uint32_t slot = ring;
  auto refill = [&]() {
    if (kf == 40) { wp = p.wd + (size_t)(sc * 384 + kd * 96) * DM + cd * 8; pitch = DM; }
    if (kf < (tid < 320 ? 64 : 40)) {
#pragma unroll
      for (int j = 0; j < 4; j++) asm volatile("cp.async.cg.shared.global.L2::cache_hint [%0], [%1], 16, %2;" ::"r"(slot + j * 6144), "l"(wp + j * pitch), "l"(POL_FIRST) : "memory");
    }
    asm volatile("cp.async.commit_group;" ::: "memory");
    wp += 4 * pitch; kf++;
    slot += STEP; if (slot == ring + DEPTH * STEP) slot = ring;
  };
  auto gemv = [&](int n, const float* x0, const float* x1, float* out) {
    float a[2][8] = {};
#pragma unroll 1
    for (int k = 0; k < n; k += 4) {
      refill();
      asm volatile("cp.async.wait_group %0;" ::"n"(DEPTH - 1) : "memory");
      const float4 f0 = *(const float4*)(x0 + k), f1 = *(const float4*)(x1 + k);
      const float y0[4] = {f0.x, f0.y, f0.z, f0.w}, y1[4] = {f1.x, f1.y, f1.z, f1.w};
#pragma unroll
      for (int j = 0; j < 4; j++) {
        const uint4 v = lds128(slot + j * 6144);
        const uint32_t u[4] = {v.x, v.y, v.z, v.w};
#pragma unroll
        for (int i = 0; i < 4; i++) {
          a[0][2 * i] += y0[j] * bf_lo(u[i]); a[0][2 * i + 1] += y0[j] * bf_hi(u[i]);
          a[1][2 * i] += y1[j] * bf_lo(u[i]); a[1][2 * i + 1] += y1[j] * bf_hi(u[i]);
        }
      }
    }
#pragma unroll
    for (int i = 0; i < 16; i++) out[(i >> 3) * 768 + (i & 7)] = a[i >> 3][i & 7];
  };
  auto load_row = [&](const __nv_bfloat16* r, uint32_t (&v)[10]) {
    const uint4 a = __ldg((const uint4*)r + lane), b = __ldg((const uint4*)r + 32 + lane);
    const uint2 c = __ldg((const uint2*)r + 128 + lane);
    v[0] = a.x; v[1] = a.y; v[2] = a.z; v[3] = a.w; v[4] = b.x; v[5] = b.y; v[6] = b.z; v[7] = b.w; v[8] = c.x; v[9] = c.y;
  };
  uint32_t wr[10], xb[3][10];
  load_row(p.wr, wr);
  auto stat2 = [&](int pair) {
    uint4 v;
    do v = ld_pkt((const uint4*)p.s->stat + pair); while ((((v.x ^ (epoch + 1)) | (v.z ^ (epoch + 1))) & 0xffff) && --budget >= 0);
    return make_uint4(__byte_perm(v.x, 0, 0x3232), v.y, __byte_perm(v.z, 0, 0x3232), v.w);
  };
  if (tid < 256) ((uint4*)s_st)[tid] = stat2(sc * 256 + tid);
  __syncthreads();
#pragma unroll
  for (int b = 0; b < 3; b++) load_row(p.x + (size_t)(sc * 512 + warp + 12 * b) * DM, xb[b]);
#pragma unroll 1
  for (int k = 0; k < DEPTH - 1; k++) refill();
  float v0 = -INFINITY, v1 = -INFINITY; int i0 = 0xfff, i1 = 0xfff;
  auto better = [](float a, int ia, float b, int ib) { return a > b || (a == b && ia < ib); };
  auto push = [&](float v, int i) {
    if (better(v, i, v0, i0)) { v1 = v0; i1 = i0; v0 = v; i0 = i; }
    else if (better(v, i, v1, i1)) { v1 = v; i1 = i; }
  };
  auto push2 = [&](uint4 c) { push(__uint_as_float(c.x), c.y & 0xfff); push(__uint_as_float(c.z), c.w & 0xfff); };
#pragma unroll 1
  for (int l3 = warp; l3 < 512; l3 += 36) {
#pragma unroll
    for (int b = 0; b < 3; b++) {
      const int lr = l3 + 12 * b;
      if (lr >= 512) break;
      const uint2 st = s_st[lr];
      uint32_t v[10];
#pragma unroll
      for (int i = 0; i < 10; i++) v[i] = hsub2(xb[b][i], st.x);
      if (lr + 36 < 512) load_row(p.x + (size_t)(sc * 512 + lr + 36) * DM, xb[b]);
      float r0 = 0.f, r1 = 0.f;
#pragma unroll
      for (int i = 0; i < 10; i++) {
        const uint32_t xn = pack_bf16(bf_lo(v[i]) * __uint_as_float(st.y), bf_hi(v[i]) * __uint_as_float(st.y));
        r0 = fmaf(bf_lo(xn), bf_lo(wr[i]), r0); r1 = fmaf(bf_hi(xn), bf_hi(wr[i]), r1);
      }
      r0 += r1;
#pragma unroll
      for (int o = 16; o > 0; o >>= 1) r0 += __shfl_xor_sync(~0u, r0, o);
      push(rbf(r0), sc * 512 + lr);
    }
  }
  if (lane == 0) s_c[warp] = make_uint4(__float_as_uint(v0), i0, __float_as_uint(v1), i1);
  __syncthreads();
#pragma unroll 1
  for (int w = 1; w < 12; w++) push2(s_c[(warp + w) % 12]);
  const uint32_t tag = (epoch + 1) << 12;
  if (tid == 0) st_pkt(p.s->cand + sc, __float_as_uint(v0), i0 | tag, __float_as_uint(v1), i1);
  {
    uint4 c;
    do c = ld_pkt(p.s->cand + (lane & 3)); while (((c.y ^ tag) >> 12) && --budget >= 0);
#pragma unroll 1
    for (int w = 1; w < 4; w++) { const int o = (sc + w) & 3; push2(make_uint4(__shfl_sync(~0u, c.x, o), __shfl_sync(~0u, c.y, o), __shfl_sync(~0u, c.z, o), __shfl_sync(~0u, c.w, o))); }
  }
  if (i0 >= SQ) i0 = 0;
  if (i1 >= SQ) i1 = (i0 == 0) ? 1 : 0;
  if (tid < 320) {
    const int row = tid < 160 ? i0 : i1;
    const uint2 u = __ldg((const uint2*)(p.x + (size_t)row * DM) + tid % 160);
    const uint4 st = stat2(row >> 1);
    const uint32_t mean2 = row & 1 ? st.z : st.x, d0 = hsub2(u.x, mean2), d1 = hsub2(u.y, mean2);
    const float inv = __uint_as_float(row & 1 ? st.w : st.y);
    ((float4*)s_x)[tid] = make_float4(rbf(bf_lo(d0) * inv), rbf(bf_hi(d0) * inv), rbf(bf_lo(d1) * inv), rbf(bf_hi(d1) * inv));
  }
  __syncthreads();
  gemv(160, s_x + ks * 160, s_x + DM + ks * 160, s_red + ks * 1536 + cg * 8);
  __syncthreads();
#pragma unroll
  for (int t = 0; t < 2; t++) {
    float g = 0.f, u = 0.f;
#pragma unroll
    for (int k = 0; k < 4; k++) { g += s_red[(k * 2 + t) * 768 + tid]; u += s_red[(k * 2 + t) * 768 + 384 + tid]; }
    s_h[t * 384 + tid] = rbf(rbf(silu_f(rbf(g))) * rbf(u));
  }
  __syncthreads();
  if (tid < 320) gemv(96, s_h + kd * 96, s_h + 384 + kd * 96, s_red + kd * 1536 + cd * 8);
  __syncthreads();
  const int o4 = tid + (tid < 160 ? 0 : 32);
  if (tid < 320) {
    const float4 *r = (const float4*)s_red + o4, a = r[0], b = r[384], c = r[768], d = r[1152];
    ((float4*)p.s->ffn)[sc * 320 + tid] = make_float4(a.x + b.x + c.x + d.x, a.y + b.y + c.y + d.y, a.z + b.z + c.z + d.z, a.w + b.w + c.w + d.w);
  }
  __syncthreads();
  if (tid == 0) { __threadfence(); s_c[0].x = (atomicAdd(&p.s->flag[FL_SIDE], 1u) & 3u) == 3u; __threadfence(); }
  __syncthreads();
  if (s_c[0].x) {
    if (tid < 320) {
      const float4 *r = (const float4*)p.s->ffn + tid, a = __ldcg(r), b = __ldcg(r + 320), c = __ldcg(r + 640), d = __ldcg(r + 960), x = ((float4*)s_x)[tid];
      const float rs = rbf(sigmoid_f(tid < 160 ? v0 : v1));
      auto gate = [&](float xn, float y) { return silu_f(rbf(xn + rbf(rbf(y) * rs))); };
      if (tid == 0) { p.s->sel[0] = i0; p.s->sel[1] = i1; }
      ((uint2*)p.s->gsel)[tid] =
          make_uint2(pack_bf16(gate(x.x, a.x + b.x + c.x + d.x), gate(x.y, a.y + b.y + c.y + d.y)), pack_bf16(gate(x.z, a.z + b.z + c.z + d.z), gate(x.w, a.w + b.w + c.w + d.w)));
    }
    __syncthreads();
    if (tid == 0) red_release(&p.s->flag[FL_FFN]);
  }
}

constexpr float SM_C = 0.07216878364870322f * 1.4426950408889634f;

constexpr int LD = 0, LS = 3;
__device__ __forceinline__ void ln_piece(const Params& p, uint32_t (&r)[48], int k, int row, int l16) {
  auto f = [&](int i) { return __uint_as_float(r[i]); };
  if (k == LD) {
#pragma unroll
    for (int i = 0; i < 5; i++) {
      const uint4 v = ldg_nc((const uint4*)(p.x + (size_t)row * DM) + i * 16 + l16);
      r[4 * i] = v.x; r[4 * i + 1] = v.y; r[4 * i + 2] = v.z; r[4 * i + 3] = v.w;
    }
    asm volatile("ld.relaxed.gpu.global.v2.u32 {%0,%1}, [%2];" : "=r"(r[20]), "=r"(r[21]) : "l"(&p.s->done));
  } else if (k == LS || k == LS + 1) {
    if (k == LS) { r[22] = __shfl_sync(~0u, r[0], 0, 16) << 16; r[23] = r[24] = 0; }
    float s0 = f(23), s1 = 0.f, q0 = f(24), q1 = 0.f;
#pragma unroll
    for (int i = 10 * (k - LS); i < 10 * (k - LS) + 10; i++) {
      const float a = bf_lo(r[i]) - f(22), b = bf_hi(r[i]) - f(22);
      s0 += a; s1 += b; q0 = fmaf(a, a, q0); q1 = fmaf(b, b, q1);
    }
    r[23] = __float_as_uint(s0 + s1); r[24] = __float_as_uint(q0 + q1);
  } else if (k == LS + 2) {
    float s0 = f(23), q0 = f(24);
#pragma unroll
    for (int o = 8; o > 0; o >>= 1) { s0 += __shfl_xor_sync(~0u, s0, o); q0 += __shfl_xor_sync(~0u, q0, o); }
    s0 *= 1.f / DM;
    const float mean = f(22) + s0, var = rbf(fmaxf(fmaf(q0, 1.f / DM, -s0 * s0), 0.f));
    float sd; asm("sqrt.approx.ftz.f32 %0, %1;" : "=f"(sd) : "f"(rbf(var + 1e-5f)));
    const float inv = rcp(rbf(sd));
    r[22] = pack_bf16(mean, mean); r[23] = __float_as_uint(inv * SM_C);
    const uint32_t tag = __funnelshift_r(r[20], r[21], 7) + 1;
    if (l16 == 0) st_pkt8(&p.s->stat[row], __byte_perm(tag, r[22], 0x7610), __float_as_uint(inv));
  } else if (k > LS + 2 && k <= LS + 5) {
#pragma unroll
    for (int j = 2 * (k - LS - 3); j < 2 * (k - LS - 3) + 2 && j < 5; j++) {
#pragma unroll
      for (int i = 4 * j; i < 4 * j + 4; i++) { const uint32_t d = hsub2(r[i], r[22]); r[i] = pack_bf16(bf_lo(d) * f(23), bf_hi(d) * f(23)); }
      *((uint4*)(p.s->xn + (size_t)row * DM) + j * 16 + l16) = make_uint4(r[4 * j], r[4 * j + 1], r[4 * j + 2], r[4 * j + 3]);
    }
  }
}

constexpr float SM_HI = 0x1p64f, SM_LO = 0x1p-64f;
__device__ __forceinline__ void exp_block(float (&s)[32], float& l0, float& l1, int from = 0, int to = 32) {
#pragma unroll
  for (int i = from; i < to; i++) { s[i] = ex2(s[i]); if (i & 2) l1 += s[i]; else l0 += s[i]; }
}
__device__ __forceinline__ float quad_sum(float v) { v += __shfl_xor_sync(~0u, v, 1); return v + __shfl_xor_sync(~0u, v, 2); }
__device__ __forceinline__ float quad_max(float v) { v = fmaxf(v, __shfl_xor_sync(~0u, v, 1)); return fmaxf(v, __shfl_xor_sync(~0u, v, 2)); }
__device__ __noinline__ void safe_head(const uint32_t* kp, const uint32_t* vp, uint4* io) {
  uint32_t fq[48];
#pragma unroll
  for (int i = 0; i < 12; i++) { const uint4 v = io[(i >> 1) * 512 + (i & 1) * 32]; fq[4 * i] = v.x; fq[4 * i + 1] = v.y; fq[4 * i + 2] = v.z; fq[4 * i + 3] = v.w; }
  float m0 = -INFINITY, m1 = -INFINITY;
#pragma unroll 1
  for (int pass = 0; pass < 3; pass++) {
    float o[48] = {}, l0 = 0.f, l1 = 0.f;
#pragma unroll 1
    for (int n = 0; n < 64; n++) {
      const uint32_t *kr = kp + n * (8 * DH / 2), *vr = vp + n * (8 * DH / 2) + (pass - 1) * 48;
      float d[4] = {};
#pragma unroll
      for (int t = 0; t < 12; t++)
        asm volatile("mma.sync.aligned.m16n8k16.row.col.f32.bf16.bf16.f32 {%0,%1,%2,%3}, {%4,%5,%6,%7}, {%8,%9}, {%0,%1,%2,%3};"
                     : "+f"(d[0]), "+f"(d[1]), "+f"(d[2]), "+f"(d[3])
                     : "r"(fq[4 * t]), "r"(fq[4 * t + 1]), "r"(fq[4 * t + 2]), "r"(fq[4 * t + 3]), "r"(__ldg(kr + 8 * t)), "r"(__ldg(kr + 8 * t + 4)));
      if (pass == 0) { m0 = fmaxf(m0, fmaxf(d[0], d[1])); m1 = fmaxf(m1, fmaxf(d[2], d[3])); continue; }
      d[0] = ex2(d[0] - m0); d[1] = ex2(d[1] - m0); d[2] = ex2(d[2] - m1); d[3] = ex2(d[3] - m1);
      l0 += d[0] + d[1]; l1 += d[2] + d[3];
      const uint32_t p0 = pack_bf16(d[0], d[1]), p1 = pack_bf16(d[2], d[3]);
#pragma unroll
      for (int c = 0; c < 12; c++)
        asm volatile("{\n.reg .b32 t;\nmovmatrix.sync.aligned.m8n8.trans.b16 t, %6;\n"
                     "mma.sync.aligned.m16n8k8.row.col.f32.bf16.bf16.f32 {%0,%1,%2,%3}, {%4,%5}, {t}, {%0,%1,%2,%3};\n}\n"
                     : "+f"(o[4 * c]), "+f"(o[4 * c + 1]), "+f"(o[4 * c + 2]), "+f"(o[4 * c + 3]) : "r"(p0), "r"(p1), "r"(__ldg(vr + 4 * c)));
    }
    if (pass == 0) { m0 = quad_max(m0); m1 = quad_max(m1); continue; }
    l0 = rcp(quad_sum(l0)); l1 = rcp(quad_sum(l1));
#pragma unroll
    for (int i = 0; i < 6; i++) {
      const float* v = o + 16 * (i >> 1) + 2 * (i & 1);
      const float r = i & 1 ? l1 : l0;
      io[(3 * (pass - 1) + (i >> 1)) * 512 + (i & 1) * 32] =
          make_uint4(pack_bf16(v[0] * r, v[1] * r), pack_bf16(v[4] * r, v[5] * r), pack_bf16(v[8] * r, v[9] * r), pack_bf16(v[12] * r, v[13] * r));
    }
  }
}

__device__ __forceinline__ constexpr int end_stage(int n) { return n < 4 ? n : n < 6 ? n - 4 : n == 6 ? 4 : n % 5; }
__device__ __forceinline__ constexpr int sent(int n) { return n < 8 ? 0 : n < 9 ? 3 : n < 11 ? 5 : n < 16 ? 10 : n < 17 ? 14 : 15; }
template <int N> struct IntC { static constexpr int value = N; };
template <int N, int I = 0, class F> __device__ __forceinline__ void static_for(F&& f) { if constexpr (I < N) { f(IntC<I>{}); static_for<N, I + 1>(f); } }

extern __shared__ __align__(1024) uint8_t smem_raw[];
constexpr uint32_t EA = 160, EB = 184;
#define SMEM_LAYOUT                                                                                                          \
  [[maybe_unused]] const uint32_t sb = smem_u32(smem_raw), bar_a = sb + OFF_M, bar_b = bar_a + 40, bar_x = bar_a + 88,      \
      bar_u = bar_a + 96, bar_e = bar_a + 104, bar_o = bar_a + 200, bar_w = bar_a + 208, bar_c = bar_a + 216,                \
      bar_z = bar_a + 288, bar_s = bar_a + 296, bar_d = bar_a + 304, s_stat = bar_a + 512, s_sel = s_stat + 1024;

__device__ __forceinline__ int cluster_role() {
  uint32_t t, n;
  asm("mov.u32 %0, %%smid;" : "=r"(t)); asm("mov.u32 %0, %%nsmid;" : "=r"(n));
  t >>= 1;
  return n != 132 ? blockIdx.x >> 1 : t < 32 ? t : t < 60 ? t + 1 + (((t - 32) * 37) >> 8) : t < 62 ? t + 4 : (t - 58) * 8;
}

__device__ __forceinline__ int k_block(int t, int hg) {
  const int i = (t * 11) >> 5;
  return (((hg | 1) ^ (i & 1)) * 4 + (i >> 1)) * 6 + (t == 3 * i ? 4 : 2 * (t - 3 * i) - 2);
}

__device__ __noinline__ int errands(Scratch* s, const Maps& m, int qt, int hg, int warp, uint32_t tag, int budget) {
  SMEM_LAYOUT
  const int lane = threadIdx.x & 31, kq = hg >> 1, nh = hg & 1;
  if (warp == 1) {
#pragma unroll 1
    for (int u = 0; u < 5; u++) {
      mbar_wait(bar_o, u & 1);
      if (lane == 0) red_release(&s->flag[u ? FL_O + (qt * 8 + hg) * 8 : FL_XN + qt * 32]);
      __syncwarp();
    }
  } else if (warp == 2) {
    mbar_wait(bar_x, 0, budget);
    while ((int)(ld_acquire(&s->flag[FL_FFN]) - tag) < 0 && --budget >= 0) {}
    if (lane < 21) {
      const uint4 v = __ldcg(lane ? (const uint4*)(s->gsel + (lane > 10 ? DM - 80 : 0) + nh * 320 + kq * 80) + lane - 1 : (const uint4*)s->sel);
      asm volatile("st.shared.v4.u32 [%0], {%1,%2,%3,%4};" ::"r"(s_sel + 16 * lane), "r"(v.x), "r"(v.y), "r"(v.z), "r"(v.w) : "memory");
    }
    __syncwarp();
    if (lane == 0) { mbar_arrive(bar_u); asm volatile("red.relaxed.gpu.global.add.u64 [%0], 1;" ::"l"(&s->done) : "memory"); }
    while ((int)(ld_acquire(&s->flag[FL_RD + (qt * 8 + (hg ^ 1)) * 8]) - tag) < 0 && --budget >= 0) {}
    if (lane < 3) mbar_arrive(bar_z);
  } else {
    wait_flag(&s->flag[FL_XN + qt * 32], tag * 8);
    fence_proxy_async();
    mbar_wait(bar_a + EA + 32, 1);
    uint32_t a8 = 0, pha = 1;
    const int kb = (qt * 192 + k_block(lane, hg)) * 512;
#pragma unroll 1
    for (int n = 0; n < 54; n++) {
      const int t = n - 30, ko = __shfl_sync(~0u, kb, t);
      if (t == 0 || t == 18) {
        wait_flag(&s->flag[FL_O + (qt * 8 + (t ? 2 * kq + (lane & 1) : lane & 7)) * 8], tag * 4 - (t ? 0 : 1));
        fence_proxy_async();
      }
      mbar_wait(bar_a + EA + a8, pha);
      const uint32_t fb = bar_a + a8, dst = sb + a8 * (TA >> 3);
      if (elect()) {
        if (t >= 0) {
          mbar_expect_tx(fb, TA);
          bulk_load(dst, s->o + ko, TA, fb);
          if (t == 5) {
            mbar_expect_tx(bar_x, 6 * 3840);
#pragma unroll 1
            for (int e = 0; e < 6; e++) tma2d(sb + OFF_B + TW + e * TB, &m.xg, nh * 320 + kq * 80, qt * 128 + e * 24, bar_x);
            asm volatile("prefetch.tensormap [%0];\nprefetch.tensormap [%1];\nprefetch.tensormap [%2];\nprefetch.tensormap [%3];"
                         ::"l"(m.w3), "l"(m.w3 + 1), "l"(&m.xe), "l"(&m.out) : "memory");
          }
          if (t == 22) asm volatile("red.relaxed.gpu.global.add.u32 [%0], 1;" ::"l"(&s->flag[FL_RD + (qt * 8 + hg) * 8]) : "memory");
        } else if (n >= 10 && pha) mbar_arrive(fb);
        else { mbar_expect_tx(fb, TA); tma2d(dst, &m.xn, 8 * a8 + (pha || (n >= 15 && n < 20) ? 0 : 320), qt * 128, fb); }
      }
      a8 += 8; if (a8 == 40) { a8 = 0; pha ^= 1; }
    }
    if (lane < 3) mbar_arrive(bar_z);
  }
  return budget;
}

__global__ void __launch_bounds__(384, 1) __cluster_dims__(2, 1, 1)
fused_kernel(const Params p, const __grid_constant__ Maps m) {
  SMEM_LAYOUT
  const int wi = __shfl_sync(~0u, threadIdx.x >> 5, 0), wg = wi >> 2;
  const int lane = threadIdx.x & 31;
  const int cl = cluster_role();
  const int rank = blockIdx.x & 1;

  if (cl >= 64) {
    const unsigned epoch = (unsigned)(__ldcg(&p.s->done) >> 7);
    side_cta(p, 2 * cl + rank - 128, epoch, (float*)smem_raw);
    return;
  }
  const int qt = (cl & 7) * 2 + rank, hg = cl >> 3;
  const int kq = hg >> 1, nh = hg & 1;

  const int s0 = qt < 8 ? 0 : 5, kg0 = 10 * ((qt >> 1) & 3);
  if (elect()) {
    const int c = (int)(0x5ff7700000ull >> (4 * wi) & 15) + 1;
    for (int i = 0; i < 4; i++) mbar_init(bar_a + 32 * wi + 8 * i, c);
    asm volatile("fence.mbarrier_init.release.cluster;" ::: "memory");
  }
  __syncwarp();
  cluster_arrive();
  if (wi < 2 && elect()) {
    if (wi) {
      mbar_expect_tx(bar_b, TB);
      for (int i = 0; i < 2; i++)
        asm volatile("cp.async.bulk.tensor.4d.shared::cluster.global.mbarrier::complete_tx::bytes.L2::cache_hint [%0], [%1, {%3, %3, %4, %5}], [%2], %6;"
                     ::"r"(sb + OFF_B + i * (TB / 2)), "l"(&m.wq), "r"(bar_b), "r"(0), "r"(12 * hg), "r"(8 * s0 + 4 * i), "l"(POL_FIRST) : "memory");
    } else { mbar_expect_tx(bar_a, TA); tma2d(sb, &m.x, 64 * s0, qt * 128, bar_a); }
  }
  __syncwarp();
  cluster_wait();
  if (wg > 0) {
    const int w = wg - 1;
    const int cw = wi - 4;
    asm volatile("setmaxnreg.inc.sync.aligned.u32 232;");
    uint32_t fr[48];
    reg_fence(fr);
    auto ln_row = [&]() { int v = qt * 128 + hg * 16 + cw * 2 + (lane >> 4); asm volatile("" : "+r"(v)); return v; };
    uint32_t rel_addr;
    asm volatile("mapa.shared::cluster.u32 %0, %1, %2;" : "=r"(rel_addr) : "r"(bar_b + EB), "r"(lane & 1));
    auto rel_a = [&](uint32_t o8) { if (lane == 0) mbar_arrive(bar_a + EA + o8); };
    auto rel_b = [&](uint32_t o8) { if (lane < 2) mbar_arrive_cluster(rel_addr + o8); };
    uint32_t b8 = 0, phb = 0;
    auto next_pair = [&]() { b8 += 16; if (b8 == 48) { b8 = 0; phb ^= 1; } };
    const int g = lane >> 2, q = lane & 3;
    constexpr uint64_t HI_A = desc_hi(16, 1024, 1);
    constexpr uint64_t HI_W = desc_hi(1024, 3072, 1);
    constexpr uint64_t HI_O = desc_hi(2048, 512, 2);
    if (w == 1) asm volatile("bar.arrive 1, 256;" ::: "memory");

    uint32_t zero; asm volatile("mov.u32 %0, %%tid.y;" : "=r"(zero));
    float acc[96];
    uint4* optr = p.s->o + (size_t)(qt * 192 + hg * 24) * 512 + (cw * 16 + g) * 4 + (q ^ ((g >> 1) & 3));
    uint32_t rl[4];
    auto store_o = [&](int pp) {
#pragma unroll
      for (int i = (12 * pp + 8) / 9; i < (12 * (pp + 1) + 8) / 9; i++) {
#pragma unroll
        for (int k = 4 * i; k < 4 * i + 4; k++)
          asm volatile("{\n.reg .b32 t;\nmul.rn.bf16x2 t, %0, %2;\nfma.rn.bf16x2 %0, %0, %1, t;\n}\n" : "+r"(fr[k]) : "r"(rl[i & 1]), "r"(rl[2 + (i & 1)]));
        fr[4 * i] &= ~1u;
        optr[(i >> 1) * 512 + (i & 1) * 32] = make_uint4(fr[4 * i], fr[4 * i + 1], fr[4 * i + 2], fr[4 * i + 3]);
      }
      if (pp == 8) optr += 6 * 512;
    };
    auto fresh = [&]() { uint32_t v = sb; asm volatile("" : "+r"(v)); return v; };
    reg_fence(rl);

#pragma unroll 1
    for (int u = 0; u < 4; u++) {
      const uint32_t sq = fresh();
      const uint64_t dA = mkdesc(sq + w * 8192, HI_A), dB0 = mkdesc(sq + OFF_B, HI_W);
      uint32_t pb8 = 0;
#pragma unroll
      for (int s = 0; s < 10; s++) {
        const uint32_t o8 = b8 + 8 * (s & 1);
        const uint64_t dW = dB0 + o8 * (TB >> 7);
        mbar_wait(bar_a + 8 * (s % 5), s / 5);
        mbar_wait(bar_b + o8, phb);
        if (s == 9 || (s >= LS && u == 0)) asm volatile("bar.sync %0, 256;" ::"r"(1 + w) : "memory");
        WG_FENCE();
#pragma unroll
        for (int kk = 0; kk < 4; kk++) wg_ss192t(acc, dA + ((s % 5) * (TA >> 4) + kk * 2), dW + kk * 384, kk != 0 || s != 0);
        WG_COMMIT();
        if (s >= LS && (s == 9) == (u > 0)) asm volatile("bar.arrive %0, 256;" ::"r"(2 - w) : "memory");
        if (s > 0) { WG_WAIT(1); rel_a(8 * ((s - 1) % 5)); rel_b(pb8); }
        if (s < 9) {
          if (u > 0) store_o(s);
          else { if (s == 6 && lane == 0) mbar_arrive(bar_c); ln_piece(p, fr, s, ln_row(), lane & 15); }
        }
        if (s == 8) { __syncwarp(); if (lane == 0) mbar_arrive(bar_o); }
        pb8 = o8;
        if (s & 1) next_pair();
      }
      if (u == 0) {
        mbar_wait(bar_s, 0);
        const uint2 s0 = lds64(s_stat + (cw * 16 + g) * 8), s1 = lds64(s_stat + 64 + (cw * 16 + g) * 8);
        const uint32_t msk = q == 0 ? 0xffffffffu : q == 1 ? 0xffffu : 0u;
        const float c0 = SM_C * __uint_as_float(s0.y), c1 = SM_C * __uint_as_float(s1.y);
        uint32_t am[4] = {(s0.x ^ 0x80008000u) & msk, (s1.x ^ 0x80008000u) & msk, 0, 0};
        reg_fence(am);
        WG_FENCE();
        wg_rs192t(acc, am[0], am[1], am[2], am[3], mkdesc(sb, desc_hi(1024, 0, 1)), 1);
        WG_COMMIT();
        asm volatile("bar.arrive %0, 256;" ::"r"(2 - w) : "memory");
        WG_WAIT(0);
        reg_fence(acc);
#pragma unroll
        for (int i = 0; i < 24; i++) { acc[4 * i] *= c0; acc[4 * i + 1] *= c0; acc[4 * i + 2] *= c1; acc[4 * i + 3] *= c1; }
      } else { WG_WAIT(0); reg_fence(acc); }
      rel_b(pb8);
      rel_a(32);
#pragma unroll
      for (int i = 0; i < 48; i++) fr[i] = pack_bf16(acc[2 * i], acc[2 * i + 1]);
      reg_fence(fr);
      float sc[32], l0 = 0.f, l1 = 0.f;
      uint32_t pf[16], k8;
      auto pack_p = [&](const float (&s_)[32], int from = 0, int to = 16) {
#pragma unroll
        for (int i = from; i < to; i++) pf[i] = pack_bf16(s_[2 * i], s_[2 * i + 1]);
      };
      auto scores = [&](int j, int pass = 11) {
        k8 = b8 + 8;
        mbar_wait(bar_b + k8, phb);
        next_pair();
        mbar_wait(bar_b + b8, phb);
        const uint64_t dk = mkdesc(sb + OFF_B, HI_W) + k8 * (TB >> 7);
        asm volatile("bar.sync %0, 256;" ::"r"(1 + w) : "memory");
        WG_FENCE();
#pragma unroll
        for (int t = 0; t < 12; t++) {
          wg_rs64(sc, fr[4 * t], fr[4 * t + 1], fr[4 * t + 2], fr[4 * t + 3], dk + (t >> 2) * 64 + (t & 3) * 2, t != 0);
          if (t == 11) WG_COMMIT();
          if (t == pass) asm volatile("bar.arrive %0, 256;" ::"r"(2 - w) : "memory");
        }
      };
      auto pv = [&](int add) {
        const uint64_t dv = mkdesc(sb + OFF_B, HI_W) + b8 * (TB >> 7);
#pragma unroll
        for (int kk = 0; kk < 4; kk++) wg_rs192t(acc, pf[4 * kk], pf[4 * kk + 1], pf[4 * kk + 2], pf[4 * kk + 3], dv + kk * 384, kk != 0 || add);
        WG_COMMIT();
      };
      auto finish = [&]() {
        WG_WAIT(1);
        reg_fence(sc);
        exp_block(sc, l0, l1);
        rel_b(k8 + (__float_as_uint(l0) & __float_as_uint(l1) & zero));
        WG_WAIT(0);
        reg_fence(acc); reg_fence(pf);
        rel_b(b8);
        pack_p(sc);
      };
      {
        mbar_wait(bar_b + b8, phb);
        const uint64_t dk = mkdesc(sb + OFF_B, HI_W) + b8 * (TB >> 7);
        asm volatile("bar.sync %0, 256;" ::"r"(1 + w) : "memory");
#pragma unroll
        for (int t = 0; t < 12; t++) {
          if (t == 0) WG_FENCE();
          wg_rs64(sc, fr[4 * t], fr[4 * t + 1], fr[4 * t + 2], fr[4 * t + 3], dk + (t >> 2) * 64 + (t & 3) * 2, t != 0);
          if (t == 7) asm volatile("bar.arrive %0, 256;" ::"r"(2 - w) : "memory");
        }
        WG_COMMIT();
        WG_WAIT(0);
        reg_fence(sc);
        constexpr int NE = 8;
        float s0[32];
#pragma unroll
        for (int i = 0; i < 32; i++) s0[i] = i < NE ? sc[i] : __uint_as_float(__float_as_uint(sc[i]) ^ zero);
        exp_block(s0, l0, l1, 0, NE);
        pack_p(s0, 0, NE / 2);
#pragma unroll
        for (int i = NE; i < 32; i++) asm volatile("" : "+f"(s0[i])::"memory");
#pragma unroll
        for (int i = 0; i < NE / 2; i++) asm volatile("" : "+r"(pf[i])::"memory");
        rel_b(b8);
        scores(1, 8);
        const uint32_t z = lds32(s_stat) & zero;
#pragma unroll
        for (int i = NE; i < 32; i++) {
          asm("{\n.reg .pred p;\nsetp.eq.u32 p, %1, 0;\n@p ex2.approx.ftz.f32 %0, %0;\n}\n" : "+f"(s0[i]) : "r"(z));
          if (i & 2) l1 += s0[i]; else l0 += s0[i];
        }
        pack_p(s0, NE / 2, 16);
        reg_fence(pf);
        WG_FENCE();
        pv(0);
        finish();
      }
#pragma unroll 1
      for (int j = 2; j < 8; j++) { scores(j); pv(1); finish(); }
      const uint32_t v8 = b8 + 8;
      mbar_wait(bar_b + v8, phb);
      next_pair();
      {
        const uint64_t dv = mkdesc(sb + OFF_B, HI_W) + v8 * (TB >> 7);
        asm volatile("bar.sync %0, 256;" ::"r"(1 + w) : "memory");
        WG_FENCE();
#pragma unroll
        for (int kk = 0; kk < 4; kk++) {
          wg_rs192t(acc, pf[4 * kk], pf[4 * kk + 1], pf[4 * kk + 2], pf[4 * kk + 3], dv + kk * 384, 1);
          if (kk == 1 && (u < 3 || w == 0)) asm volatile("bar.arrive %0, 256;" ::"r"(2 - w) : "memory");
        }
        WG_COMMIT();
      }
      l0 = quad_sum(l0); l1 = quad_sum(l1);
      const bool unsafe = __any_sync(~0u, !(l0 >= SM_LO && l1 >= SM_LO && l0 + l1 <= SM_HI));
      l0 = rcp(l0); l1 = rcp(l1);
      rl[0] = pack_bf16(l0, l0); rl[1] = pack_bf16(l1, l1);
      l0 -= bf_lo(rl[0]); l1 -= bf_lo(rl[1]);
      rl[2] = pack_bf16(l0, l0); rl[3] = pack_bf16(l1, l1);
      WG_WAIT(0);
      reg_fence(acc);
      rel_b(v8);
      if (__builtin_expect(unsafe, 0)) {
        int o = hg * 4 + u; asm volatile("" : "+r"(o));
        o = (o * SKC + (SKC - WIN) + g) * (DH / 2) + q;
#pragma unroll
        for (int i = 0; i < 12; i++) optr[(i >> 1) * 512 + (i & 1) * 32] = make_uint4(fr[4 * i], fr[4 * i + 1], fr[4 * i + 2], fr[4 * i + 3]);
        safe_head((const uint32_t*)p.k + o, (const uint32_t*)p.v + o, optr);
#pragma unroll
        for (int i = 0; i < 12; i++) { const uint4 v = optr[(i >> 1) * 512 + (i & 1) * 32]; fr[4 * i] = v.x; fr[4 * i + 1] = v.y; fr[4 * i + 2] = v.z; fr[4 * i + 3] = v.w; }
        rl[0] = rl[1] = 0x3f803f80u; rl[2] = rl[3] = 0;
      } else {
#pragma unroll
        for (int i = 0; i < 24; i++) {
          fr[8 * (i >> 2) + (i & 3)] = pack_bf16(acc[4 * i], acc[4 * i + 1]);
          fr[8 * (i >> 2) + 4 + (i & 3)] = pack_bf16(acc[4 * i + 2], acc[4 * i + 3]);
        }
      }
    }

    float aF[80], aS[80];
    uint32_t pha = 0, a8 = 0, pa8 = 0, pb8 = 0;
#pragma unroll 1
    for (int s = 0; s < 19; s++) {
      const uint64_t d0 = mkdesc(sb, HI_O), dO = d0 + (a8 * (TA >> 7) + w * 256), dB = d0 + ((OFF_B >> 4) + b8 * (TB >> 7));
      mbar_wait(bar_a + a8, pha);
      mbar_wait(bar_b + b8, phb);
      WG_FENCE();
#pragma unroll
      for (int kk = 0; kk < 4; kk++) wg_ss160t(aF, dO + ((kk >> 1) * 512 + (kk & 1) * 2), dB + ((kk >> 1) * 640 + (kk & 1) * 64), kk != 0 || s != 0);
      WG_COMMIT();
      mbar_wait(bar_b + b8 + 8, phb);
      WG_WAIT(1);
      if (s > 0) { rel_a(pa8); rel_b(pb8 + 8); }
      WG_FENCE();
#pragma unroll
      for (int kk = 0; kk < 4; kk++) wg_ss160t(aS, dO + ((kk >> 1) * 512 + (kk & 1) * 2), dB + ((TB >> 4) + (kk >> 1) * 640 + (kk & 1) * 64), kk != 0 || s != 0);
      WG_COMMIT();
      if (s < 9) {
#pragma unroll
        for (int pp = 0; pp < 9; pp++) if (s == pp) store_o(pp);
        if (s == 8) { __syncwarp(); if (lane == 0) mbar_arrive(bar_o); }
      } else if (s < 15) {
        const int b = 2 * cw + ((lane >> 3) & 1);
        uint32_t ga = sb + OFF_B + TW + ((b * 11) >> 5) * (TB - 3840) + b * 1280 + (lane & 7) * 160 + (lane >> 4) * 16;
        if (s < 14) {
          mbar_wait(bar_x, 0);
          ga += 32 * (s - 9);
          ldsm4(ga, fr);
#pragma unroll
          for (int i = 0; i < 4; i++) {
            const uint2 st = lds64(s_stat + (cw * 16 + g + 8 * (i & 1)) * 8);
            const uint32_t d = hsub2(fr[i], st.x), xn = pack_bf16(bf_lo(d) * __uint_as_float(st.y), bf_hi(d) * __uint_as_float(st.y));
            fr[i] = pack_bf16(silu_f(bf_lo(xn)), silu_f(bf_hi(xn)));
          }
          stsm4(ga, fr);
        } else {
          mbar_wait(bar_u, 0);
          const uint2 sel = lds64(s_sel);
          const uint32_t row = qt * 128 + cw * 16 + (lane & 15);
          if (row == sel.x || row == sel.y) ga = s_sel + 16 + (row == sel.y ? 160 : 0) + (lane >> 4) * 16;
#pragma unroll
          for (int k = 0; k < 5; k++) ldsm4(ga + 32 * k, fr + 4 * k);
        }
      }
      WG_WAIT(1);
      rel_b(b8);
      pa8 = a8; a8 += 8; if (a8 == 40) { a8 = 0; pha ^= 1; }
      pb8 = b8; next_pair();
    }
    const int t128 = threadIdx.x & 127;
    uint4* const xbase = p.s->o + (size_t)(qt * 192 + nh * 24 + 10) * 512 + w * 640 + t128;
    uint4* const dst = xbase + kq * (48 * 512);
    float q1[40], q2[40], oth[40], own[40];
    auto take = [&](float (&x)[40], const float* a, uint32_t z) {
#pragma unroll
      for (int k = 0; k < 40; k++) x[k] = __uint_as_float(__float_as_uint(a[k]) ^ z);
      reg_fence(x);
    };
    reg_fence(aF);
    take(q1, aF, zero);
    auto fa = [&](int i) { return mbar_try(bar_a + 8 * ((4 + i) % 5), i == 0); };
    auto fb = [&](int e) { return mbar_try(bar_b + 8 * (e % 6), (e / 6) & 1); };
    auto send = [&](int m) {
      const float* v = (m < 5 ? q1 : m < 10 ? q2 : oth) + 8 * (m % 5);
      st_pkt(dst + (m / 5) * 1280 + (m % 5) * 128, pack_bf16(v[0], v[1]) | 1, pack_bf16(v[2], v[3]), pack_bf16(v[4], v[5]), pack_bf16(v[6], v[7]));
    };
    static_for<20>([&](auto n_) {
      constexpr int n = n_.value, i = end_stage(n), e = 142 + n / 2, qi = n == 4 ? 1 : n == 6 ? 0 : n / 5;
      float (&acc_)[40] = qi == 0 ? q1 : qi == 1 ? q2 : qi == 2 ? oth : own;
      if (n == 0) while (!(fa(0) & fa(1) & fb(142) & fb(143))) {}
      if (n == 2) while (!(fa(2) & fa(3) & fb(144))) {}
      if (n == 6) while (!(fa(4) & fb(145) & fb(146) & mbar_try(bar_z, 0))) {}
      if (n == 10) while (!(fb(147) & fb(148) & fb(149))) {}
      const uint64_t d0 = mkdesc(fresh(), HI_O), dw = d0 + w * 256;
      WG_FENCE();
#pragma unroll
      for (int kk = 0; kk < 4; kk++)
        wg_ss80t(acc_, dw + (((4 + i) % 5) * (TA >> 4) + (kk >> 1) * 512 + (kk & 1) * 2),
                 d0 + ((OFF_B >> 4) + (e % 6) * (TB >> 4) + (n & 1) * 768 + (kk >> 1) * 384 + (kk & 1) * 64), 1);
      WG_COMMIT();
      if ((!(n & 1) && n <= 16 && n != 12) || n == 15 || n == 7) WG_WAIT(1);
      if (n == 0) rel_a(24);
      if (!(n & 1) && n <= 8) rel_b(8 * ((e - 1) % 6));
      if (n == 0) take(q2, aF + 40, lds32(s_stat) & zero);
      if (n == 10 || n == 14 || n == 16) rel_a(4u * n - 40);
      if (n == 7) reg_fence(q1);
      if (n == 10) reg_fence(q2);
      if (n == 15) reg_fence(oth);
      if (n == 14 || n == 17) while (!fb(n == 14 ? 150 : 151)) {}
      static_for<sent(n + 1) - sent(n)>([&](auto k_) { send(sent(n) + k_.value); });
      if (n == 8) {
        reg_fence(aS);
#pragma unroll
        for (int k = 0; k < 40; k++) oth[k] = kq & 1 ? aS[k] : aS[40 + k];
        reg_fence(oth);
      }
      if (n == 10) {
        reg_fence(aS);
        const bool odd = (kq ^ (lds32(s_stat) & zero)) & 1;
#pragma unroll
        for (int k = 0; k < 40; k++) own[k] = odd ? aS[40 + k] : aS[k];
        reg_fence(own);
      }
    });
    {
      auto poll = [&](int e, uint4 (&v)[5]) {
#pragma unroll
        for (int i = 0; i < 5; i++) v[i] = ld_pkt(xbase + (kq ^ (e < 2 ? 2 + e : 1)) * (48 * 512) + (e < 2 ? kq & 1 : 2) * 1280 + i * 128);
      };
      auto check = [&](int e, uint4 (&v)[5]) {
        auto tags = [&]() { uint32_t t; asm("{\n.reg .b32 t;\nlop3.b32 t, %1, %2, %3, 0x80;\nlop3.b32 %0, t, %4, %5, 0x80;\n}\n" : "=r"(t) : "r"(v[0].x), "r"(v[1].x), "r"(v[2].x), "r"(v[3].x), "r"(v[4].x)); return t & 1; };
        while (!__all_sync(~0u, tags())) poll(e, v);
      };
      auto add = [&](const uint4 (&v)[5]) {
#pragma unroll
        for (int i = 0; i < 5; i++) {
          float* o = own + 8 * i;
          o[0] += bf_lo(v[i].x); o[1] += bf_hi(v[i].x); o[2] += bf_lo(v[i].y); o[3] += bf_hi(v[i].y);
          o[4] += bf_lo(v[i].z); o[5] += bf_hi(v[i].z); o[6] += bf_lo(v[i].w); o[7] += bf_hi(v[i].w);
        }
      };
      uint4 v[2][5];
      uint32_t xr[20];
      const uint32_t xs = sb + OFF_B + 2 * TB + cw * 2560, xa = xs + (lane & 15) * 160 + (lane >> 4) * 16;
      while (!(mbar_try(bar_e, 0) & mbar_try(bar_e + 8, 0))) {}
#pragma unroll
      for (int i = 0; i < 10; i++) v[i / 5][i % 5] = lds128(sb + OFF_B + (3 + i / 5) * TB + (w * 640 + i % 5 * 128 + t128) * 16);
#pragma unroll
      for (int k = 0; k < 5; k++) ldsm4(xa + 32 * k, xr + 4 * k);
      check(0, v[0]); check(1, v[1]);
#pragma unroll
      for (int i = 0; i < 5; i++) v[0][i] = make_uint4(hadd2(v[0][i].x, v[1][i].x), hadd2(v[0][i].y, v[1][i].y), hadd2(v[0][i].z, v[1][i].z), hadd2(v[0][i].w, v[1][i].w));
      WG_WAIT(0);
      reg_fence(own);
      poll(2, v[1]);
      add(v[0]);
      reg_fence(own);
      check(2, v[1]);
      add(v[1]);
      if (lane == 0) mbar_arrive(bar_w);
      cluster_arrive();
#pragma unroll
      for (int i = 0; i < 20; i++) xr[i] = hadd2(xr[i], hmul2(pack_bf16(own[2 * i], own[2 * i + 1]), fr[i]));
#pragma unroll
      for (int k = 0; k < 5; k++) stsm4(xa + 32 * k, xr + 4 * k);
      asm volatile("fence.proxy.async.shared::cta;" ::: "memory");
      __syncwarp();
      if (elect()) {
        tma2d_store(&m.out, xs, nh * 320 + kq * 80, qt * 128 + cw * 16);
        asm volatile("cp.async.bulk.commit_group;\ncp.async.bulk.wait_group.read 0;" ::: "memory");
      }
      __syncwarp();
    }
    cluster_wait();
  } else {
    asm volatile("setmaxnreg.dec.sync.aligned.u32 40;");
    uint32_t tid_; asm volatile("mov.u32 %0, %%tid.x;" : "=r"(tid_));
    const int warp = __shfl_sync(~0u, tid_ >> 5, 0);
    auto is_warp = [&](int k) { uint32_t e; asm volatile("{\n.reg .pred q;\nsetp.eq.u32 q, %1, %2;\nselp.u32 %0, 1, 0, q;\n}" : "=r"(e) : "r"(warp), "r"(k)); return e != 0; };
    if (warp > 0) {
      const unsigned epoch = (unsigned)(__ldcg(&p.s->done) >> 7);
      int budget = WAIT_BUDGET;
      const uint32_t tag = epoch + 1;
      mbar_wait(bar_b + (kg0 & ~7), 0, budget); mbar_wait(bar_b + (kg0 & ~7) + 8, 0, budget);
      float cs0 = 0.f, cs1 = 0.f;
      const int n = rank * 96 + (warp - 1) * 32;
#pragma unroll 1
      for (int kg = kg0 + (lane >> 4) * 5, e = kg + 5; kg < e; kg++) {
        const uint32_t ad = sb + OFF_B + kg * 3072 + (n >> 6) * 1024 + (n & 63) * 2 + (lane & 15) * 4;
#pragma unroll
        for (int k = 0; k < 8; k++) { const uint32_t v = lds32(ad ^ (k * 0x90)); cs0 += bf_lo(v); cs1 += bf_hi(v); }
      }
      cs0 += __shfl_xor_sync(~0u, cs0, 16); cs1 += __shfl_xor_sync(~0u, cs1, 16);
      if (lane < 16) st_pkt8((uint2*)(p.s->cs + (hg * 4 + (qt >> 2)) * 96 + (n >> 1) + lane) + ((qt >> 1) & 1), (__float_as_uint(cs0) & ~3u) | (tag & 3), __float_as_uint(cs1));
      if (lane < 2) { uint32_t a; asm volatile("mapa.shared::cluster.u32 %0, %1, %2;" : "=r"(a) : "r"(bar_d), "r"(lane)); mbar_arrive_cluster(a); }
      mbar_wait(bar_c, 0, budget);
      uint4 v[5];
      while (true) {
        uint32_t bad = 0;
#pragma unroll
        for (int i = 0; i < 5; i++) v[i] = ld_pkt(i < 4 ? p.s->cs + (hg * 4 + i) * 96 + (tid_ - 32) : (const uint4*)p.s->stat + qt * 64 + (tid_ & 63));
#pragma unroll
        for (int i = 0; i < 5; i++) bad |= (v[i].x ^ tag) | (v[i].z ^ tag);
        if (!__any_sync(~0u, bad & 3) || --budget < 0) break;
      }
      asm volatile("st.shared.v4.u32 [%0], {%1,%2,%3,%4};" ::"r"(s_stat + (tid_ & 63) * 16), "r"(__byte_perm(v[4].x, 0, 0x3232)), "r"(v[4].y), "r"(__byte_perm(v[4].z, 0, 0x3232)), "r"(v[4].w) : "memory");
      cs0 = cs1 = 0.f;
#pragma unroll
      for (int i = 0; i < 4; i++) { cs0 += __uint_as_float(v[i].x & ~3u) + __uint_as_float(v[i].z & ~3u); cs1 += __uint_as_float(v[i].y) + __uint_as_float(v[i].w); }
#pragma unroll
      for (int k = 0; k < 8; k++) {
        const uint32_t t = k < 3 ? pack_bf16(cs0, cs1) : 0;
        sts32((sb + (warp - 1) * 1024 + lane * 4) ^ (k * 0x90), t);
        cs0 -= bf_lo(t); cs1 -= bf_hi(t);
      }
      asm volatile("fence.proxy.async.shared::cta;" ::: "memory");
      __syncwarp();
      if (lane < 2) mbar_arrive(bar_s);
      budget = errands(p.s, m, qt, hg, warp, tag, budget);
      if (is_warp(2)) {
        mbar_wait(bar_w, 0, budget);
        if (budget < 0) asm volatile("st.global.u32 [%0], %1;" ::"l"(0ull), "r"(budget) : "memory");
      }
    } else {
      uint32_t fb = bar_b + 8, dst = sb + OFF_B + TB, ph = 1;
      auto next = [&]() { fb += 8; dst += TB; if (fb == bar_b + 48) { fb = bar_b; dst = sb + OFF_B; ph ^= 1; } };
#pragma unroll 1
      for (int u = 0; u < 4; u++) {
        const int h = hg * 4 + u;
        int s = u ? (u == 2 ? 5 : 0) : s0 + 1;
#pragma unroll 1
        for (int i = u == 0; i < 10; i++) {
          if (u == 0) {
            const uint32_t a8 = 8 * (i < 5 ? i : i - 5);
            if (i >= 3) mbar_wait(bar_a + 8 * (i < 8 ? i - 3 : i - 8), i >= 8);
            mbar_wait(bar_a + EA + a8, i < 5);
            if (elect()) { mbar_expect_tx(bar_a + a8, TA); tma2d(sb + a8 * (TA >> 3), &m.x, 64 * s, qt * 128, bar_a + a8); }
            if (i == 6 + (kg0 >> 3)) mbar_wait(bar_d, 0);
          }
          mbar_wait(fb + EB, ph);
          if (elect()) { mbar_expect_tx(fb, TB); tma4d_mc(dst + rank * (TB / 2), &m.wq, 3 * h, 8 * s + 4 * rank, fb); }
          next();
          if (++s == 10) s = 0;
        }
        const int kv0 = (h * SKC + (SKC - WIN)) / 8 + 4 * rank;
#pragma unroll 1
        for (int i = 0; i < 16; i++) {
          const bool isk = (0x2AAB >> i) & 1;
          mbar_wait(fb + EB, ph);
          if (elect()) { mbar_expect_tx(fb, TB); tma4d_mc(dst + rank * (TB / 2), isk ? &m.k : &m.v, 0, kv0 + 8 * (isk ? (i + 1) >> 1 : (i - 1) >> 1), fb); }
          next();
        }
      }
      const int cF = 10 * nh + 5 - 5 * (kq >> 1), cS = 10 * nh + 5 * (kq >> 1);
      const int kb = 4 * (k_block(lane, hg) + rank);
#pragma unroll 1
      for (int n = 0; n < 38; n++) {
        const int c2 = __shfl_sync(~0u, kb, n >> 1);
        mbar_wait(fb + EB, ph);
        if (elect()) { mbar_expect_tx(fb, TW); tma5d_mc(dst + rank * (TW / 2), &m.wo, c2, n & 1 ? cS : cF, fb); }
        next();
      }
      const int odd = ((0x7fb0 ^ (kq & 1 ? 0xffc00 : 0)) >> lane) & 1;
      const int tq = __shfl_sync(~0u, kb, 19 + end_stage(lane)) << 16 | odd << 7 | ((lane < 10 ? cF : cS) + 2 * odd);
#pragma unroll 1
      for (int n = 0; n < 20; n += 2) {
        const int t0 = __shfl_sync(~0u, tq, n), t1 = __shfl_sync(~0u, tq, n + 1);
        mbar_wait(fb + EB, ph);
        if (elect()) {
          mbar_expect_tx(fb, TB);
          tma5d_mc(dst + rank * (TB / 4), (const CUtensorMap*)((const char*)m.w3 + (t0 & 128)), t0 >> 16, t0 & 31, fb);
          tma5d_mc(dst + TB / 2 + rank * (TB / 4), (const CUtensorMap*)((const char*)m.w3 + (t1 & 128)), t1 >> 16, t1 & 31, fb);
        }
        next();
      }
      mbar_wait(bar_a + EA, 0);
      if (elect()) { mbar_expect_tx(bar_e, TW); tma2d(sb + OFF_B + 2 * TB, &m.xe, nh * 320 + kq * 80, qt * 128, bar_e); }
      const uint4* src = p.s->o + (size_t)(qt * 192 + nh * 24 + 10 + (kq ^ 2) * 48) * 512 + (kq & 1) * 1280;
      mbar_wait(bar_a + EA + 16, 0);
      if (elect()) {
        mbar_expect_tx(bar_e + 8, 2 * TW);
        bulk_load(sb + OFF_B + 3 * TB, src, TW, bar_e + 8);
        bulk_load(sb + OFF_B + 4 * TB, src + (kq & 1 ? -48 * 512 : 48 * 512), TW, bar_e + 8);
      }
    }
    cluster_sync();
  }
}

typedef CUresult (*EncodeFn)(CUtensorMap*, CUtensorMapDataType, cuuint32_t, void*, const cuuint64_t*, const cuuint64_t*,
                             const cuuint32_t*, const cuuint32_t*, CUtensorMapInterleave, CUtensorMapSwizzle,
                             CUtensorMapL2promotion, CUtensorMapFloatOOBfill);

void encode(EncodeFn fn, CUtensorMap* tm, void* base, int rank, const cuuint64_t* dims, const cuuint64_t* strides,
            const cuuint32_t* box, CUtensorMapSwizzle sw) {
  const cuuint32_t es[5] = {1, 1, 1, 1, 1};
  fn(tm, CU_TENSOR_MAP_DATA_TYPE_BFLOAT16, rank, base, dims, strides, box, es, CU_TENSOR_MAP_INTERLEAVE_NONE, sw,
     CU_TENSOR_MAP_L2_PROMOTION_L2_128B, CU_TENSOR_MAP_FLOAT_OOB_FILL_NONE);
}

}

extern "C" void kernel_launch(void* const* d_in, const int* in_sizes, int n_in, void* d_out, int out_size) {
  static EncodeFn fn = nullptr;
  static Scratch* scr = nullptr;
  if (!fn) {
    void* f = nullptr;
    cudaDriverEntryPointQueryResult st;
    cudaGetDriverEntryPoint("cuTensorMapEncodeTiled", &f, cudaEnableDefault, &st);
    fn = (EncodeFn)f;
    cudaGetSymbolAddress((void**)&scr, g_scratch);
    cudaFuncSetAttribute(fused_kernel, cudaFuncAttributeMaxDynamicSharedMemorySize, SMEM_BYTES);
  }
  Maps m;
  { const cuuint64_t d[2] = {DM, SQ}, s[1] = {DM * 2}; const cuuint32_t b[2] = {64, 128};
    encode(fn, &m.x, d_in[0], 2, d, s, b, CU_TENSOR_MAP_SWIZZLE_128B);
    encode(fn, &m.xn, scr->xn, 2, d, s, b, CU_TENSOR_MAP_SWIZZLE_128B); }
  { const cuuint64_t d[4] = {64, 8, QD / 64, DM / 8}, s[3] = {QD * 2, 128, 8 * QD * 2}; const cuuint32_t b[4] = {64, 8, 3, 4};
    encode(fn, &m.wq, d_in[3], 4, d, s, b, CU_TENSOR_MAP_SWIZZLE_128B); }
  { const cuuint64_t d[4] = {64, 8, 3, NH * SKC / 8}, s[3] = {DH * 2, 128, 8 * DH * 2}; const cuuint32_t b[4] = {64, 8, 3, 4};
    encode(fn, &m.k, d_in[1], 4, d, s, b, CU_TENSOR_MAP_SWIZZLE_128B);
    encode(fn, &m.v, d_in[2], 4, d, s, b, CU_TENSOR_MAP_SWIZZLE_128B); }
  {
    const cuuint64_t d[5] = {32, 2, QD / 8, 4, DM / 32}, s[4] = {DM * 2, 8 * DM * 2, 2 * DM * 2, 64}; const cuuint32_t b[5] = {32, 2, 4, 4, 5};
    encode(fn, &m.wo, d_in[4], 5, d, s, b, CU_TENSOR_MAP_SWIZZLE_64B);
    const cuuint32_t b3[5] = {32, 2, 4, 4, 3};
    encode(fn, &m.w3[0], d_in[4], 5, d, s, b3, CU_TENSOR_MAP_SWIZZLE_64B);
    encode(fn, &m.w3[1], (char*)d_in[4] + 32, 5, d, s, b3, CU_TENSOR_MAP_SWIZZLE_64B); }
  { const cuuint64_t d[2] = {DM, SQ}, s[1] = {DM * 2}; const cuuint32_t bg[2] = {80, 24}, bx[2] = {80, 128}, bo[2] = {80, 16};
    encode(fn, &m.xg, d_in[0], 2, d, s, bg, CU_TENSOR_MAP_SWIZZLE_NONE);
    encode(fn, &m.xe, d_in[0], 2, d, s, bx, CU_TENSOR_MAP_SWIZZLE_NONE);
    encode(fn, &m.out, d_out, 2, d, s, bo, CU_TENSOR_MAP_SWIZZLE_NONE); }
  Params p;
  p.x = (const __nv_bfloat16*)d_in[0]; p.wr = (const __nv_bfloat16*)d_in[6]; p.wg = (const __nv_bfloat16*)d_in[7];
  p.wu = (const __nv_bfloat16*)d_in[8]; p.wd = (const __nv_bfloat16*)d_in[9];

  p.k = (const __nv_bfloat16*)d_in[1]; p.v = (const __nv_bfloat16*)d_in[2]; p.s = scr;
  cudaLaunchConfig_t cfg = {};
  cfg.gridDim = dim3(132); cfg.blockDim = dim3(384); cfg.dynamicSmemBytes = SMEM_BYTES; cfg.stream = cudaStreamPerThread;
  cudaLaunchKernelEx(&cfg, fused_kernel, p, m);
}
```

```cpp
#include <cuda_runtime.h>
#include <cuda_bf16.h>
#include <cuda.h>
#include <stdint.h>

namespace {

constexpr int SQ = 2048, DM = 640, NH = 32, DH = 192, SKC = 2048, WIN = 512, FF = 1536;
constexpr int QD = NH * DH;
constexpr uint32_t TA = 16384, TB = 24576, TW = 20480, OFF_B = 5 * TA, OFF_M = OFF_B + 6 * TB, SMEM_BYTES = OFF_M + 3072;
constexpr int WAIT_BUDGET = 1 << 20;

constexpr int FL_XN = 0;
constexpr int FL_O = 512;
constexpr int FL_RD = FL_O + 1024;
constexpr int FL_FFN = FL_RD + 1024;
constexpr int FL_SIDE = FL_FFN + 32;
struct __align__(1024) Scratch {
  unsigned long long done, pad0[15];
  unsigned flag[FL_SIDE + 32];
  uint4 cand[8];
  float ffn[4 * 2 * DM];
  int sel[4];
  __nv_bfloat16 gsel[2 * DM];
  uint4 cs[8 * 4 * DH / 2];
  uint2 stat[SQ];
  __align__(1024) __nv_bfloat16 xn[SQ * DM];
  __align__(1024) uint4 o[SQ * QD / 8];
};
__device__ Scratch g_scratch;

__device__ __forceinline__ uint32_t smem_u32(const void* p) { return (uint32_t)__cvta_generic_to_shared(p); }
__device__ __forceinline__ void mbar_init(uint32_t bar, int cnt) { asm volatile("mbarrier.init.shared::cta.b64 [%0], %1;" ::"r"(bar), "r"(cnt)); }
__device__ __forceinline__ void mbar_expect_tx(uint32_t bar, uint32_t bytes) {
  asm volatile("mbarrier.arrive.expect_tx.shared::cta.b64 _, [%0], %1;" ::"r"(bar), "r"(bytes) : "memory");
}
__device__ __forceinline__ void mbar_arrive(uint32_t bar) { asm volatile("mbarrier.arrive.shared::cta.b64 _, [%0];" ::"r"(bar) : "memory"); }
__device__ __forceinline__ void mbar_arrive_cluster(uint32_t addr) { asm volatile("mbarrier.arrive.shared::cluster.b64 _, [%0];" ::"r"(addr) : "memory"); }
__device__ __forceinline__ bool mbar_try(uint32_t bar, uint32_t parity) {
  uint32_t ok;
  asm volatile("{\n.reg .pred p;\nmbarrier.try_wait.parity.shared::cta.b64 p, [%1], %2;\nselp.u32 %0, 1, 0, p;\n}\n" : "=r"(ok) : "r"(bar), "r"(parity) : "memory");
  return ok;
}
__device__ __forceinline__ void mbar_wait(uint32_t bar, uint32_t parity, int& budget) {
#pragma unroll 1
  while (!mbar_try(bar, parity)) { if (--budget < 0) break; }
}
__device__ __forceinline__ void mbar_wait(uint32_t bar, uint32_t parity) {
#pragma unroll 1
  while (!mbar_try(bar, parity)) {}
}
__device__ __forceinline__ unsigned ld_acquire(const unsigned* p) { unsigned v; asm volatile("ld.acquire.gpu.global.u32 %0, [%1];" : "=r"(v) : "l"(p) : "memory"); return v; }
__device__ __forceinline__ void wait_flag(const unsigned* p, unsigned target) {
#pragma unroll 1
  while (__any_sync(~0u, (int)(ld_acquire(p) - target) < 0)) {}
}
__device__ __forceinline__ void red_release(unsigned* p) { asm volatile("red.release.gpu.global.add.u32 [%0], 1;" ::"l"(p) : "memory"); }
__device__ __forceinline__ void fence_proxy_async() { asm volatile("fence.proxy.async.global;" ::: "memory"); }
__device__ __forceinline__ bool elect() {
  uint32_t p;
  asm volatile("{\n.reg .pred P;\nelect.sync _|P, 0xffffffff;\nselp.u32 %0, 1, 0, P;\n}\n" : "=r"(p));
  return p;
}
__device__ __forceinline__ void cluster_arrive() { asm volatile("barrier.cluster.arrive.relaxed.aligned;" ::: "memory"); }
__device__ __forceinline__ void cluster_wait() { asm volatile("barrier.cluster.wait.aligned;" ::: "memory"); }
__device__ __forceinline__ void cluster_sync() { cluster_arrive(); cluster_wait(); }
__device__ __forceinline__ void tma2d(uint32_t dst, const CUtensorMap* tm, int c0, int c1, uint32_t bar) {
  asm volatile("cp.async.bulk.tensor.2d.shared::cluster.global.mbarrier::complete_tx::bytes [%0], [%1, {%3, %4}], [%2];"
               ::"r"(dst), "l"(tm), "r"(bar), "r"(c0), "r"(c1) : "memory");
}
constexpr uint64_t POL_FIRST = 0x12F0000000000000ull;
__device__ __forceinline__ void tma4d_mc(uint32_t dst, const CUtensorMap* tm, int c2, int c3, uint32_t bar) {
  asm volatile("cp.async.bulk.tensor.4d.shared::cluster.global.mbarrier::complete_tx::bytes.multicast::cluster.L2::cache_hint [%0], [%1, {%3, %3, %4, %5}], [%2], %6, %7;"
               ::"r"(dst), "l"(tm), "r"(bar), "r"(0), "r"(c2), "r"(c3), "h"((uint16_t)3), "l"(POL_FIRST) : "memory");
}
__device__ __forceinline__ void tma5d_mc(uint32_t dst, const CUtensorMap* tm, int c2, int c4, uint32_t bar) {
  asm volatile("cp.async.bulk.tensor.5d.shared::cluster.global.mbarrier::complete_tx::bytes.multicast::cluster.L2::cache_hint [%0], [%1, {%3, %3, %4, %3, %5}], [%2], %6, %7;"
               ::"r"(dst), "l"(tm), "r"(bar), "r"(0), "r"(c2), "r"(c4), "h"((uint16_t)3), "l"(POL_FIRST) : "memory");
}
__device__ __forceinline__ void bulk_load(uint32_t dst, const void* src, uint32_t bytes, uint32_t bar) {
  asm volatile("cp.async.bulk.shared::cluster.global.mbarrier::complete_tx::bytes.L2::cache_hint [%0], [%1], %2, [%3], %4;" ::"r"(dst), "l"(src), "r"(bytes), "r"(bar), "l"(POL_FIRST) : "memory");
}
__device__ __forceinline__ void tma2d_store(const CUtensorMap* tm, uint32_t src, int c0, int c1) {
  asm volatile("cp.async.bulk.tensor.2d.global.shared::cta.bulk_group [%0, {%2, %3}], [%1];" ::"l"(tm), "r"(src), "r"(c0), "r"(c1) : "memory");
}
__device__ __forceinline__ uint32_t lds32(uint32_t a) { uint32_t v; asm volatile("ld.shared.u32 %0, [%1];" : "=r"(v) : "r"(a) : "memory"); return v; }
__device__ __forceinline__ uint2 lds64(uint32_t a) { uint2 v; asm volatile("ld.shared.v2.u32 {%0,%1}, [%2];" : "=r"(v.x), "=r"(v.y) : "r"(a) : "memory"); return v; }
__device__ __forceinline__ uint4 lds128(uint32_t a) { uint4 v; asm volatile("ld.shared.v4.u32 {%0,%1,%2,%3}, [%4];" : "=r"(v.x), "=r"(v.y), "=r"(v.z), "=r"(v.w) : "r"(a) : "memory"); return v; }
__device__ __forceinline__ void ldsm4(uint32_t a, uint32_t* v) {
  asm volatile("ldmatrix.sync.aligned.m8n8.x4.shared.b16 {%0,%1,%2,%3}, [%4];" : "=r"(v[0]), "=r"(v[1]), "=r"(v[2]), "=r"(v[3]) : "r"(a) : "memory");
}
__device__ __forceinline__ void stsm4(uint32_t a, const uint32_t* v) {
  asm volatile("stmatrix.sync.aligned.m8n8.x4.shared.b16 [%0], {%1,%2,%3,%4};" ::"r"(a), "r"(v[0]), "r"(v[1]), "r"(v[2]), "r"(v[3]) : "memory");
}
__device__ __forceinline__ void sts32(uint32_t a, uint32_t v) { asm volatile("st.shared.u32 [%0], %1;" ::"r"(a), "r"(v) : "memory"); }
__device__ __forceinline__ void st_pkt(uint4* p, uint32_t a, uint32_t b, uint32_t c, uint32_t d) {
  asm volatile("st.relaxed.gpu.global.v4.b32 [%0], {%1, %2, %3, %4};" ::"l"(p), "r"(a), "r"(b), "r"(c), "r"(d) : "memory");
}
__device__ __forceinline__ void st_pkt8(void* p, uint32_t a, uint32_t b) {
  asm volatile("{\n.reg .b64 v;\nmov.b64 v, {%1, %2};\nst.relaxed.gpu.global.b64 [%0], v;\n}\n" ::"l"(p), "r"(a), "r"(b) : "memory");
}
__device__ __forceinline__ uint4 ld_pkt(const uint4* p) {
  uint4 v;
  asm volatile("{\n.reg .b128 v;\nld.relaxed.gpu.global.b128 v, [%4];\nmov.b128 {%0, %1, %2, %3}, v;\n}\n" : "=r"(v.x), "=r"(v.y), "=r"(v.z), "=r"(v.w) : "l"(p) : "memory");
  return v;
}
__device__ __forceinline__ uint4 ldg_nc(const void* p) {
  uint4 v;
  asm volatile("ld.global.nc.v4.u32 {%0,%1,%2,%3}, [%4];" : "=r"(v.x), "=r"(v.y), "=r"(v.z), "=r"(v.w) : "l"(p));
  return v;
}
#define WG_FENCE() asm volatile("wgmma.fence.sync.aligned;" ::: "memory")
#define WG_COMMIT() asm volatile("wgmma.commit_group.sync.aligned;" ::: "memory")
#define WG_WAIT(n) asm volatile("wgmma.wait_group.sync.aligned " #n ";" ::: "memory")
template <int N> __device__ __forceinline__ void reg_fence(float (&d)[N]) {
#pragma unroll
  for (int i = 0; i < N; i++) asm volatile("" : "+f"(d[i])::"memory");
}
template <int N> __device__ __forceinline__ void reg_fence(uint32_t (&d)[N]) {
#pragma unroll
  for (int i = 0; i < N; i++) asm volatile("" : "+r"(d[i])::"memory");
}
__device__ __forceinline__ constexpr uint64_t desc_hi(uint32_t lbo, uint32_t sbo, uint64_t sw) {
  return ((uint64_t)(lbo >> 4) << 16) | ((uint64_t)(sbo >> 4) << 32) | (sw << 62);
}
__device__ __forceinline__ uint64_t mkdesc(uint32_t addr, uint64_t hi) { return hi | (uint64_t)((addr & 0x3FFFF) >> 4); }
__device__ __forceinline__ uint32_t pack_bf16(float lo, float hi) { uint32_t r; asm("cvt.rn.bf16x2.f32 %0, %1, %2;" : "=r"(r) : "f"(hi), "f"(lo)); return r; }
__device__ __forceinline__ float bf_lo(uint32_t v) { return __uint_as_float(v << 16); }
__device__ __forceinline__ float bf_hi(uint32_t v) { return __uint_as_float(v & 0xffff0000u); }
__device__ __forceinline__ uint32_t hadd2(uint32_t a, uint32_t b) { uint32_t r; asm("add.rn.bf16x2 %0, %1, %2;" : "=r"(r) : "r"(a), "r"(b)); return r; }
__device__ __forceinline__ uint32_t hsub2(uint32_t a, uint32_t b) { uint32_t r; asm("sub.rn.bf16x2 %0, %1, %2;" : "=r"(r) : "r"(a), "r"(b)); return r; }
__device__ __forceinline__ uint32_t hmul2(uint32_t a, uint32_t b) { uint32_t r; asm("mul.rn.bf16x2 %0, %1, %2;" : "=r"(r) : "r"(a), "r"(b)); return r; }
__device__ __forceinline__ float rbf(float x) { return __bfloat162float(__float2bfloat16_rn(x)); }
__device__ __forceinline__ float ex2(float x) { float y; asm("ex2.approx.ftz.f32 %0, %1;" : "=f"(y) : "f"(x)); return y; }
__device__ __forceinline__ float rcp(float x) { float y; asm("rcp.approx.ftz.f32 %0, %1;" : "=f"(y) : "f"(x)); return y; }
__device__ __forceinline__ float sigmoid_f(float x) { return rcp(1.f + ex2(x * -1.4426950408889634f)); }
__device__ __forceinline__ float silu_f(float x) { return x * sigmoid_f(x); }

__device__ __forceinline__ void wg_ss192t(float (&d)[96], uint64_t da, uint64_t db, int sd) {
  asm volatile("{\n.reg .pred p;\nsetp.ne.b32 p, %98, 0;\n"
    "wgmma.mma_async.sync.aligned.m64n192k16.f32.bf16.bf16 {%0,%1,%2,%3,%4,%5,%6,%7,%8,%9,%10,%11,%12,%13,%14,%15,%16,%17,%18,%19,%20,%21,%22,%23,%24,%25,%26,%27,%28,%29,%30,%31,%32,%33,%34,%35,%36,%37,%38,%39,%40,%41,%42,%43,%44,%45,%46,%47,%48,%49,%50,%51,%52,%53,%54,%55,%56,%57,%58,%59,%60,%61,%62,%63,%64,%65,%66,%67,%68,%69,%70,%71,%72,%73,%74,%75,%76,%77,%78,%79,%80,%81,%82,%83,%84,%85,%86,%87,%88,%89,%90,%91,%92,%93,%94,%95}, %96, %97, p, 1, 1, 0, 1;\n}\n"
    : "+f"(d[0]),"+f"(d[1]),"+f"(d[2]),"+f"(d[3]),"+f"(d[4]),"+f"(d[5]),"+f"(d[6]),"+f"(d[7]),"+f"(d[8]),"+f"(d[9]),"+f"(d[10]),"+f"(d[11]),"+f"(d[12]),"+f"(d[13]),"+f"(d[14]),"+f"(d[15]),"+f"(d[16]),"+f"(d[17]),"+f"(d[18]),"+f"(d[19]),"+f"(d[20]),"+f"(d[21]),"+f"(d[22]),"+f"(d[23]),"+f"(d[24]),"+f"(d[25]),"+f"(d[26]),"+f"(d[27]),"+f"(d[28]),"+f"(d[29]),"+f"(d[30]),"+f"(d[31]),"+f"(d[32]),"+f"(d[33]),"+f"(d[34]),"+f"(d[35]),"+f"(d[36]),"+f"(d[37]),"+f"(d[38]),"+f"(d[39]),"+f"(d[40]),"+f"(d[41]),"+f"(d[42]),"+f"(d[43]),"+f"(d[44]),"+f"(d[45]),"+f"(d[46]),"+f"(d[47]),"+f"(d[48]),"+f"(d[49]),"+f"(d[50]),"+f"(d[51]),"+f"(d[52]),"+f"(d[53]),"+f"(d[54]),"+f"(d[55]),"+f"(d[56]),"+f"(d[57]),"+f"(d[58]),"+f"(d[59]),"+f"(d[60]),"+f"(d[61]),"+f"(d[62]),"+f"(d[63]),"+f"(d[64]),"+f"(d[65]),"+f"(d[66]),"+f"(d[67]),"+f"(d[68]),"+f"(d[69]),"+f"(d[70]),"+f"(d[71]),"+f"(d[72]),"+f"(d[73]),"+f"(d[74]),"+f"(d[75]),"+f"(d[76]),"+f"(d[77]),"+f"(d[78]),"+f"(d[79]),"+f"(d[80]),"+f"(d[81]),"+f"(d[82]),"+f"(d[83]),"+f"(d[84]),"+f"(d[85]),"+f"(d[86]),"+f"(d[87]),"+f"(d[88]),"+f"(d[89]),"+f"(d[90]),"+f"(d[91]),"+f"(d[92]),"+f"(d[93]),"+f"(d[94]),"+f"(d[95])
    : "l"(da), "l"(db), "r"(sd));
}
__device__ __forceinline__ void wg_rs64(float (&d)[32], uint32_t a0, uint32_t a1, uint32_t a2, uint32_t a3, uint64_t db, int sd) {
  asm volatile("{\n.reg .pred p;\nsetp.ne.b32 p, %37, 0;\n"
    "wgmma.mma_async.sync.aligned.m64n64k16.f32.bf16.bf16 {%0,%1,%2,%3,%4,%5,%6,%7,%8,%9,%10,%11,%12,%13,%14,%15,%16,%17,%18,%19,%20,%21,%22,%23,%24,%25,%26,%27,%28,%29,%30,%31}, {%32,%33,%34,%35}, %36, p, 1, 1, 0;\n}\n"
    : "+f"(d[0]),"+f"(d[1]),"+f"(d[2]),"+f"(d[3]),"+f"(d[4]),"+f"(d[5]),"+f"(d[6]),"+f"(d[7]),"+f"(d[8]),"+f"(d[9]),"+f"(d[10]),"+f"(d[11]),"+f"(d[12]),"+f"(d[13]),"+f"(d[14]),"+f"(d[15]),"+f"(d[16]),"+f"(d[17]),"+f"(d[18]),"+f"(d[19]),"+f"(d[20]),"+f"(d[21]),"+f"(d[22]),"+f"(d[23]),"+f"(d[24]),"+f"(d[25]),"+f"(d[26]),"+f"(d[27]),"+f"(d[28]),"+f"(d[29]),"+f"(d[30]),"+f"(d[31])
    : "r"(a0), "r"(a1), "r"(a2), "r"(a3), "l"(db), "r"(sd));
}
__device__ __forceinline__ void wg_rs192t(float (&d)[96], uint32_t a0, uint32_t a1, uint32_t a2, uint32_t a3, uint64_t db, int sd) {
  asm volatile("{\n.reg .pred p;\nsetp.ne.b32 p, %101, 0;\n"
    "wgmma.mma_async.sync.aligned.m64n192k16.f32.bf16.bf16 {%0,%1,%2,%3,%4,%5,%6,%7,%8,%9,%10,%11,%12,%13,%14,%15,%16,%17,%18,%19,%20,%21,%22,%23,%24,%25,%26,%27,%28,%29,%30,%31,%32,%33,%34,%35,%36,%37,%38,%39,%40,%41,%42,%43,%44,%45,%46,%47,%48,%49,%50,%51,%52,%53,%54,%55,%56,%57,%58,%59,%60,%61,%62,%63,%64,%65,%66,%67,%68,%69,%70,%71,%72,%73,%74,%75,%76,%77,%78,%79,%80,%81,%82,%83,%84,%85,%86,%87,%88,%89,%90,%91,%92,%93,%94,%95}, {%96,%97,%98,%99}, %100, p, 1, 1, 1;\n}\n"
    : "+f"(d[0]),"+f"(d[1]),"+f"(d[2]),"+f"(d[3]),"+f"(d[4]),"+f"(d[5]),"+f"(d[6]),"+f"(d[7]),"+f"(d[8]),"+f"(d[9]),"+f"(d[10]),"+f"(d[11]),"+f"(d[12]),"+f"(d[13]),"+f"(d[14]),"+f"(d[15]),"+f"(d[16]),"+f"(d[17]),"+f"(d[18]),"+f"(d[19]),"+f"(d[20]),"+f"(d[21]),"+f"(d[22]),"+f"(d[23]),"+f"(d[24]),"+f"(d[25]),"+f"(d[26]),"+f"(d[27]),"+f"(d[28]),"+f"(d[29]),"+f"(d[30]),"+f"(d[31]),"+f"(d[32]),"+f"(d[33]),"+f"(d[34]),"+f"(d[35]),"+f"(d[36]),"+f"(d[37]),"+f"(d[38]),"+f"(d[39]),"+f"(d[40]),"+f"(d[41]),"+f"(d[42]),"+f"(d[43]),"+f"(d[44]),"+f"(d[45]),"+f"(d[46]),"+f"(d[47]),"+f"(d[48]),"+f"(d[49]),"+f"(d[50]),"+f"(d[51]),"+f"(d[52]),"+f"(d[53]),"+f"(d[54]),"+f"(d[55]),"+f"(d[56]),"+f"(d[57]),"+f"(d[58]),"+f"(d[59]),"+f"(d[60]),"+f"(d[61]),"+f"(d[62]),"+f"(d[63]),"+f"(d[64]),"+f"(d[65]),"+f"(d[66]),"+f"(d[67]),"+f"(d[68]),"+f"(d[69]),"+f"(d[70]),"+f"(d[71]),"+f"(d[72]),"+f"(d[73]),"+f"(d[74]),"+f"(d[75]),"+f"(d[76]),"+f"(d[77]),"+f"(d[78]),"+f"(d[79]),"+f"(d[80]),"+f"(d[81]),"+f"(d[82]),"+f"(d[83]),"+f"(d[84]),"+f"(d[85]),"+f"(d[86]),"+f"(d[87]),"+f"(d[88]),"+f"(d[89]),"+f"(d[90]),"+f"(d[91]),"+f"(d[92]),"+f"(d[93]),"+f"(d[94]),"+f"(d[95])
    : "r"(a0), "r"(a1), "r"(a2), "r"(a3), "l"(db), "r"(sd));
}
__device__ __forceinline__ void wg_ss160t(float (&d)[80], uint64_t da, uint64_t db, int sd) {
  asm volatile("{\n.reg .pred p;\nsetp.ne.b32 p, %82, 0;\n"
    "wgmma.mma_async.sync.aligned.m64n160k16.f32.bf16.bf16 {%0,%1,%2,%3,%4,%5,%6,%7,%8,%9,%10,%11,%12,%13,%14,%15,%16,%17,%18,%19,%20,%21,%22,%23,%24,%25,%26,%27,%28,%29,%30,%31,%32,%33,%34,%35,%36,%37,%38,%39,%40,%41,%42,%43,%44,%45,%46,%47,%48,%49,%50,%51,%52,%53,%54,%55,%56,%57,%58,%59,%60,%61,%62,%63,%64,%65,%66,%67,%68,%69,%70,%71,%72,%73,%74,%75,%76,%77,%78,%79}, %80, %81, p, 1, 1, 0, 1;\n}\n"
    : "+f"(d[0]),"+f"(d[1]),"+f"(d[2]),"+f"(d[3]),"+f"(d[4]),"+f"(d[5]),"+f"(d[6]),"+f"(d[7]),"+f"(d[8]),"+f"(d[9]),"+f"(d[10]),"+f"(d[11]),"+f"(d[12]),"+f"(d[13]),"+f"(d[14]),"+f"(d[15]),"+f"(d[16]),"+f"(d[17]),"+f"(d[18]),"+f"(d[19]),"+f"(d[20]),"+f"(d[21]),"+f"(d[22]),"+f"(d[23]),"+f"(d[24]),"+f"(d[25]),"+f"(d[26]),"+f"(d[27]),"+f"(d[28]),"+f"(d[29]),"+f"(d[30]),"+f"(d[31]),"+f"(d[32]),"+f"(d[33]),"+f"(d[34]),"+f"(d[35]),"+f"(d[36]),"+f"(d[37]),"+f"(d[38]),"+f"(d[39]),"+f"(d[40]),"+f"(d[41]),"+f"(d[42]),"+f"(d[43]),"+f"(d[44]),"+f"(d[45]),"+f"(d[46]),"+f"(d[47]),"+f"(d[48]),"+f"(d[49]),"+f"(d[50]),"+f"(d[51]),"+f"(d[52]),"+f"(d[53]),"+f"(d[54]),"+f"(d[55]),"+f"(d[56]),"+f"(d[57]),"+f"(d[58]),"+f"(d[59]),"+f"(d[60]),"+f"(d[61]),"+f"(d[62]),"+f"(d[63]),"+f"(d[64]),"+f"(d[65]),"+f"(d[66]),"+f"(d[67]),"+f"(d[68]),"+f"(d[69]),"+f"(d[70]),"+f"(d[71]),"+f"(d[72]),"+f"(d[73]),"+f"(d[74]),"+f"(d[75]),"+f"(d[76]),"+f"(d[77]),"+f"(d[78]),"+f"(d[79])
    : "l"(da), "l"(db), "r"(sd));
}
__device__ __forceinline__ void wg_ss80t(float (&d)[40], uint64_t da, uint64_t db, int sd) {
  asm volatile("{\n.reg .pred p;\nsetp.ne.b32 p, %42, 0;\n"
    "wgmma.mma_async.sync.aligned.m64n80k16.f32.bf16.bf16 {%0,%1,%2,%3,%4,%5,%6,%7,%8,%9,%10,%11,%12,%13,%14,%15,%16,%17,%18,%19,%20,%21,%22,%23,%24,%25,%26,%27,%28,%29,%30,%31,%32,%33,%34,%35,%36,%37,%38,%39}, %40, %41, p, 1, 1, 0, 1;\n}\n"
    : "+f"(d[0]),"+f"(d[1]),"+f"(d[2]),"+f"(d[3]),"+f"(d[4]),"+f"(d[5]),"+f"(d[6]),"+f"(d[7]),"+f"(d[8]),"+f"(d[9]),"+f"(d[10]),"+f"(d[11]),"+f"(d[12]),"+f"(d[13]),"+f"(d[14]),"+f"(d[15]),"+f"(d[16]),"+f"(d[17]),"+f"(d[18]),"+f"(d[19]),"+f"(d[20]),"+f"(d[21]),"+f"(d[22]),"+f"(d[23]),"+f"(d[24]),"+f"(d[25]),"+f"(d[26]),"+f"(d[27]),"+f"(d[28]),"+f"(d[29]),"+f"(d[30]),"+f"(d[31]),"+f"(d[32]),"+f"(d[33]),"+f"(d[34]),"+f"(d[35]),"+f"(d[36]),"+f"(d[37]),"+f"(d[38]),"+f"(d[39])
    : "l"(da), "l"(db), "r"(sd));
}

struct Maps { CUtensorMap x, xn, wq, k, v, wo, w3[2], xg, xe, out; };
struct Params {
  const __nv_bfloat16 *x, *wr, *wg, *wu, *wd, *k, *v;
  Scratch* s;
};

__device__ __forceinline__ void side_cta(const Params& p, int sc, unsigned epoch, float* sm) {
  const int tid = threadIdx.x, lane = tid & 31, warp = tid >> 5;
  int budget = WAIT_BUDGET;
  float* s_x = sm;
  float* s_red = sm + 1280;
  float* s_h = s_red + 6144;
  uint4* s_c = (uint4*)(s_h + 768);
  uint2* s_st = (uint2*)(s_c + 16);
  constexpr int DEPTH = 7, STEP = 4 * 6144;
  const uint32_t ring = smem_u32(s_st + 512) + tid * 16;
  const int cg = tid % 96, ks = tid / 96, cd = tid % 80, kd = tid / 80;
  const __nv_bfloat16* wp = (cg < 48 ? p.wg : p.wu) + (size_t)(ks * 160) * FF + sc * 384 + (cg % 48) * 8;
  int kf = 0, pitch = FF;
  uint32_t slot = ring;
  auto refill = [&]() {
    if (kf == 40) { wp = p.wd + (size_t)(sc * 384 + kd * 96) * DM + cd * 8; pitch = DM; }
    if (kf < (tid < 320 ? 64 : 40)) {
#pragma unroll
      for (int j = 0; j < 4; j++) asm volatile("cp.async.cg.shared.global.L2::cache_hint [%0], [%1], 16, %2;" ::"r"(slot + j * 6144), "l"(wp + j * pitch), "l"(POL_FIRST) : "memory");
    }
    asm volatile("cp.async.commit_group;" ::: "memory");
    wp += 4 * pitch; kf++;
    slot += STEP; if (slot == ring + DEPTH * STEP) slot = ring;
  };
  auto gemv = [&](int n, const float* x0, const float* x1, float* out) {
    float a[2][8] = {};
#pragma unroll 1
    for (int k = 0; k < n; k += 4) {
      refill();
      asm volatile("cp.async.wait_group %0;" ::"n"(DEPTH - 1) : "memory");
      const float4 f0 = *(const float4*)(x0 + k), f1 = *(const float4*)(x1 + k);
      const float y0[4] = {f0.x, f0.y, f0.z, f0.w}, y1[4] = {f1.x, f1.y, f1.z, f1.w};
#pragma unroll
      for (int j = 0; j < 4; j++) {
        const uint4 v = lds128(slot + j * 6144);
        const uint32_t u[4] = {v.x, v.y, v.z, v.w};
#pragma unroll
        for (int i = 0; i < 4; i++) {
          a[0][2 * i] += y0[j] * bf_lo(u[i]); a[0][2 * i + 1] += y0[j] * bf_hi(u[i]);
          a[1][2 * i] += y1[j] * bf_lo(u[i]); a[1][2 * i + 1] += y1[j] * bf_hi(u[i]);
        }
      }
    }
#pragma unroll
    for (int i = 0; i < 16; i++) out[(i >> 3) * 768 + (i & 7)] = a[i >> 3][i & 7];
  };
  auto load_row = [&](const __nv_bfloat16* r, uint32_t (&v)[10]) {
    const uint4 a = __ldg((const uint4*)r + lane), b = __ldg((const uint4*)r + 32 + lane);
    const uint2 c = __ldg((const uint2*)r + 128 + lane);
    v[0] = a.x; v[1] = a.y; v[2] = a.z; v[3] = a.w; v[4] = b.x; v[5] = b.y; v[6] = b.z; v[7] = b.w; v[8] = c.x; v[9] = c.y;
  };
  uint32_t wr[10], xb[3][10];
  load_row(p.wr, wr);
  auto stat2 = [&](int pair) {
    uint4 v;
    do v = ld_pkt((const uint4*)p.s->stat + pair); while ((((v.x ^ (epoch + 1)) | (v.z ^ (epoch + 1))) & 0xffff) && --budget >= 0);
    return make_uint4(__byte_perm(v.x, 0, 0x3232), v.y, __byte_perm(v.z, 0, 0x3232), v.w);
  };
  if (tid < 256) ((uint4*)s_st)[tid] = stat2(sc * 256 + tid);
  __syncthreads();
#pragma unroll
  for (int b = 0; b < 3; b++) load_row(p.x + (size_t)(sc * 512 + warp + 12 * b) * DM, xb[b]);
#pragma unroll 1
  for (int k = 0; k < DEPTH - 1; k++) refill();
  float v0 = -INFINITY, v1 = -INFINITY; int i0 = 0xfff, i1 = 0xfff;
  auto better = [](float a, int ia, float b, int ib) { return a > b || (a == b && ia < ib); };
  auto push = [&](float v, int i) {
    if (better(v, i, v0, i0)) { v1 = v0; i1 = i0; v0 = v; i0 = i; }
    else if (better(v, i, v1, i1)) { v1 = v; i1 = i; }
  };
  auto push2 = [&](uint4 c) { push(__uint_as_float(c.x), c.y & 0xfff); push(__uint_as_float(c.z), c.w & 0xfff); };
#pragma unroll 1
  for (int l3 = warp; l3 < 512; l3 += 36) {
#pragma unroll
    for (int b = 0; b < 3; b++) {
      const int lr = l3 + 12 * b;
      if (lr >= 512) break;
      const uint2 st = s_st[lr];
      uint32_t v[10];
#pragma unroll
      for (int i = 0; i < 10; i++) v[i] = hsub2(xb[b][i], st.x);
      if (lr + 36 < 512) load_row(p.x + (size_t)(sc * 512 + lr + 36) * DM, xb[b]);
      float r0 = 0.f, r1 = 0.f;
#pragma unroll
      for (int i = 0; i < 10; i++) {
        const uint32_t xn = pack_bf16(bf_lo(v[i]) * __uint_as_float(st.y), bf_hi(v[i]) * __uint_as_float(st.y));
        r0 = fmaf(bf_lo(xn), bf_lo(wr[i]), r0); r1 = fmaf(bf_hi(xn), bf_hi(wr[i]), r1);
      }
      r0 += r1;
#pragma unroll
      for (int o = 16; o > 0; o >>= 1) r0 += __shfl_xor_sync(~0u, r0, o);
      push(rbf(r0), sc * 512 + lr);
    }
  }
  if (lane == 0) s_c[warp] = make_uint4(__float_as_uint(v0), i0, __float_as_uint(v1), i1);
  __syncthreads();
#pragma unroll 1
  for (int w = 1; w < 12; w++) push2(s_c[(warp + w) % 12]);
  const uint32_t tag = (epoch + 1) << 12;
  if (tid == 0) st_pkt(p.s->cand + sc, __float_as_uint(v0), i0 | tag, __float_as_uint(v1), i1);
  {
    uint4 c;
    do c = ld_pkt(p.s->cand + (lane & 3)); while (((c.y ^ tag) >> 12) && --budget >= 0);
#pragma unroll 1
    for (int w = 1; w < 4; w++) { const int o = (sc + w) & 3; push2(make_uint4(__shfl_sync(~0u, c.x, o), __shfl_sync(~0u, c.y, o), __shfl_sync(~0u, c.z, o), __shfl_sync(~0u, c.w, o))); }
  }
  if (i0 >= SQ) i0 = 0;
  if (i1 >= SQ) i1 = (i0 == 0) ? 1 : 0;
  if (tid < 320) {
    const int row = tid < 160 ? i0 : i1;
    const uint2 u = __ldg((const uint2*)(p.x + (size_t)row * DM) + tid % 160);
    const uint4 st = stat2(row >> 1);
    const uint32_t mean2 = row & 1 ? st.z : st.x, d0 = hsub2(u.x, mean2), d1 = hsub2(u.y, mean2);
    const float inv = __uint_as_float(row & 1 ? st.w : st.y);
    ((float4*)s_x)[tid] = make_float4(rbf(bf_lo(d0) * inv), rbf(bf_hi(d0) * inv), rbf(bf_lo(d1) * inv), rbf(bf_hi(d1) * inv));
  }
  __syncthreads();
  gemv(160, s_x + ks * 160, s_x + DM + ks * 160, s_red + ks * 1536 + cg * 8);
  __syncthreads();
#pragma unroll
  for (int t = 0; t < 2; t++) {
    float g = 0.f, u = 0.f;
#pragma unroll
    for (int k = 0; k < 4; k++) { g += s_red[(k * 2 + t) * 768 + tid]; u += s_red[(k * 2 + t) * 768 + 384 + tid]; }
    s_h[t * 384 + tid] = rbf(rbf(silu_f(rbf(g))) * rbf(u));
  }
  __syncthreads();
  if (tid < 320) gemv(96, s_h + kd * 96, s_h + 384 + kd * 96, s_red + kd * 1536 + cd * 8);
  __syncthreads();
  const int o4 = tid + (tid < 160 ? 0 : 32);
  if (tid < 320) {
    const float4 *r = (const float4*)s_red + o4, a = r[0], b = r[384], c = r[768], d = r[1152];
    ((float4*)p.s->ffn)[sc * 320 + tid] = make_float4(a.x + b.x + c.x + d.x, a.y + b.y + c.y + d.y, a.z + b.z + c.z + d.z, a.w + b.w + c.w + d.w);
  }
  __syncthreads();
  if (tid == 0) { __threadfence(); s_c[0].x = (atomicAdd(&p.s->flag[FL_SIDE], 1u) & 3u) == 3u; __threadfence(); }
  __syncthreads();
  if (s_c[0].x) {
    if (tid < 320) {
      const float4 *r = (const float4*)p.s->ffn + tid, a = __ldcg(r), b = __ldcg(r + 320), c = __ldcg(r + 640), d = __ldcg(r + 960), x = ((float4*)s_x)[tid];
      const float rs = rbf(sigmoid_f(tid < 160 ? v0 : v1));
      auto gate = [&](float xn, float y) { return silu_f(rbf(xn + rbf(rbf(y) * rs))); };
      if (tid == 0) { p.s->sel[0] = i0; p.s->sel[1] = i1; }
      ((uint2*)p.s->gsel)[tid] =
          make_uint2(pack_bf16(gate(x.x, a.x + b.x + c.x + d.x), gate(x.y, a.y + b.y + c.y + d.y)), pack_bf16(gate(x.z, a.z + b.z + c.z + d.z), gate(x.w, a.w + b.w + c.w + d.w)));
    }
    __syncthreads();
    if (tid == 0) red_release(&p.s->flag[FL_FFN]);
  }
}

constexpr float SM_C = 0.07216878364870322f * 1.4426950408889634f;

constexpr int LD = 0, LS = 3;
__device__ __forceinline__ void ln_piece(const Params& p, uint32_t (&r)[48], int k, int row, int l16) {
  auto f = [&](int i) { return __uint_as_float(r[i]); };
  if (k == LD) {
#pragma unroll
    for (int i = 0; i < 5; i++) {
      const uint4 v = ldg_nc((const uint4*)(p.x + (size_t)row * DM) + i * 16 + l16);
      r[4 * i] = v.x; r[4 * i + 1] = v.y; r[4 * i + 2] = v.z; r[4 * i + 3] = v.w;
    }
    asm volatile("ld.relaxed.gpu.global.v2.u32 {%0,%1}, [%2];" : "=r"(r[20]), "=r"(r[21]) : "l"(&p.s->done));
  } else if (k == LS || k == LS + 1) {
    if (k == LS) { r[22] = __shfl_sync(~0u, r[0], 0, 16) << 16; r[23] = r[24] = 0; }
    float s0 = f(23), s1 = 0.f, q0 = f(24), q1 = 0.f;
#pragma unroll
    for (int i = 10 * (k - LS); i < 10 * (k - LS) + 10; i++) {
      const float a = bf_lo(r[i]) - f(22), b = bf_hi(r[i]) - f(22);
      s0 += a; s1 += b; q0 = fmaf(a, a, q0); q1 = fmaf(b, b, q1);
    }
    r[23] = __float_as_uint(s0 + s1); r[24] = __float_as_uint(q0 + q1);
  } else if (k == LS + 2) {
    float s0 = f(23), q0 = f(24);
#pragma unroll
    for (int o = 8; o > 0; o >>= 1) { s0 += __shfl_xor_sync(~0u, s0, o); q0 += __shfl_xor_sync(~0u, q0, o); }
    s0 *= 1.f / DM;
    const float mean = f(22) + s0, var = rbf(fmaxf(fmaf(q0, 1.f / DM, -s0 * s0), 0.f));
    float sd; asm("sqrt.approx.ftz.f32 %0, %1;" : "=f"(sd) : "f"(rbf(var + 1e-5f)));
    const float inv = rcp(rbf(sd));
    r[22] = pack_bf16(mean, mean); r[23] = __float_as_uint(inv * SM_C);
    const uint32_t tag = __funnelshift_r(r[20], r[21], 7) + 1;
    if (l16 == 0) st_pkt8(&p.s->stat[row], __byte_perm(tag, r[22], 0x7610), __float_as_uint(inv));
  } else if (k > LS + 2 && k <= LS + 5) {
#pragma unroll
    for (int j = 2 * (k - LS - 3); j < 2 * (k - LS - 3) + 2 && j < 5; j++) {
#pragma unroll
      for (int i = 4 * j; i < 4 * j + 4; i++) { const uint32_t d = hsub2(r[i], r[22]); r[i] = pack_bf16(bf_lo(d) * f(23), bf_hi(d) * f(23)); }
      *((uint4*)(p.s->xn + (size_t)row * DM) + j * 16 + l16) = make_uint4(r[4 * j], r[4 * j + 1], r[4 * j + 2], r[4 * j + 3]);
    }
  }
}

constexpr float SM_SHIFT = -21.f, SM_HI = 0x1p64f, SM_LO = 0x1p-80f;
__device__ __forceinline__ void exp_block(float (&s)[32], float& l0, float& l1, int from = 0, int to = 32) {
#pragma unroll
  for (int i = from; i < to; i++) { s[i] = ex2(s[i]); if (i & 2) l1 += s[i]; else l0 += s[i]; }
}
__device__ __forceinline__ float quad_sum(float v) { v += __shfl_xor_sync(~0u, v, 1); return v + __shfl_xor_sync(~0u, v, 2); }
__device__ __forceinline__ float quad_max(float v) { v = fmaxf(v, __shfl_xor_sync(~0u, v, 1)); return fmaxf(v, __shfl_xor_sync(~0u, v, 2)); }
__device__ __noinline__ void safe_head(const uint32_t* kp, const uint32_t* vp, uint4* io) {
  uint32_t fq[48];
#pragma unroll
  for (int i = 0; i < 12; i++) { const uint4 v = io[(i >> 1) * 512 + (i & 1) * 32]; fq[4 * i] = v.x; fq[4 * i + 1] = v.y; fq[4 * i + 2] = v.z; fq[4 * i + 3] = v.w; }
  float m0 = -INFINITY, m1 = -INFINITY;
#pragma unroll 1
  for (int pass = 0; pass < 3; pass++) {
    float o[48] = {}, l0 = 0.f, l1 = 0.f;
#pragma unroll 1
    for (int n = 0; n < 64; n++) {
      const uint32_t *kr = kp + n * (8 * DH / 2), *vr = vp + n * (8 * DH / 2) + (pass - 1) * 48;
      float d[4] = {};
#pragma unroll
      for (int t = 0; t < 12; t++)
        asm volatile("mma.sync.aligned.m16n8k16.row.col.f32.bf16.bf16.f32 {%0,%1,%2,%3}, {%4,%5,%6,%7}, {%8,%9}, {%0,%1,%2,%3};"
                     : "+f"(d[0]), "+f"(d[1]), "+f"(d[2]), "+f"(d[3])
                     : "r"(fq[4 * t]), "r"(fq[4 * t + 1]), "r"(fq[4 * t + 2]), "r"(fq[4 * t + 3]), "r"(__ldg(kr + 8 * t)), "r"(__ldg(kr + 8 * t + 4)));
      if (pass == 0) { m0 = fmaxf(m0, fmaxf(d[0], d[1])); m1 = fmaxf(m1, fmaxf(d[2], d[3])); continue; }
      d[0] = ex2(d[0] - m0); d[1] = ex2(d[1] - m0); d[2] = ex2(d[2] - m1); d[3] = ex2(d[3] - m1);
      l0 += d[0] + d[1]; l1 += d[2] + d[3];
      const uint32_t p0 = pack_bf16(d[0], d[1]), p1 = pack_bf16(d[2], d[3]);
#pragma unroll
      for (int c = 0; c < 12; c++)
        asm volatile("{\n.reg .b32 t;\nmovmatrix.sync.aligned.m8n8.trans.b16 t, %6;\n"
                     "mma.sync.aligned.m16n8k8.row.col.f32.bf16.bf16.f32 {%0,%1,%2,%3}, {%4,%5}, {t}, {%0,%1,%2,%3};\n}\n"
                     : "+f"(o[4 * c]), "+f"(o[4 * c + 1]), "+f"(o[4 * c + 2]), "+f"(o[4 * c + 3]) : "r"(p0), "r"(p1), "r"(__ldg(vr + 4 * c)));
    }
    if (pass == 0) { m0 = quad_max(m0); m1 = quad_max(m1); continue; }
    l0 = rcp(quad_sum(l0)); l1 = rcp(quad_sum(l1));
#pragma unroll
    for (int i = 0; i < 6; i++) {
      const float* v = o + 16 * (i >> 1) + 2 * (i & 1);
      const float r = i & 1 ? l1 : l0;
      io[(3 * (pass - 1) + (i >> 1)) * 512 + (i & 1) * 32] =
          make_uint4(pack_bf16(v[0] * r, v[1] * r), pack_bf16(v[4] * r, v[5] * r), pack_bf16(v[8] * r, v[9] * r), pack_bf16(v[12] * r, v[13] * r));
    }
  }
}

__device__ __forceinline__ constexpr int end_stage(int n) { return n < 4 ? n : n < 6 ? n - 4 : n == 6 ? 4 : n % 5; }
__device__ __forceinline__ constexpr int sent(int n) { return n < 8 ? 0 : n < 9 ? 3 : n < 11 ? 5 : n < 16 ? 10 : n < 17 ? 14 : 15; }
template <int N> struct IntC { static constexpr int value = N; };
template <int N, int I = 0, class F> __device__ __forceinline__ void static_for(F&& f) { if constexpr (I < N) { f(IntC<I>{}); static_for<N, I + 1>(f); } }

extern __shared__ __align__(1024) uint8_t smem_raw[];
constexpr uint32_t EA = 160, EB = 184;
#define SMEM_LAYOUT                                                                                                          \
  [[maybe_unused]] const uint32_t sb = smem_u32(smem_raw), bar_a = sb + OFF_M, bar_b = bar_a + 40, bar_x = bar_a + 88,      \
      bar_u = bar_a + 96, bar_e = bar_a + 104, bar_o = bar_a + 200, bar_w = bar_a + 208, bar_c = bar_a + 216,                \
      bar_z = bar_a + 288, bar_s = bar_a + 296, bar_d = bar_a + 304, s_stat = bar_a + 512, s_sel = s_stat + 1024;

__device__ __forceinline__ int cluster_role() {
  uint32_t t, n;
  asm("mov.u32 %0, %%smid;" : "=r"(t)); asm("mov.u32 %0, %%nsmid;" : "=r"(n));
  t >>= 1;
  return n != 132 ? blockIdx.x >> 1 : t < 32 ? t : t < 60 ? t + 1 + (((t - 32) * 37) >> 8) : t < 62 ? t + 4 : (t - 58) * 8;
}

__device__ __forceinline__ int k_block(int t, int hg) {
  const int i = (t * 11) >> 5;
  return (((hg | 1) ^ (i & 1)) * 4 + (i >> 1)) * 6 + (t == 3 * i ? 4 : 2 * (t - 3 * i) - 2);
}

__device__ __noinline__ int errands(Scratch* s, const Maps& m, int qt, int hg, int warp, uint32_t tag, int budget) {
  SMEM_LAYOUT
  const int lane = threadIdx.x & 31, kq = hg >> 1, nh = hg & 1;
  if (warp == 1) {
#pragma unroll 1
    for (int u = 0; u < 5; u++) {
      mbar_wait(bar_o, u & 1);
      if (lane == 0) red_release(&s->flag[u ? FL_O + (qt * 8 + hg) * 8 : FL_XN + qt * 32]);
      __syncwarp();
    }
  } else if (warp == 2) {
    mbar_wait(bar_x, 0, budget);
    while ((int)(ld_acquire(&s->flag[FL_FFN]) - tag) < 0 && --budget >= 0) {}
    if (lane < 21) {
      const uint4 v = __ldcg(lane ? (const uint4*)(s->gsel + (lane > 10 ? DM - 80 : 0) + nh * 320 + kq * 80) + lane - 1 : (const uint4*)s->sel);
      asm volatile("st.shared.v4.u32 [%0], {%1,%2,%3,%4};" ::"r"(s_sel + 16 * lane), "r"(v.x), "r"(v.y), "r"(v.z), "r"(v.w) : "memory");
    }
    __syncwarp();
    if (lane == 0) { mbar_arrive(bar_u); asm volatile("red.relaxed.gpu.global.add.u64 [%0], 1;" ::"l"(&s->done) : "memory"); }
    while ((int)(ld_acquire(&s->flag[FL_RD + (qt * 8 + (hg ^ 1)) * 8]) - tag) < 0 && --budget >= 0) {}
    if (lane < 3) mbar_arrive(bar_z);
  } else {
    wait_flag(&s->flag[FL_XN + qt * 32], tag * 8);
    fence_proxy_async();
    mbar_wait(bar_a + EA + 32, 1);
    uint32_t a8 = 0, pha = 1;
    const int kb = (qt * 192 + k_block(lane, hg)) * 512;
#pragma unroll 1
    for (int n = 0; n < 54; n++) {
      const int t = n - 30, ko = __shfl_sync(~0u, kb, t);
      if (t == 0 || t == 18) {
        wait_flag(&s->flag[FL_O + (qt * 8 + (t ? 2 * kq + (lane & 1) : lane & 7)) * 8], tag * 4 - (t ? 0 : 1));
        fence_proxy_async();
      }
      mbar_wait(bar_a + EA + a8, pha);
      const uint32_t fb = bar_a + a8, dst = sb + a8 * (TA >> 3);
      if (elect()) {
        if (t >= 0) {
          mbar_expect_tx(fb, TA);
          bulk_load(dst, s->o + ko, TA, fb);
          if (t == 5) {
            mbar_expect_tx(bar_x, 6 * 3840);
#pragma unroll 1
            for (int e = 0; e < 6; e++) tma2d(sb + OFF_B + TW + e * TB, &m.xg, nh * 320 + kq * 80, qt * 128 + e * 24, bar_x);
            asm volatile("prefetch.tensormap [%0];\nprefetch.tensormap [%1];\nprefetch.tensormap [%2];\nprefetch.tensormap [%3];"
                         ::"l"(m.w3), "l"(m.w3 + 1), "l"(&m.xe), "l"(&m.out) : "memory");
          }
          if (t == 22) asm volatile("red.relaxed.gpu.global.add.u32 [%0], 1;" ::"l"(&s->flag[FL_RD + (qt * 8 + hg) * 8]) : "memory");
        } else if (n >= 10 && pha) mbar_arrive(fb);
        else { mbar_expect_tx(fb, TA); tma2d(dst, &m.xn, 8 * a8 + (pha || (n >= 15 && n < 20) ? 0 : 320), qt * 128, fb); }
      }
      a8 += 8; if (a8 == 40) { a8 = 0; pha ^= 1; }
    }
    if (lane < 3) mbar_arrive(bar_z);
  }
  return budget;
}

__global__ void __launch_bounds__(384, 1) __cluster_dims__(2, 1, 1)
fused_kernel(const Params p, const __grid_constant__ Maps m) {
  SMEM_LAYOUT
  const int wi = __shfl_sync(~0u, threadIdx.x >> 5, 0), wg = wi >> 2;
  const int lane = threadIdx.x & 31;
  const int cl = cluster_role();
  const int rank = blockIdx.x & 1;

  if (cl >= 64) {
    const unsigned epoch = (unsigned)(__ldcg(&p.s->done) >> 7);
    side_cta(p, 2 * cl + rank - 128, epoch, (float*)smem_raw);
    return;
  }
  const int qt = (cl & 7) * 2 + rank, hg = cl >> 3;
  const int kq = hg >> 1, nh = hg & 1;

  const int s0 = qt < 8 ? 0 : 5, kg0 = 10 * ((qt >> 1) & 3);
  if (elect()) {
    const int c = (int)(0x5ff7700000ull >> (4 * wi) & 15) + 1;
    for (int i = 0; i < 4; i++) mbar_init(bar_a + 32 * wi + 8 * i, c);
    asm volatile("fence.mbarrier_init.release.cluster;" ::: "memory");
  }
  __syncwarp();
  cluster_arrive();
  if (wi < 2 && elect()) {
    if (wi) {
      mbar_expect_tx(bar_b, TB);
      for (int i = 0; i < 2; i++)
        asm volatile("cp.async.bulk.tensor.4d.shared::cluster.global.mbarrier::complete_tx::bytes.L2::cache_hint [%0], [%1, {%3, %3, %4, %5}], [%2], %6;"
                     ::"r"(sb + OFF_B + i * (TB / 2)), "l"(&m.wq), "r"(bar_b), "r"(0), "r"(12 * hg), "r"(8 * s0 + 4 * i), "l"(POL_FIRST) : "memory");
    } else { mbar_expect_tx(bar_a, TA); tma2d(sb, &m.x, 64 * s0, qt * 128, bar_a); }
  }
  __syncwarp();
  cluster_wait();
  if (wg > 0) {
    const int w = wg - 1;
    const int cw = wi - 4;
    asm volatile("setmaxnreg.inc.sync.aligned.u32 232;");
    uint32_t fr[48];
    reg_fence(fr);
    auto ln_row = [&]() { int v = qt * 128 + hg * 16 + cw * 2 + (lane >> 4); asm volatile("" : "+r"(v)); return v; };
    uint32_t rel_addr;
    asm volatile("mapa.shared::cluster.u32 %0, %1, %2;" : "=r"(rel_addr) : "r"(bar_b + EB), "r"(lane & 1));
    auto rel_a = [&](uint32_t o8) { if (lane == 0) mbar_arrive(bar_a + EA + o8); };
    auto rel_b = [&](uint32_t o8) { if (lane < 2) mbar_arrive_cluster(rel_addr + o8); };
    uint32_t b8 = 0, phb = 0;
    auto next_pair = [&]() { b8 += 16; if (b8 == 48) { b8 = 0; phb ^= 1; } };
    const int g = lane >> 2, q = lane & 3;
    constexpr uint64_t HI_A = desc_hi(16, 1024, 1);
    constexpr uint64_t HI_W = desc_hi(1024, 3072, 1);
    constexpr uint64_t HI_O = desc_hi(2048, 512, 2);
    if (w == 1) asm volatile("bar.arrive 1, 256;" ::: "memory");

    uint32_t zero; asm volatile("mov.u32 %0, %%tid.y;" : "=r"(zero));
    float acc[96];
    uint4* optr = p.s->o + (size_t)(qt * 192 + hg * 24) * 512 + (cw * 16 + g) * 4 + (q ^ ((g >> 1) & 3));
    uint32_t rl[4];
    auto store_o = [&](int pp) {
#pragma unroll
      for (int i = (12 * pp + 8) / 9; i < (12 * (pp + 1) + 8) / 9; i++) {
#pragma unroll
        for (int k = 4 * i; k < 4 * i + 4; k++)
          asm volatile("{\n.reg .b32 t;\nmul.rn.bf16x2 t, %0, %2;\nfma.rn.bf16x2 %0, %0, %1, t;\n}\n" : "+r"(fr[k]) : "r"(rl[i & 1]), "r"(rl[2 + (i & 1)]));
        fr[4 * i] &= ~1u;
        optr[(i >> 1) * 512 + (i & 1) * 32] = make_uint4(fr[4 * i], fr[4 * i + 1], fr[4 * i + 2], fr[4 * i + 3]);
      }
      if (pp == 8) optr += 6 * 512;
    };
    auto fresh = [&]() { uint32_t v = sb; asm volatile("" : "+r"(v)); return v; };
    reg_fence(rl);

#pragma unroll 1
    for (int u = 0; u < 4; u++) {
      const uint32_t sq = fresh();
      const uint64_t dA = mkdesc(sq + w * 8192, HI_A), dB0 = mkdesc(sq + OFF_B, HI_W);
      uint32_t pb8 = 0;
#pragma unroll
      for (int s = 0; s < 10; s++) {
        const uint32_t o8 = b8 + 8 * (s & 1);
        const uint64_t dW = dB0 + o8 * (TB >> 7);
        mbar_wait(bar_a + 8 * (s % 5), s / 5);
        mbar_wait(bar_b + o8, phb);
        if (s == 9 || (s >= LS && u == 0)) asm volatile("bar.sync %0, 256;" ::"r"(1 + w) : "memory");
        WG_FENCE();
#pragma unroll
        for (int kk = 0; kk < 4; kk++) wg_ss192t(acc, dA + ((s % 5) * (TA >> 4) + kk * 2), dW + kk * 384, kk != 0 || s != 0);
        WG_COMMIT();
        if (s >= LS && (s == 9) == (u > 0)) asm volatile("bar.arrive %0, 256;" ::"r"(2 - w) : "memory");
        if (s > 0) { WG_WAIT(1); rel_a(8 * ((s - 1) % 5)); rel_b(pb8); }
        if (s < 9) {
          if (u > 0) store_o(s);
          else { if (s == 6 && lane == 0) mbar_arrive(bar_c); ln_piece(p, fr, s, ln_row(), lane & 15); }
        }
        if (s == 8) { __syncwarp(); if (lane == 0) mbar_arrive(bar_o); }
        pb8 = o8;
        if (s & 1) next_pair();
      }
      if (u == 0) {
        mbar_wait(bar_s, 0);
        const uint2 s0 = lds64(s_stat + (cw * 16 + g) * 8), s1 = lds64(s_stat + 64 + (cw * 16 + g) * 8);
        const uint32_t msk = q == 0 ? 0xffffffffu : q == 1 ? 0xffffu : 0u;
        const float c0 = SM_C * __uint_as_float(s0.y), c1 = SM_C * __uint_as_float(s1.y);
        uint32_t am[4] = {(s0.x ^ 0x80008000u) & msk, (s1.x ^ 0x80008000u) & msk, 0, 0};
        reg_fence(am);
        WG_FENCE();
        wg_rs192t(acc, am[0], am[1], am[2], am[3], mkdesc(sb, desc_hi(1024, 0, 1)), 1);
        WG_COMMIT();
        asm volatile("bar.arrive %0, 256;" ::"r"(2 - w) : "memory");
        WG_WAIT(0);
        reg_fence(acc);
#pragma unroll
        for (int i = 0; i < 24; i++) { acc[4 * i] *= c0; acc[4 * i + 1] *= c0; acc[4 * i + 2] *= c1; acc[4 * i + 3] *= c1; }
      } else { WG_WAIT(0); reg_fence(acc); }
      rel_b(pb8);
      rel_a(32);
#pragma unroll
      for (int i = 0; i < 48; i++) fr[i] = pack_bf16(acc[2 * i], acc[2 * i + 1]);
      reg_fence(fr);
      float sc[32], l0 = 0.f, l1 = 0.f;
      auto shift = [&]() {
#pragma unroll
        for (int i = 0; i < 32; i++) sc[i] = SM_SHIFT;
        reg_fence(sc);
      };
      uint32_t pf[16], k8;
      auto pack_p = [&](const float (&s_)[32], int from = 0, int to = 16) {
#pragma unroll
        for (int i = from; i < to; i++) pf[i] = pack_bf16(s_[2 * i], s_[2 * i + 1]);
      };
      auto scores = [&](int j, int pass = 11) {
        shift();
        k8 = b8 + 8;
        mbar_wait(bar_b + k8, phb);
        next_pair();
        mbar_wait(bar_b + b8, phb);
        const uint64_t dk = mkdesc(sb + OFF_B, HI_W) + k8 * (TB >> 7);
        asm volatile("bar.sync %0, 256;" ::"r"(1 + w) : "memory");
        WG_FENCE();
#pragma unroll
        for (int t = 0; t < 12; t++) {
          wg_rs64(sc, fr[4 * t], fr[4 * t + 1], fr[4 * t + 2], fr[4 * t + 3], dk + (t >> 2) * 64 + (t & 3) * 2, 1);
          if (t == 11) WG_COMMIT();
          if (t == pass) asm volatile("bar.arrive %0, 256;" ::"r"(2 - w) : "memory");
        }
      };
      auto pv = [&](int add) {
        const uint64_t dv = mkdesc(sb + OFF_B, HI_W) + b8 * (TB >> 7);
#pragma unroll
        for (int kk = 0; kk < 4; kk++) wg_rs192t(acc, pf[4 * kk], pf[4 * kk + 1], pf[4 * kk + 2], pf[4 * kk + 3], dv + kk * 384, kk != 0 || add);
        WG_COMMIT();
      };
      auto finish = [&]() {
        WG_WAIT(1);
        reg_fence(sc);
        exp_block(sc, l0, l1);
        rel_b(k8 + (__float_as_uint(l0) & __float_as_uint(l1) & zero));
        WG_WAIT(0);
        reg_fence(acc); reg_fence(pf);
        rel_b(b8);
        pack_p(sc);
      };
      {
        shift();
        mbar_wait(bar_b + b8, phb);
        const uint64_t dk = mkdesc(sb + OFF_B, HI_W) + b8 * (TB >> 7);
        asm volatile("bar.sync %0, 256;" ::"r"(1 + w) : "memory");
#pragma unroll
        for (int t = 0; t < 12; t++) {
          if (t == 0) WG_FENCE();
          wg_rs64(sc, fr[4 * t], fr[4 * t + 1], fr[4 * t + 2], fr[4 * t + 3], dk + (t >> 2) * 64 + (t & 3) * 2, 1);
          if (t == 7) asm volatile("bar.arrive %0, 256;" ::"r"(2 - w) : "memory");
        }
        WG_COMMIT();
        WG_WAIT(0);
        reg_fence(sc);
        constexpr int NE = 8;
        float s0[32];
#pragma unroll
        for (int i = 0; i < 32; i++) s0[i] = i < NE ? sc[i] : __uint_as_float(__float_as_uint(sc[i]) ^ zero);
        exp_block(s0, l0, l1, 0, NE);
        pack_p(s0, 0, NE / 2);
#pragma unroll
        for (int i = NE; i < 32; i++) asm volatile("" : "+f"(s0[i])::"memory");
#pragma unroll
        for (int i = 0; i < NE / 2; i++) asm volatile("" : "+r"(pf[i])::"memory");
        rel_b(b8);
        scores(1, 8);
        const uint32_t z = lds32(s_stat) & zero;
#pragma unroll
        for (int i = NE; i < 32; i++) {
          asm("{\n.reg .pred p;\nsetp.eq.u32 p, %1, 0;\n@p ex2.approx.ftz.f32 %0, %0;\n}\n" : "+f"(s0[i]) : "r"(z));
          if (i & 2) l1 += s0[i]; else l0 += s0[i];
        }
        pack_p(s0, NE / 2, 16);
        reg_fence(pf);
        WG_FENCE();
        pv(0);
        finish();
      }
#pragma unroll 1
      for (int j = 2; j < 8; j++) { scores(j); pv(1); finish(); }
      const uint32_t v8 = b8 + 8;
      mbar_wait(bar_b + v8, phb);
      next_pair();
      {
        const uint64_t dv = mkdesc(sb + OFF_B, HI_W) + v8 * (TB >> 7);
        asm volatile("bar.sync %0, 256;" ::"r"(1 + w) : "memory");
        WG_FENCE();
#pragma unroll
        for (int kk = 0; kk < 4; kk++) {
          wg_rs192t(acc, pf[4 * kk], pf[4 * kk + 1], pf[4 * kk + 2], pf[4 * kk + 3], dv + kk * 384, 1);
          if (kk == 1 && (u < 3 || w == 0)) asm volatile("bar.arrive %0, 256;" ::"r"(2 - w) : "memory");
        }
        WG_COMMIT();
      }
      l0 = quad_sum(l0); l1 = quad_sum(l1);
      const bool unsafe = __any_sync(~0u, !(l0 >= SM_LO && l1 >= SM_LO && l0 + l1 <= SM_HI));
      l0 = rcp(l0); l1 = rcp(l1);
      rl[0] = pack_bf16(l0, l0); rl[1] = pack_bf16(l1, l1);
      l0 -= bf_lo(rl[0]); l1 -= bf_lo(rl[1]);
      rl[2] = pack_bf16(l0, l0); rl[3] = pack_bf16(l1, l1);
      WG_WAIT(0);
      reg_fence(acc);
      rel_b(v8);
      if (__builtin_expect(unsafe, 0)) {
        int o = hg * 4 + u; asm volatile("" : "+r"(o));
        o = (o * SKC + (SKC - WIN) + g) * (DH / 2) + q;
#pragma unroll
        for (int i = 0; i < 12; i++) optr[(i >> 1) * 512 + (i & 1) * 32] = make_uint4(fr[4 * i], fr[4 * i + 1], fr[4 * i + 2], fr[4 * i + 3]);
        safe_head((const uint32_t*)p.k + o, (const uint32_t*)p.v + o, optr);
#pragma unroll
        for (int i = 0; i < 12; i++) { const uint4 v = optr[(i >> 1) * 512 + (i & 1) * 32]; fr[4 * i] = v.x; fr[4 * i + 1] = v.y; fr[4 * i + 2] = v.z; fr[4 * i + 3] = v.w; }
        rl[0] = rl[1] = 0x3f803f80u; rl[2] = rl[3] = 0;
      } else {
#pragma unroll
        for (int i = 0; i < 24; i++) {
          fr[8 * (i >> 2) + (i & 3)] = pack_bf16(acc[4 * i], acc[4 * i + 1]);
          fr[8 * (i >> 2) + 4 + (i & 3)] = pack_bf16(acc[4 * i + 2], acc[4 * i + 3]);
        }
      }
    }

    float aF[80], aS[80];
    uint32_t pha = 0, a8 = 0, pa8 = 0, pb8 = 0;
#pragma unroll 1
    for (int s = 0; s < 19; s++) {
      const uint64_t d0 = mkdesc(sb, HI_O), dO = d0 + (a8 * (TA >> 7) + w * 256), dB = d0 + ((OFF_B >> 4) + b8 * (TB >> 7));
      mbar_wait(bar_a + a8, pha);
      mbar_wait(bar_b + b8, phb);
      WG_FENCE();
#pragma unroll
      for (int kk = 0; kk < 4; kk++) wg_ss160t(aF, dO + ((kk >> 1) * 512 + (kk & 1) * 2), dB + ((kk >> 1) * 640 + (kk & 1) * 64), kk != 0 || s != 0);
      WG_COMMIT();
      mbar_wait(bar_b + b8 + 8, phb);
      WG_WAIT(1);
      if (s > 0) { rel_a(pa8); rel_b(pb8 + 8); }
      WG_FENCE();
#pragma unroll
      for (int kk = 0; kk < 4; kk++) wg_ss160t(aS, dO + ((kk >> 1) * 512 + (kk & 1) * 2), dB + ((TB >> 4) + (kk >> 1) * 640 + (kk & 1) * 64), kk != 0 || s != 0);
      WG_COMMIT();
      if (s < 9) {
#pragma unroll
        for (int pp = 0; pp < 9; pp++) if (s == pp) store_o(pp);
        if (s == 8) { __syncwarp(); if (lane == 0) mbar_arrive(bar_o); }
      } else if (s < 15) {
        const int b = 2 * cw + ((lane >> 3) & 1);
        uint32_t ga = sb + OFF_B + TW + ((b * 11) >> 5) * (TB - 3840) + b * 1280 + (lane & 7) * 160 + (lane >> 4) * 16;
        if (s < 14) {
          mbar_wait(bar_x, 0);
          ga += 32 * (s - 9);
          ldsm4(ga, fr);
#pragma unroll
          for (int i = 0; i < 4; i++) {
            const uint2 st = lds64(s_stat + (cw * 16 + g + 8 * (i & 1)) * 8);
            const uint32_t d = hsub2(fr[i], st.x), xn = pack_bf16(bf_lo(d) * __uint_as_float(st.y), bf_hi(d) * __uint_as_float(st.y));
            fr[i] = pack_bf16(silu_f(bf_lo(xn)), silu_f(bf_hi(xn)));
          }
          stsm4(ga, fr);
        } else {
          mbar_wait(bar_u, 0);
          const uint2 sel = lds64(s_sel);
          const uint32_t row = qt * 128 + cw * 16 + (lane & 15);
          if (row == sel.x || row == sel.y) ga = s_sel + 16 + (row == sel.y ? 160 : 0) + (lane >> 4) * 16;
#pragma unroll
          for (int k = 0; k < 5; k++) ldsm4(ga + 32 * k, fr + 4 * k);
        }
      }
      WG_WAIT(1);
      rel_b(b8);
      pa8 = a8; a8 += 8; if (a8 == 40) { a8 = 0; pha ^= 1; }
      pb8 = b8; next_pair();
    }
    const int t128 = threadIdx.x & 127;
    uint4* const xbase = p.s->o + (size_t)(qt * 192 + nh * 24 + 10) * 512 + w * 640 + t128;
    uint4* const dst = xbase + kq * (48 * 512);
    float q1[40], q2[40], oth[40], own[40];
    auto take = [&](float (&x)[40], const float* a, uint32_t z) {
#pragma unroll
      for (int k = 0; k < 40; k++) x[k] = __uint_as_float(__float_as_uint(a[k]) ^ z);
      reg_fence(x);
    };
    reg_fence(aF);
    take(q1, aF, zero);
    auto fa = [&](int i) { return mbar_try(bar_a + 8 * ((4 + i) % 5), i == 0); };
    auto fb = [&](int e) { return mbar_try(bar_b + 8 * (e % 6), (e / 6) & 1); };
    auto send = [&](int m) {
      const float* v = (m < 5 ? q1 : m < 10 ? q2 : oth) + 8 * (m % 5);
      st_pkt(dst + (m / 5) * 1280 + (m % 5) * 128, pack_bf16(v[0], v[1]) | 1, pack_bf16(v[2], v[3]), pack_bf16(v[4], v[5]), pack_bf16(v[6], v[7]));
    };
    static_for<20>([&](auto n_) {
      constexpr int n = n_.value, i = end_stage(n), e = 142 + n / 2, qi = n == 4 ? 1 : n == 6 ? 0 : n / 5;
      float (&acc_)[40] = qi == 0 ? q1 : qi == 1 ? q2 : qi == 2 ? oth : own;
      if (n == 0) while (!(fa(0) & fa(1) & fb(142) & fb(143))) {}
      if (n == 2) while (!(fa(2) & fa(3) & fb(144))) {}
      if (n == 6) while (!(fa(4) & fb(145) & fb(146) & mbar_try(bar_z, 0))) {}
      if (n == 10) while (!(fb(147) & fb(148) & fb(149))) {}
      const uint64_t d0 = mkdesc(fresh(), HI_O), dw = d0 + w * 256;
      WG_FENCE();
#pragma unroll
      for (int kk = 0; kk < 4; kk++)
        wg_ss80t(acc_, dw + (((4 + i) % 5) * (TA >> 4) + (kk >> 1) * 512 + (kk & 1) * 2),
                 d0 + ((OFF_B >> 4) + (e % 6) * (TB >> 4) + (n & 1) * 768 + (kk >> 1) * 384 + (kk & 1) * 64), 1);
      WG_COMMIT();
      if ((!(n & 1) && n <= 16 && n != 12) || n == 15 || n == 7) WG_WAIT(1);
      if (n == 0) rel_a(24);
      if (!(n & 1) && n <= 8) rel_b(8 * ((e - 1) % 6));
      if (n == 0) take(q2, aF + 40, lds32(s_stat) & zero);
      if (n == 10 || n == 14 || n == 16) rel_a(4u * n - 40);
      if (n == 7) reg_fence(q1);
      if (n == 10) reg_fence(q2);
      if (n == 15) reg_fence(oth);
      if (n == 14 || n == 17) while (!fb(n == 14 ? 150 : 151)) {}
      static_for<sent(n + 1) - sent(n)>([&](auto k_) { send(sent(n) + k_.value); });
      if (n == 8) {
        reg_fence(aS);
#pragma unroll
        for (int k = 0; k < 40; k++) oth[k] = kq & 1 ? aS[k] : aS[40 + k];
        reg_fence(oth);
      }
      if (n == 10) {
        reg_fence(aS);
        const bool odd = (kq ^ (lds32(s_stat) & zero)) & 1;
#pragma unroll
        for (int k = 0; k < 40; k++) own[k] = odd ? aS[40 + k] : aS[k];
        reg_fence(own);
      }
    });
    {
      auto poll = [&](int e, uint4 (&v)[5]) {
#pragma unroll
        for (int i = 0; i < 5; i++) v[i] = ld_pkt(xbase + (kq ^ (e < 2 ? 2 + e : 1)) * (48 * 512) + (e < 2 ? kq & 1 : 2) * 1280 + i * 128);
      };
      auto check = [&](int e, uint4 (&v)[5]) {
        auto tags = [&]() { uint32_t t; asm("{\n.reg .b32 t;\nlop3.b32 t, %1, %2, %3, 0x80;\nlop3.b32 %0, t, %4, %5, 0x80;\n}\n" : "=r"(t) : "r"(v[0].x), "r"(v[1].x), "r"(v[2].x), "r"(v[3].x), "r"(v[4].x)); return t & 1; };
        while (!__all_sync(~0u, tags())) poll(e, v);
      };
      auto add = [&](const uint4 (&v)[5]) {
#pragma unroll
        for (int i = 0; i < 5; i++) {
          float* o = own + 8 * i;
          o[0] += bf_lo(v[i].x); o[1] += bf_hi(v[i].x); o[2] += bf_lo(v[i].y); o[3] += bf_hi(v[i].y);
          o[4] += bf_lo(v[i].z); o[5] += bf_hi(v[i].z); o[6] += bf_lo(v[i].w); o[7] += bf_hi(v[i].w);
        }
      };
      uint4 v[2][5];
      uint32_t xr[20];
      const uint32_t xs = sb + OFF_B + 2 * TB + cw * 2560, xa = xs + (lane & 15) * 160 + (lane >> 4) * 16;
      while (!(mbar_try(bar_e, 0) & mbar_try(bar_e + 8, 0))) {}
#pragma unroll
      for (int i = 0; i < 10; i++) v[i / 5][i % 5] = lds128(sb + OFF_B + (3 + i / 5) * TB + (w * 640 + i % 5 * 128 + t128) * 16);
#pragma unroll
      for (int k = 0; k < 5; k++) ldsm4(xa + 32 * k, xr + 4 * k);
      check(0, v[0]); check(1, v[1]);
#pragma unroll
      for (int i = 0; i < 5; i++) v[0][i] = make_uint4(hadd2(v[0][i].x, v[1][i].x), hadd2(v[0][i].y, v[1][i].y), hadd2(v[0][i].z, v[1][i].z), hadd2(v[0][i].w, v[1][i].w));
      WG_WAIT(0);
      reg_fence(own);
      poll(2, v[1]);
      add(v[0]);
      reg_fence(own);
      check(2, v[1]);
      add(v[1]);
      if (lane == 0) mbar_arrive(bar_w);
      cluster_arrive();
#pragma unroll
      for (int i = 0; i < 20; i++) xr[i] = hadd2(xr[i], hmul2(pack_bf16(own[2 * i], own[2 * i + 1]), fr[i]));
#pragma unroll
      for (int k = 0; k < 5; k++) stsm4(xa + 32 * k, xr + 4 * k);
      asm volatile("fence.proxy.async.shared::cta;" ::: "memory");
      __syncwarp();
      if (elect()) {
        tma2d_store(&m.out, xs, nh * 320 + kq * 80, qt * 128 + cw * 16);
        asm volatile("cp.async.bulk.commit_group;\ncp.async.bulk.wait_group.read 0;" ::: "memory");
      }
      __syncwarp();
    }
    cluster_wait();
  } else {
    asm volatile("setmaxnreg.dec.sync.aligned.u32 40;");
    uint32_t tid_; asm volatile("mov.u32 %0, %%tid.x;" : "=r"(tid_));
    const int warp = __shfl_sync(~0u, tid_ >> 5, 0);
    auto is_warp = [&](int k) { uint32_t e; asm volatile("{\n.reg .pred q;\nsetp.eq.u32 q, %1, %2;\nselp.u32 %0, 1, 0, q;\n}" : "=r"(e) : "r"(warp), "r"(k)); return e != 0; };
    if (warp > 0) {
      const unsigned epoch = (unsigned)(__ldcg(&p.s->done) >> 7);
      int budget = WAIT_BUDGET;
      const uint32_t tag = epoch + 1;
      mbar_wait(bar_b + (kg0 & ~7), 0, budget); mbar_wait(bar_b + (kg0 & ~7) + 8, 0, budget);
      float cs0 = 0.f, cs1 = 0.f;
      const int n = rank * 96 + (warp - 1) * 32;
#pragma unroll 1
      for (int kg = kg0 + (lane >> 4) * 5, e = kg + 5; kg < e; kg++) {
        const uint32_t ad = sb + OFF_B + kg * 3072 + (n >> 6) * 1024 + (n & 63) * 2 + (lane & 15) * 4;
#pragma unroll
        for (int k = 0; k < 8; k++) { const uint32_t v = lds32(ad ^ (k * 0x90)); cs0 += bf_lo(v); cs1 += bf_hi(v); }
      }
      cs0 += __shfl_xor_sync(~0u, cs0, 16); cs1 += __shfl_xor_sync(~0u, cs1, 16);
      if (lane < 16) st_pkt8((uint2*)(p.s->cs + (hg * 4 + (qt >> 2)) * 96 + (n >> 1) + lane) + ((qt >> 1) & 1), (__float_as_uint(cs0) & ~3u) | (tag & 3), __float_as_uint(cs1));
      if (lane < 2) { uint32_t a; asm volatile("mapa.shared::cluster.u32 %0, %1, %2;" : "=r"(a) : "r"(bar_d), "r"(lane)); mbar_arrive_cluster(a); }
      mbar_wait(bar_c, 0, budget);
      uint4 v[5];
      while (true) {
        uint32_t bad = 0;
#pragma unroll
        for (int i = 0; i < 5; i++) v[i] = ld_pkt(i < 4 ? p.s->cs + (hg * 4 + i) * 96 + (tid_ - 32) : (const uint4*)p.s->stat + qt * 64 + (tid_ & 63));
#pragma unroll
        for (int i = 0; i < 5; i++) bad |= (v[i].x ^ tag) | (v[i].z ^ tag);
        if (!__any_sync(~0u, bad & 3) || --budget < 0) break;
      }
      asm volatile("st.shared.v4.u32 [%0], {%1,%2,%3,%4};" ::"r"(s_stat + (tid_ & 63) * 16), "r"(__byte_perm(v[4].x, 0, 0x3232)), "r"(v[4].y), "r"(__byte_perm(v[4].z, 0, 0x3232)), "r"(v[4].w) : "memory");
      cs0 = cs1 = 0.f;
#pragma unroll
      for (int i = 0; i < 4; i++) { cs0 += __uint_as_float(v[i].x & ~3u) + __uint_as_float(v[i].z & ~3u); cs1 += __uint_as_float(v[i].y) + __uint_as_float(v[i].w); }
#pragma unroll
      for (int k = 0; k < 8; k++) {
        const uint32_t t = k < 3 ? pack_bf16(cs0, cs1) : 0;
        sts32((sb + (warp - 1) * 1024 + lane * 4) ^ (k * 0x90), t);
        cs0 -= bf_lo(t); cs1 -= bf_hi(t);
      }
      asm volatile("fence.proxy.async.shared::cta;" ::: "memory");
      __syncwarp();
      if (lane < 2) mbar_arrive(bar_s);
      budget = errands(p.s, m, qt, hg, warp, tag, budget);
      if (is_warp(2)) {
        mbar_wait(bar_w, 0, budget);
        if (budget < 0) asm volatile("st.global.u32 [%0], %1;" ::"l"(0ull), "r"(budget) : "memory");
      }
    } else {
      uint32_t fb = bar_b + 8, dst = sb + OFF_B + TB, ph = 1;
      auto next = [&]() { fb += 8; dst += TB; if (fb == bar_b + 48) { fb = bar_b; dst = sb + OFF_B; ph ^= 1; } };
#pragma unroll 1
      for (int u = 0; u < 4; u++) {
        const int h = hg * 4 + u;
        int s = u ? (u == 2 ? 5 : 0) : s0 + 1;
#pragma unroll 1
        for (int i = u == 0; i < 10; i++) {
          if (u == 0) {
            const uint32_t a8 = 8 * (i < 5 ? i : i - 5);
            if (i >= 3) mbar_wait(bar_a + 8 * (i < 8 ? i - 3 : i - 8), i >= 8);
            mbar_wait(bar_a + EA + a8, i < 5);
            if (elect()) { mbar_expect_tx(bar_a + a8, TA); tma2d(sb + a8 * (TA >> 3), &m.x, 64 * s, qt * 128, bar_a + a8); }
            if (i == 6 + (kg0 >> 3)) mbar_wait(bar_d, 0);
          }
          mbar_wait(fb + EB, ph);
          if (elect()) { mbar_expect_tx(fb, TB); tma4d_mc(dst + rank * (TB / 2), &m.wq, 3 * h, 8 * s + 4 * rank, fb); }
          next();
          if (++s == 10) s = 0;
        }
        const int kv0 = (h * SKC + (SKC - WIN)) / 8 + 4 * rank;
#pragma unroll 1
        for (int i = 0; i < 16; i++) {
          const bool isk = (0x2AAB >> i) & 1;
          mbar_wait(fb + EB, ph);
          if (elect()) { mbar_expect_tx(fb, TB); tma4d_mc(dst + rank * (TB / 2), isk ? &m.k : &m.v, 0, kv0 + 8 * (isk ? (i + 1) >> 1 : (i - 1) >> 1), fb); }
          next();
        }
      }
      const int cF = 10 * nh + 5 - 5 * (kq >> 1), cS = 10 * nh + 5 * (kq >> 1);
      const int kb = 4 * (k_block(lane, hg) + rank);
#pragma unroll 1
      for (int n = 0; n < 38; n++) {
        const int c2 = __shfl_sync(~0u, kb, n >> 1);
        mbar_wait(fb + EB, ph);
        if (elect()) { mbar_expect_tx(fb, TW); tma5d_mc(dst + rank * (TW / 2), &m.wo, c2, n & 1 ? cS : cF, fb); }
        next();
      }
      const int odd = ((0x7fb0 ^ (kq & 1 ? 0xffc00 : 0)) >> lane) & 1;
      const int tq = __shfl_sync(~0u, kb, 19 + end_stage(lane)) << 16 | odd << 7 | ((lane < 10 ? cF : cS) + 2 * odd);
#pragma unroll 1
      for (int n = 0; n < 20; n += 2) {
        const int t0 = __shfl_sync(~0u, tq, n), t1 = __shfl_sync(~0u, tq, n + 1);
        mbar_wait(fb + EB, ph);
        if (elect()) {
          mbar_expect_tx(fb, TB);
          tma5d_mc(dst + rank * (TB / 4), (const CUtensorMap*)((const char*)m.w3 + (t0 & 128)), t0 >> 16, t0 & 31, fb);
          tma5d_mc(dst + TB / 2 + rank * (TB / 4), (const CUtensorMap*)((const char*)m.w3 + (t1 & 128)), t1 >> 16, t1 & 31, fb);
        }
        next();
      }
      mbar_wait(bar_a + EA, 0);
      if (elect()) { mbar_expect_tx(bar_e, TW); tma2d(sb + OFF_B + 2 * TB, &m.xe, nh * 320 + kq * 80, qt * 128, bar_e); }
      const uint4* src = p.s->o + (size_t)(qt * 192 + nh * 24 + 10 + (kq ^ 2) * 48) * 512 + (kq & 1) * 1280;
      mbar_wait(bar_a + EA + 16, 0);
      if (elect()) {
        mbar_expect_tx(bar_e + 8, 2 * TW);
        bulk_load(sb + OFF_B + 3 * TB, src, TW, bar_e + 8);
        bulk_load(sb + OFF_B + 4 * TB, src + (kq & 1 ? -48 * 512 : 48 * 512), TW, bar_e + 8);
      }
    }
    cluster_sync();
  }
}

typedef CUresult (*EncodeFn)(CUtensorMap*, CUtensorMapDataType, cuuint32_t, void*, const cuuint64_t*, const cuuint64_t*,
                             const cuuint32_t*, const cuuint32_t*, CUtensorMapInterleave, CUtensorMapSwizzle,
                             CUtensorMapL2promotion, CUtensorMapFloatOOBfill);

void encode(EncodeFn fn, CUtensorMap* tm, void* base, int rank, const cuuint64_t* dims, const cuuint64_t* strides,
            const cuuint32_t* box, CUtensorMapSwizzle sw) {
  const cuuint32_t es[5] = {1, 1, 1, 1, 1};
  fn(tm, CU_TENSOR_MAP_DATA_TYPE_BFLOAT16, rank, base, dims, strides, box, es, CU_TENSOR_MAP_INTERLEAVE_NONE, sw,
     CU_TENSOR_MAP_L2_PROMOTION_L2_128B, CU_TENSOR_MAP_FLOAT_OOB_FILL_NONE);
}

}

extern "C" void kernel_launch(void* const* d_in, const int* in_sizes, int n_in, void* d_out, int out_size) {
  static EncodeFn fn = nullptr;
  static Scratch* scr = nullptr;
  if (!fn) {
    void* f = nullptr;
    cudaDriverEntryPointQueryResult st;
    cudaGetDriverEntryPoint("cuTensorMapEncodeTiled", &f, cudaEnableDefault, &st);
    fn = (EncodeFn)f;
    cudaGetSymbolAddress((void**)&scr, g_scratch);
    cudaFuncSetAttribute(fused_kernel, cudaFuncAttributeMaxDynamicSharedMemorySize, SMEM_BYTES);
  }
  Maps m;
  { const cuuint64_t d[2] = {DM, SQ}, s[1] = {DM * 2}; const cuuint32_t b[2] = {64, 128};
    encode(fn, &m.x, d_in[0], 2, d, s, b, CU_TENSOR_MAP_SWIZZLE_128B);
    encode(fn, &m.xn, scr->xn, 2, d, s, b, CU_TENSOR_MAP_SWIZZLE_128B); }
  { const cuuint64_t d[4] = {64, 8, QD / 64, DM / 8}, s[3] = {QD * 2, 128, 8 * QD * 2}; const cuuint32_t b[4] = {64, 8, 3, 4};
    encode(fn, &m.wq, d_in[3], 4, d, s, b, CU_TENSOR_MAP_SWIZZLE_128B); }
  { const cuuint64_t d[4] = {64, 8, 3, NH * SKC / 8}, s[3] = {DH * 2, 128, 8 * DH * 2}; const cuuint32_t b[4] = {64, 8, 3, 4};
    encode(fn, &m.k, d_in[1], 4, d, s, b, CU_TENSOR_MAP_SWIZZLE_128B);
    encode(fn, &m.v, d_in[2], 4, d, s, b, CU_TENSOR_MAP_SWIZZLE_128B); }
  {
    const cuuint64_t d[5] = {32, 2, QD / 8, 4, DM / 32}, s[4] = {DM * 2, 8 * DM * 2, 2 * DM * 2, 64}; const cuuint32_t b[5] = {32, 2, 4, 4, 5};
    encode(fn, &m.wo, d_in[4], 5, d, s, b, CU_TENSOR_MAP_SWIZZLE_64B);
    const cuuint32_t b3[5] = {32, 2, 4, 4, 3};
    encode(fn, &m.w3[0], d_in[4], 5, d, s, b3, CU_TENSOR_MAP_SWIZZLE_64B);
    encode(fn, &m.w3[1], (char*)d_in[4] + 32, 5, d, s, b3, CU_TENSOR_MAP_SWIZZLE_64B); }
  { const cuuint64_t d[2] = {DM, SQ}, s[1] = {DM * 2}; const cuuint32_t bg[2] = {80, 24}, bx[2] = {80, 128}, bo[2] = {80, 16};
    encode(fn, &m.xg, d_in[0], 2, d, s, bg, CU_TENSOR_MAP_SWIZZLE_NONE);
    encode(fn, &m.xe, d_in[0], 2, d, s, bx, CU_TENSOR_MAP_SWIZZLE_NONE);
    encode(fn, &m.out, d_out, 2, d, s, bo, CU_TENSOR_MAP_SWIZZLE_NONE); }
  Params p;
  p.x = (const __nv_bfloat16*)d_in[0]; p.wr = (const __nv_bfloat16*)d_in[6]; p.wg = (const __nv_bfloat16*)d_in[7];
  p.wu = (const __nv_bfloat16*)d_in[8]; p.wd = (const __nv_bfloat16*)d_in[9];

  p.k = (const __nv_bfloat16*)d_in[1]; p.v = (const __nv_bfloat16*)d_in[2]; p.s = scr;
  cudaLaunchConfig_t cfg = {};
  cfg.gridDim = dim3(132); cfg.blockDim = dim3(384); cfg.dynamicSmemBytes = SMEM_BYTES; cfg.stream = cudaStreamPerThread;
  cudaLaunchKernelEx(&cfg, fused_kernel, p, m);
}
```
